```python
import torch

def _softmax(x, axis=-1):
    return torch.softmax(x, dim=axis)
def _gelu(x):
    return torch.nn.functional.gelu(x, approximate="tanh")
def _silu(x):
    return torch.nn.functional.silu(x)
def _sigmoid(x):
    return torch.sigmoid(x)
def _layernorm(x, axis=-1, eps=1e-5):
    m = x.mean(dim=axis, keepdim=True)
    v = x.var(dim=axis, keepdim=True, unbiased=False)
    return (x - m) / torch.sqrt(v + eps)
def _scatter_add(tgt, idx, src, axis=0):
    return tgt.clone().index_add_(axis, idx, src)
def _segment_sum(src, seg, n):
    out = torch.zeros((n,) + src.shape[1:], dtype=src.dtype)
    return out.index_add_(0, seg, src)
def _pad(x, pw):
    flat = tuple(v for pair in reversed(pw) for v in pair)
    return torch.nn.functional.pad(x, flat)

kernel_name = 'recurrent_scan__ssm_conv_h3__dense_activation_gelu__prompt'

def setup_inputs():

    _w = (lambda a: (lambda t: t.to(torch.bfloat16) if t.is_floating_point() else t)(torch.as_tensor(a)))
    def _A_setup():
        B, S, D = 1, 2048, 640
        ks = 4
        return {
            "q": _w((lambda *s: torch.randn(*s, dtype=torch.bfloat16) * 0.05)(B, S, D)),
            "k": _w((lambda *s: torch.randn(*s, dtype=torch.bfloat16) * 0.8)(B, S, D)),
            "v": _w((lambda *s: torch.randn(*s, dtype=torch.bfloat16) * 0.8)(B, S, D)),
            "shift_k": _w((lambda *s: torch.randn(*s, dtype=torch.bfloat16) * 0.8)(D, ks) * 0.5),
            "ssm_k": _w((lambda *s: torch.randn(*s, dtype=torch.bfloat16) * 0.8)(D, S) * (1.0 / S ** 0.5)),
            "ssm_D": _w((lambda *s: torch.randn(*s, dtype=torch.bfloat16) * 0.8)(D)),
        }
    _A_in = _A_setup()

    def _B_setup():
        B, S, D, F = 1, 2048, 640, 1728
        return {
            "x": _w((lambda *s: torch.randn(*s, dtype=torch.bfloat16) * 0.05)(B, S, D)),
            "w1": _w((lambda *s: torch.randn(*s, dtype=torch.bfloat16) * 0.2)(D, F) * (D ** -0.5)),
            "b1": _w((lambda *s: torch.randn(*s, dtype=torch.bfloat16) * 0.2)(F) * 0.01),
            "w2": _w((lambda *s: torch.randn(*s, dtype=torch.bfloat16) * 0.2)(F, D) * (F ** -0.5)),
            "b2": _w((lambda *s: torch.randn(*s, dtype=torch.bfloat16) * 0.2)(D) * 0.01),
        }
    _B_in = _B_setup()

    return {
        "A_q": _A_in["q"],
        "A_k": _A_in["k"],
        "A_v": _A_in["v"],
        "A_shift_k": _A_in["shift_k"],
        "A_ssm_k": _A_in["ssm_k"],
        "A_ssm_D": _A_in["ssm_D"],
        "B_x": _B_in["x"],
        "B_w1": _B_in["w1"],
        "B_b1": _B_in["b1"],
        "B_w2": _B_in["w2"],
        "B_b2": _B_in["b2"],
    }

def reference(A_q, A_k, A_v, A_shift_k, A_ssm_k, A_ssm_D, B_x, B_w1, B_b1, B_w2, B_b2):
    def _A_ref(q, k, v, shift_k, ssm_k, ssm_D):
        B, S, D = q.shape
        ks = shift_k.shape[-1]
        k_pad = _pad(k, ((0, 0), (ks - 1, 0), (0, 0)))
        k_shift = torch.zeros_like(k)
        for t in range(ks):
            k_shift = k_shift + k_pad[:, t:t + S, :] * shift_k[:, ks - 1 - t][None, None, :]
        kv = k_shift * v
        L = 2 * S
        kv_pad = _pad(kv, ((0, 0), (0, S), (0, 0)))
        kf_pad = _pad(ssm_k, ((0, 0), (0, S)))
        kv_f = (lambda x, axes=(-2,-1): torch.fft.rfft2(x.float(), dim=axes))(kv_pad[:, None, :, :], axes=(1, 2))
        kf_f = (lambda x, axes=(-2,-1): torch.fft.rfft2(x.float(), dim=axes))(kf_pad[:, None, :], axes=(1, 2))
        kf_f = (lambda x, *d: x.permute(*d))(kf_f, 1, 2, 0)
        y_f = kv_f * kf_f[None, :, :, :]
        y = (lambda x, s, axes=(-2,-1): torch.fft.irfft2(x, s=s, dim=axes).to(torch.bfloat16))(y_f, (1, L), axes=(1, 2))[:, 0, :S, :]
        y = y + kv * ssm_D[None, None, :]
        return q * y

    def _B_ref(x, w1, b1, w2, b2):
        h = torch.einsum("bsd,df->bsf", x, w1) + b1
        h = _gelu(h)
        return torch.einsum("bsf,fd->bsd", h, w2) + b2

    x = A_q
    xn = _layernorm(x, axis=-1)
    s = _A_ref(xn, A_k, A_v, A_shift_k, A_ssm_k, A_ssm_D)
    g = _silu(_B_ref(xn, B_w1, B_b1, B_w2, B_b2))
    return x + s * g
```

```cpp
#include <cuda_runtime.h>
#include <cuda_bf16.h>
#include <cuda.h>
#include <stdint.h>

namespace h3 {

constexpr int SL = 2048, DM = 640, FF = 1728;
constexpr int NCTA = 128;

__device__ __align__(1024) __nv_bfloat16 g_h[SL * FF];
__device__ __align__(1024) __nv_bfloat16 g_kvT[DM * SL];
__device__ __align__(1024) __nv_bfloat16 g_yT[DM * SL];
__device__ __align__(1024) uint4 g_xch[NCTA * 6 * 256];
__device__ __align__(1024) uint2 g_stat[SL];
__device__ __align__(1024) uint2 g_cs[8 * 224];
__device__ __align__(1024) unsigned g_cnt[128 * 8];
__device__ __align__(1024) unsigned g_launch[NCTA * 8];

constexpr int CNT_KV = 24, CNT_H = 32, CNT_Y = 64;

constexpr int G1_STAGE = 16384 + 28672;
constexpr int G1_NS = 4;
constexpr int HST_WG = 28672;
constexpr int CV_XCH = 4368, CV_XD = 272;
constexpr int CV_RP = 528, CV_RW = 8 * CV_RP, CV_RWG = 4 * CV_RW;
constexpr int CV_R1 = 73728, CV_X3 = CV_R1 + 2 * CV_RWG, CV_XO = CV_X3 + CV_XCH, CV_R0 = CV_XO + 4 * CV_XCH + 48;
constexpr int KT = 184320, KT_CH = 8240, KT_O = 16, KT_E = 4144;
constexpr int KV_K = KT, KV_V = KT + 21504;
constexpr int G2_STAGE = 16384 + 20480;
constexpr int FIN_Q = 107520, FIN_Y = 130048;
constexpr int G2_A3 = 91136, G2_B3 = 163840;
constexpr int MISC = 226304;
constexpr int M_BX = MISC;
constexpr int M_RED = MISC + 3584 + 1024 + 320 + 32 + 16 + 56 * 8;
constexpr int M_STATS = MISC + 3584;
constexpr int M_B2 = M_STATS + 1024;
constexpr int M_D = M_B2 + 320;
constexpr int M_TASK = M_D + 32;
constexpr int M_BAR = M_TASK + 16;
constexpr int SMEM_BYTES = M_RED + 512;
__host__ __device__ constexpr int cv_r(int c) { return (c & 1) ? CV_R1 : CV_R0 + ((c >> 1) & 1) * CV_RWG; }
__host__ __device__ constexpr int cv_x(int c) { return c == 3 ? CV_X3 : CV_XO + (c == 4 ? 3 : c) * CV_XCH; }
__host__ __device__ constexpr int g2_a(int s) { return s < 2 ? s * G2_STAGE : (s == 2 ? KT : G2_A3); }
__host__ __device__ constexpr int g2_b(int s) { return s < 2 ? s * G2_STAGE + 16384 : (s == 2 ? KT + 16384 : G2_B3); }
static_assert(CV_R0 % 16 == 0 && 2 * G2_STAGE <= CV_R1 && 2 * HST_WG <= CV_R1 && CV_R1 + CV_RWG <= G2_A3 && G2_A3 + 16384 <= CV_X3, "smem");
static_assert(FIN_Q >= CV_X3 && FIN_Q + 20480 <= CV_R0 && FIN_Y >= CV_R0 && FIN_Y + 20480 <= G2_B3 && CV_R0 + 2 * CV_RWG <= G2_B3 && G2_B3 + 20480 <= KT, "smem");
static_assert(FIN_Y % 1024 == 0 && FIN_Q % 1024 == 0 && G2_A3 % 1024 == 0 && G2_B3 % 1024 == 0 && KT % 1024 == 0 && G1_NS * G1_STAGE <= KT, "smem");
static_assert(KT + 5 * KT_CH <= MISC && KV_V + 20480 <= MISC && KT + G2_STAGE <= MISC, "smem");
static_assert(M_RED == M_BAR + 56 * 8 && SMEM_BYTES <= 232448 && MISC % 512 == 0, "smem");
constexpr int B_F1 = 0, B_E1 = 4, B_G1DONE = 8, B_TBL = 9, B_HST = 10, B_CF = 12, B_F2 = 17, B_E2 = 21, B_FIN = 25, B_KRAW = 26,
              B_KVIN = 27, B_KT = 31, B_KT2 = 32, B_SD = 36, B_RF = 41, B_CVDONE = 46, B_RED = 47, B_HB = 48;
#define KV_KC0_ 5
#define Y3_KC 2
#define KV_MAP 0x3210
#define A_NB0 24
constexpr int KV_KC0 = KV_KC0_;

__device__ __forceinline__ uint32_t s32(const void* p) { return (uint32_t)__cvta_generic_to_shared(p); }
__device__ __forceinline__ void mbar_init(uint32_t a, int c) { asm volatile("mbarrier.init.shared::cta.b64 [%0], %1;" ::"r"(a), "r"(c)); }
__device__ __forceinline__ void mbar_expect(uint32_t a, int b) { asm volatile("mbarrier.arrive.expect_tx.shared::cta.b64 _, [%0], %1;" ::"r"(a), "r"(b) : "memory"); }
__device__ __forceinline__ void mbar_arrive(uint32_t a) { asm volatile("mbarrier.arrive.shared::cta.b64 _, [%0];" ::"r"(a) : "memory"); }
__device__ __forceinline__ void mbar_arrive_rank(uint32_t a, uint32_t rank) {
  asm volatile("{\n.reg .b32 ra;\nmapa.shared::cluster.u32 ra, %0, %1;\nmbarrier.arrive.shared::cluster.b64 _, [ra];\n}" ::"r"(a), "r"(rank) : "memory");
}
__device__ __forceinline__ bool spin_guard(uint32_t& t0, uint32_t) {
  uint32_t t; asm volatile("mov.u32 %0, %%clock;" : "=r"(t));
  if (t0 == 0) t0 = t | 1u; else if (t - t0 > 2000000000u) __trap();
  return false;
}
__device__ __forceinline__ void mbar_wait(uint32_t a, int ph) {
  uint32_t ok, t0 = 0;
  while (true) {
    asm volatile("{\n.reg .pred p;\nmbarrier.try_wait.parity.shared::cta.b64 p, [%1], %2;\nselp.u32 %0, 1, 0, p;\n}" : "=r"(ok) : "r"(a), "r"(ph) : "memory");
    if (ok) break;
    if (spin_guard(t0, (a >> 3) & 63)) break;
  }
}
__device__ __forceinline__ bool mbar_test(uint32_t a, int ph) {
  uint32_t ok;
  asm volatile("{\n.reg .pred p;\nmbarrier.test_wait.parity.shared::cta.b64 p, [%1], %2;\nselp.u32 %0, 1, 0, p;\n}" : "=r"(ok) : "r"(a), "r"(ph) : "memory");
  return __all_sync(0xffffffffu, ok);
}
__device__ __forceinline__ void tma2d(uint32_t dst, const CUtensorMap* tm, int c0, int c1, uint32_t bar) {
  asm volatile("cp.async.bulk.tensor.2d.shared::cluster.global.mbarrier::complete_tx::bytes [%0], [%1, {%3, %4}], [%2];"
               ::"r"(dst), "l"(tm), "r"(bar), "r"(c0), "r"(c1) : "memory");
}
__device__ __forceinline__ void tma2d_mc(uint32_t dst, const CUtensorMap* tm, int c0, int c1, uint32_t bar) {
  asm volatile("cp.async.bulk.tensor.2d.shared::cluster.global.mbarrier::complete_tx::bytes.multicast::cluster [%0], [%1, {%3, %4}], [%2], %5;"
               ::"r"(dst), "l"(tm), "r"(bar), "r"(c0), "r"(c1), "h"((uint16_t)3) : "memory");
}
__device__ __forceinline__ void tma2d_st(const CUtensorMap* tm, int c0, int c1, uint32_t src) {
  asm volatile("cp.async.bulk.tensor.2d.global.shared::cta.bulk_group [%0, {%2, %3}], [%1];" ::"l"(tm), "r"(src), "r"(c0), "r"(c1) : "memory");
}
__device__ __forceinline__ void bulk_g2s(uint32_t dst, const void* src, int bytes, uint32_t bar) {
  asm volatile("cp.async.bulk.shared::cluster.global.mbarrier::complete_tx::bytes [%0], [%1], %2, [%3];" ::"r"(dst), "l"(src), "r"(bytes), "r"(bar) : "memory");
}
__device__ __forceinline__ void bulk_s2g(void* dst, uint32_t src, int bytes) {
  asm volatile("cp.async.bulk.global.shared::cta.bulk_group [%0], [%1], %2;" ::"l"(dst), "r"(src), "r"(bytes) : "memory");
}
__device__ __forceinline__ void bulk_commit() { asm volatile("cp.async.bulk.commit_group;" ::: "memory"); }
__device__ __forceinline__ void bulk_wait_read() { asm volatile("cp.async.bulk.wait_group.read 0;" ::: "memory"); }
__device__ __forceinline__ void bulk_wait_all() { asm volatile("cp.async.bulk.wait_group 0;" ::: "memory"); }
__device__ __forceinline__ void fence_async_smem() { asm volatile("fence.proxy.async.shared::cta;" ::: "memory"); }
__device__ __forceinline__ void fence_async_all() { asm volatile("fence.proxy.async;" ::: "memory"); }
__device__ __forceinline__ void bar_sync(int id, int n) { asm volatile("bar.sync %0, %1;" ::"r"(id), "r"(n) : "memory"); }
__device__ __forceinline__ void bar_arrive(int id, int n) { asm volatile("bar.arrive %0, %1;" ::"r"(id), "r"(n) : "memory"); }
__device__ __forceinline__ void cluster_sync() {
  asm volatile("barrier.cluster.arrive.relaxed.aligned;\nbarrier.cluster.wait.aligned;" ::: "memory");
}
__device__ __forceinline__ void wg_fence() { asm volatile("wgmma.fence.sync.aligned;" ::: "memory"); }
__device__ __forceinline__ void wg_commit() { asm volatile("wgmma.commit_group.sync.aligned;" ::: "memory"); }
template <int N> __device__ __forceinline__ void wg_wait() { asm volatile("wgmma.wait_group.sync.aligned %0;" ::"n"(N) : "memory"); }
__device__ __forceinline__ uint64_t mkdesc(uint32_t addr, uint32_t lbo, uint32_t sbo, int sw) {
  return (uint64_t)((addr & 0x3FFFF) >> 4) | ((uint64_t)(lbo >> 4) << 16) | ((uint64_t)(sbo >> 4) << 32) | ((uint64_t)sw << 62);
}
__device__ __forceinline__ void signal_cnt(int idx) {
  fence_async_all();
  asm volatile("red.release.gpu.global.add.u32 [%0], 1;" ::"l"(&g_cnt[idx * 8]) : "memory");
}
__device__ __forceinline__ unsigned ld_acquire(const unsigned* p) {
  unsigned v; asm volatile("ld.acquire.gpu.global.u32 %0, [%1];" : "=r"(v) : "l"(p) : "memory"); return v;
}
__device__ __forceinline__ void wait_cnt(int idx, unsigned target) {
  uint32_t t0 = 0;
  while ((int)(ld_acquire(&g_cnt[idx * 8]) - target) < 0) {
    if (spin_guard(t0, 0x100 + idx)) break;
  }
  fence_async_all();
}
__device__ __forceinline__ uint4 ldg128(const void* p) {
  uint4 v; asm volatile("ld.global.nc.v4.b32 {%0,%1,%2,%3}, [%4];" : "=r"(v.x), "=r"(v.y), "=r"(v.z), "=r"(v.w) : "l"(p)); return v;
}
__device__ __forceinline__ uint4 ld_relaxed128(const void* p) {
  uint4 v; asm volatile("ld.relaxed.gpu.global.v4.b32 {%0,%1,%2,%3}, [%4];" : "=r"(v.x), "=r"(v.y), "=r"(v.z), "=r"(v.w) : "l"(p) : "memory"); return v;
}
__device__ __forceinline__ uint2 ld_relaxed64(const void* p) {
  uint2 v; asm volatile("ld.relaxed.gpu.global.v2.b32 {%0,%1}, [%2];" : "=r"(v.x), "=r"(v.y) : "l"(p) : "memory"); return v;
}
__device__ __forceinline__ uint32_t ld_relaxed32(const void* p) {
  uint32_t v; asm volatile("ld.relaxed.gpu.global.b32 %0, [%1];" : "=r"(v) : "l"(p) : "memory"); return v;
}
__device__ __forceinline__ void st_relaxed128(void* p, uint32_t x, uint32_t y, uint32_t z, uint32_t w) {
  asm volatile("st.relaxed.gpu.global.v4.b32 [%0], {%1,%2,%3,%4};" ::"l"(p), "r"(x), "r"(y), "r"(z), "r"(w) : "memory");
}
__device__ __forceinline__ uint4 ld_relaxed_b128(const void* p) {
  uint4 v; asm volatile("{\n.reg .b128 t;\nld.relaxed.gpu.global.b128 t, [%4];\nmov.b128 {%0,%1,%2,%3}, t;\n}" : "=r"(v.x), "=r"(v.y), "=r"(v.z), "=r"(v.w) : "l"(p) : "memory"); return v;
}
__device__ __forceinline__ void st_relaxed_b128(void* p, uint32_t x, uint32_t y, uint32_t z, uint32_t w) {
  asm volatile("{\n.reg .b128 t;\nmov.b128 t, {%1,%2,%3,%4};\nst.relaxed.gpu.global.b128 [%0], t;\n}" ::"l"(p), "r"(x), "r"(y), "r"(z), "r"(w) : "memory");
}
__device__ __forceinline__ void st_relaxed64(void* p, uint32_t x, uint32_t y) {
  asm volatile("st.relaxed.gpu.global.v2.b32 [%0], {%1,%2};" ::"l"(p), "r"(x), "r"(y) : "memory");
}
__device__ __forceinline__ void signal_relaxed(int idx) {
  asm volatile("red.relaxed.gpu.global.add.u32 [%0], 1;" ::"l"(&g_cnt[idx * 8]) : "memory");
}
__device__ __forceinline__ uint32_t nonzero_bits(float v) {
  float r; asm("add.rm.f32 %0, %1, 0f80000000;" : "=f"(r) : "f"(v)); return __float_as_uint(r);
}
__device__ __forceinline__ void prefetch_l2(const void* p, int bytes) { asm volatile("cp.async.bulk.prefetch.L2.global [%0], %1;" ::"l"(p), "r"(bytes) : "memory"); }
__device__ __forceinline__ void prefetch_map(const CUtensorMap* tm) { asm volatile("prefetch.tensormap [%0];" ::"l"(tm) : "memory"); }
__device__ __forceinline__ uint32_t pack_bf16(float lo, float hi) {
  uint32_t r; asm("cvt.rn.bf16x2.f32 %0, %1, %2;" : "=r"(r) : "f"(hi), "f"(lo)); return r;
}
__device__ __forceinline__ float bf_lo(uint32_t v) { return __uint_as_float(v << 16); }
__device__ __forceinline__ float bf_hi(uint32_t v) { return __uint_as_float(v & 0xFFFF0000u); }
__device__ __forceinline__ float bf_round(float x) { return __bfloat162float(__float2bfloat16_rn(x)); }
__device__ __forceinline__ uint32_t bmul2(uint32_t a, uint32_t b) { uint32_t r; asm("mul.rn.bf16x2 %0, %1, %2;" : "=r"(r) : "r"(a), "r"(b)); return r; }
__device__ __forceinline__ uint32_t badd2(uint32_t a, uint32_t b) { uint32_t r; asm("add.rn.bf16x2 %0, %1, %2;" : "=r"(r) : "r"(a), "r"(b)); return r; }
__device__ __forceinline__ uint32_t bsub2(uint32_t a, uint32_t b) { uint32_t r; asm("sub.rn.bf16x2 %0, %1, %2;" : "=r"(r) : "r"(a), "r"(b)); return r; }
__device__ __forceinline__ float tanh_fast(float x) { float r; asm("tanh.approx.f32 %0, %1;" : "=f"(r) : "f"(x)); return r; }
__device__ __forceinline__ uint32_t lds32(uint32_t a) { uint32_t v; asm volatile("ld.shared.b32 %0, [%1];" : "=r"(v) : "r"(a)); return v; }
__device__ __forceinline__ float2 lds64f(uint32_t a) { float2 v; asm volatile("ld.shared.v2.f32 {%0,%1}, [%2];" : "=f"(v.x), "=f"(v.y) : "r"(a)); return v; }
__device__ __forceinline__ float4 lds128f(uint32_t a) { float4 v; asm volatile("ld.shared.v4.f32 {%0,%1,%2,%3}, [%4];" : "=f"(v.x), "=f"(v.y), "=f"(v.z), "=f"(v.w) : "r"(a)); return v; }
__device__ __forceinline__ uint4 lds128(uint32_t a) { uint4 v; asm volatile("ld.shared.v4.b32 {%0,%1,%2,%3}, [%4];" : "=r"(v.x), "=r"(v.y), "=r"(v.z), "=r"(v.w) : "r"(a)); return v; }
__device__ __forceinline__ void sts32(uint32_t a, uint32_t x) { asm volatile("st.shared.b32 [%0], %1;" ::"r"(a), "r"(x) : "memory"); }
__device__ __forceinline__ void sts128(uint32_t a, uint32_t x, uint32_t y, uint32_t z, uint32_t w) { asm volatile("st.shared.v4.b32 [%0], {%1,%2,%3,%4};" ::"r"(a), "r"(x), "r"(y), "r"(z), "r"(w) : "memory"); }
__device__ __forceinline__ uint2 lds64(uint32_t a) { uint2 v; asm volatile("ld.shared.v2.b32 {%0,%1}, [%2];" : "=r"(v.x), "=r"(v.y) : "r"(a)); return v; }
__device__ __forceinline__ void sts64(uint32_t a, uint32_t x, uint32_t y) { asm volatile("st.shared.v2.b32 [%0], {%1,%2};" ::"r"(a), "r"(x), "r"(y) : "memory"); }
__device__ __forceinline__ void sts64f(uint32_t a, float x, float y) { asm volatile("st.shared.v2.f32 [%0], {%1,%2};" ::"r"(a), "f"(x), "f"(y) : "memory"); }
__device__ __forceinline__ void stsm4(uint32_t a, uint32_t r0, uint32_t r1, uint32_t r2, uint32_t r3) {
  asm volatile("stmatrix.sync.aligned.m8n8.x4.shared.b16 [%0], {%1,%2,%3,%4};" ::"r"(a), "r"(r0), "r"(r1), "r"(r2), "r"(r3) : "memory");
}
__device__ __forceinline__ void stsm2(uint32_t a, uint32_t r0, uint32_t r1) {
  asm volatile("stmatrix.sync.aligned.m8n8.x2.shared.b16 [%0], {%1,%2};" ::"r"(a), "r"(r0), "r"(r1) : "memory");
}
__device__ __forceinline__ void ldsm4(uint32_t a, uint32_t& r0, uint32_t& r1, uint32_t& r2, uint32_t& r3) {
  asm volatile("ldmatrix.sync.aligned.m8n8.x4.shared.b16 {%0,%1,%2,%3}, [%4];" : "=r"(r0), "=r"(r1), "=r"(r2), "=r"(r3) : "r"(a) : "memory");
}
__device__ __forceinline__ void ldsm4t(uint32_t a, uint32_t& r0, uint32_t& r1, uint32_t& r2, uint32_t& r3) {
  asm volatile("ldmatrix.sync.aligned.m8n8.x4.trans.shared.b16 {%0,%1,%2,%3}, [%4];" : "=r"(r0), "=r"(r1), "=r"(r2), "=r"(r3) : "r"(a) : "memory");
}
#define TS(i)

__device__ __forceinline__ void wg_ss_224(float (&d)[112], uint64_t da, uint64_t db, int sd) {
  asm volatile("{\n.reg .pred p;\nsetp.ne.b32 p, %114, 0;\n"
    "wgmma.mma_async.sync.aligned.m64n224k16.f32.bf16.bf16 {%0,%1,%2,%3,%4,%5,%6,%7,%8,%9,%10,%11,%12,%13,%14,%15,%16,%17,%18,%19,%20,%21,%22,%23,%24,%25,%26,%27,%28,%29,%30,%31,%32,%33,%34,%35,%36,%37,%38,%39,%40,%41,%42,%43,%44,%45,%46,%47,%48,%49,%50,%51,%52,%53,%54,%55,%56,%57,%58,%59,%60,%61,%62,%63,%64,%65,%66,%67,%68,%69,%70,%71,%72,%73,%74,%75,%76,%77,%78,%79,%80,%81,%82,%83,%84,%85,%86,%87,%88,%89,%90,%91,%92,%93,%94,%95,%96,%97,%98,%99,%100,%101,%102,%103,%104,%105,%106,%107,%108,%109,%110,%111}, %112, %113, p, 1, 1, 0, 1;\n}\n"
    : "+f"(d[0]),"+f"(d[1]),"+f"(d[2]),"+f"(d[3]),"+f"(d[4]),"+f"(d[5]),"+f"(d[6]),"+f"(d[7]),"+f"(d[8]),"+f"(d[9]),"+f"(d[10]),"+f"(d[11]),"+f"(d[12]),"+f"(d[13]),"+f"(d[14]),"+f"(d[15]),"+f"(d[16]),"+f"(d[17]),"+f"(d[18]),"+f"(d[19]),"+f"(d[20]),"+f"(d[21]),"+f"(d[22]),"+f"(d[23]),"+f"(d[24]),"+f"(d[25]),"+f"(d[26]),"+f"(d[27]),"+f"(d[28]),"+f"(d[29]),"+f"(d[30]),"+f"(d[31]),"+f"(d[32]),"+f"(d[33]),"+f"(d[34]),"+f"(d[35]),"+f"(d[36]),"+f"(d[37]),"+f"(d[38]),"+f"(d[39]),"+f"(d[40]),"+f"(d[41]),"+f"(d[42]),"+f"(d[43]),"+f"(d[44]),"+f"(d[45]),"+f"(d[46]),"+f"(d[47]),"+f"(d[48]),"+f"(d[49]),"+f"(d[50]),"+f"(d[51]),"+f"(d[52]),"+f"(d[53]),"+f"(d[54]),"+f"(d[55]),"+f"(d[56]),"+f"(d[57]),"+f"(d[58]),"+f"(d[59]),"+f"(d[60]),"+f"(d[61]),"+f"(d[62]),"+f"(d[63]),"+f"(d[64]),"+f"(d[65]),"+f"(d[66]),"+f"(d[67]),"+f"(d[68]),"+f"(d[69]),"+f"(d[70]),"+f"(d[71]),"+f"(d[72]),"+f"(d[73]),"+f"(d[74]),"+f"(d[75]),"+f"(d[76]),"+f"(d[77]),"+f"(d[78]),"+f"(d[79]),"+f"(d[80]),"+f"(d[81]),"+f"(d[82]),"+f"(d[83]),"+f"(d[84]),"+f"(d[85]),"+f"(d[86]),"+f"(d[87]),"+f"(d[88]),"+f"(d[89]),"+f"(d[90]),"+f"(d[91]),"+f"(d[92]),"+f"(d[93]),"+f"(d[94]),"+f"(d[95]),"+f"(d[96]),"+f"(d[97]),"+f"(d[98]),"+f"(d[99]),"+f"(d[100]),"+f"(d[101]),"+f"(d[102]),"+f"(d[103]),"+f"(d[104]),"+f"(d[105]),"+f"(d[106]),"+f"(d[107]),"+f"(d[108]),"+f"(d[109]),"+f"(d[110]),"+f"(d[111]) : "l"(da), "l"(db), "r"(sd));
}
__device__ __forceinline__ void wg_ss_160(float (&d)[80], uint64_t da, uint64_t db, int sd) {
  asm volatile("{\n.reg .pred p;\nsetp.ne.b32 p, %82, 0;\n"
    "wgmma.mma_async.sync.aligned.m64n160k16.f32.bf16.bf16 {%0,%1,%2,%3,%4,%5,%6,%7,%8,%9,%10,%11,%12,%13,%14,%15,%16,%17,%18,%19,%20,%21,%22,%23,%24,%25,%26,%27,%28,%29,%30,%31,%32,%33,%34,%35,%36,%37,%38,%39,%40,%41,%42,%43,%44,%45,%46,%47,%48,%49,%50,%51,%52,%53,%54,%55,%56,%57,%58,%59,%60,%61,%62,%63,%64,%65,%66,%67,%68,%69,%70,%71,%72,%73,%74,%75,%76,%77,%78,%79}, %80, %81, p, 1, 1, 0, 1;\n}\n"
    : "+f"(d[0]),"+f"(d[1]),"+f"(d[2]),"+f"(d[3]),"+f"(d[4]),"+f"(d[5]),"+f"(d[6]),"+f"(d[7]),"+f"(d[8]),"+f"(d[9]),"+f"(d[10]),"+f"(d[11]),"+f"(d[12]),"+f"(d[13]),"+f"(d[14]),"+f"(d[15]),"+f"(d[16]),"+f"(d[17]),"+f"(d[18]),"+f"(d[19]),"+f"(d[20]),"+f"(d[21]),"+f"(d[22]),"+f"(d[23]),"+f"(d[24]),"+f"(d[25]),"+f"(d[26]),"+f"(d[27]),"+f"(d[28]),"+f"(d[29]),"+f"(d[30]),"+f"(d[31]),"+f"(d[32]),"+f"(d[33]),"+f"(d[34]),"+f"(d[35]),"+f"(d[36]),"+f"(d[37]),"+f"(d[38]),"+f"(d[39]),"+f"(d[40]),"+f"(d[41]),"+f"(d[42]),"+f"(d[43]),"+f"(d[44]),"+f"(d[45]),"+f"(d[46]),"+f"(d[47]),"+f"(d[48]),"+f"(d[49]),"+f"(d[50]),"+f"(d[51]),"+f"(d[52]),"+f"(d[53]),"+f"(d[54]),"+f"(d[55]),"+f"(d[56]),"+f"(d[57]),"+f"(d[58]),"+f"(d[59]),"+f"(d[60]),"+f"(d[61]),"+f"(d[62]),"+f"(d[63]),"+f"(d[64]),"+f"(d[65]),"+f"(d[66]),"+f"(d[67]),"+f"(d[68]),"+f"(d[69]),"+f"(d[70]),"+f"(d[71]),"+f"(d[72]),"+f"(d[73]),"+f"(d[74]),"+f"(d[75]),"+f"(d[76]),"+f"(d[77]),"+f"(d[78]),"+f"(d[79]) : "l"(da), "l"(db), "r"(sd));
}
__device__ __forceinline__ void wg_rs_224(float (&d)[112], uint32_t a0, uint32_t a1, uint32_t a2, uint32_t a3, uint64_t db) {
  asm volatile("{\n.reg .pred p;\nsetp.ne.b32 p, 1, 0;\n"
    "wgmma.mma_async.sync.aligned.m64n224k16.f32.bf16.bf16 {%0,%1,%2,%3,%4,%5,%6,%7,%8,%9,%10,%11,%12,%13,%14,%15,%16,%17,%18,%19,%20,%21,%22,%23,%24,%25,%26,%27,%28,%29,%30,%31,%32,%33,%34,%35,%36,%37,%38,%39,%40,%41,%42,%43,%44,%45,%46,%47,%48,%49,%50,%51,%52,%53,%54,%55,%56,%57,%58,%59,%60,%61,%62,%63,%64,%65,%66,%67,%68,%69,%70,%71,%72,%73,%74,%75,%76,%77,%78,%79,%80,%81,%82,%83,%84,%85,%86,%87,%88,%89,%90,%91,%92,%93,%94,%95,%96,%97,%98,%99,%100,%101,%102,%103,%104,%105,%106,%107,%108,%109,%110,%111}, {%112,%113,%114,%115}, %116, p, 1, 1, 1;\n}\n"
    : "+f"(d[0]),"+f"(d[1]),"+f"(d[2]),"+f"(d[3]),"+f"(d[4]),"+f"(d[5]),"+f"(d[6]),"+f"(d[7]),"+f"(d[8]),"+f"(d[9]),"+f"(d[10]),"+f"(d[11]),"+f"(d[12]),"+f"(d[13]),"+f"(d[14]),"+f"(d[15]),"+f"(d[16]),"+f"(d[17]),"+f"(d[18]),"+f"(d[19]),"+f"(d[20]),"+f"(d[21]),"+f"(d[22]),"+f"(d[23]),"+f"(d[24]),"+f"(d[25]),"+f"(d[26]),"+f"(d[27]),"+f"(d[28]),"+f"(d[29]),"+f"(d[30]),"+f"(d[31]),"+f"(d[32]),"+f"(d[33]),"+f"(d[34]),"+f"(d[35]),"+f"(d[36]),"+f"(d[37]),"+f"(d[38]),"+f"(d[39]),"+f"(d[40]),"+f"(d[41]),"+f"(d[42]),"+f"(d[43]),"+f"(d[44]),"+f"(d[45]),"+f"(d[46]),"+f"(d[47]),"+f"(d[48]),"+f"(d[49]),"+f"(d[50]),"+f"(d[51]),"+f"(d[52]),"+f"(d[53]),"+f"(d[54]),"+f"(d[55]),"+f"(d[56]),"+f"(d[57]),"+f"(d[58]),"+f"(d[59]),"+f"(d[60]),"+f"(d[61]),"+f"(d[62]),"+f"(d[63]),"+f"(d[64]),"+f"(d[65]),"+f"(d[66]),"+f"(d[67]),"+f"(d[68]),"+f"(d[69]),"+f"(d[70]),"+f"(d[71]),"+f"(d[72]),"+f"(d[73]),"+f"(d[74]),"+f"(d[75]),"+f"(d[76]),"+f"(d[77]),"+f"(d[78]),"+f"(d[79]),"+f"(d[80]),"+f"(d[81]),"+f"(d[82]),"+f"(d[83]),"+f"(d[84]),"+f"(d[85]),"+f"(d[86]),"+f"(d[87]),"+f"(d[88]),"+f"(d[89]),"+f"(d[90]),"+f"(d[91]),"+f"(d[92]),"+f"(d[93]),"+f"(d[94]),"+f"(d[95]),"+f"(d[96]),"+f"(d[97]),"+f"(d[98]),"+f"(d[99]),"+f"(d[100]),"+f"(d[101]),"+f"(d[102]),"+f"(d[103]),"+f"(d[104]),"+f"(d[105]),"+f"(d[106]),"+f"(d[107]),"+f"(d[108]),"+f"(d[109]),"+f"(d[110]),"+f"(d[111]) : "r"(a0), "r"(a1), "r"(a2), "r"(a3), "l"(db));
}
__device__ __forceinline__ void wg_cv_0_0(float (&d)[128], uint32_t a0, uint32_t a1, uint32_t a2, uint32_t a3, uint64_t db) {
  asm volatile("{\n.reg .pred p;\nsetp.ne.b32 p, 0, 0;\n"
    "wgmma.mma_async.sync.aligned.m64n32k16.f32.bf16.bf16 {%0,%1,%2,%3,%4,%5,%6,%7,%8,%9,%10,%11,%12,%13,%14,%15}, {%16,%17,%18,%19}, %20, p, 1, 1, 0;\n}\n"
    : "+f"(d[0]),"+f"(d[1]),"+f"(d[2]),"+f"(d[3]),"+f"(d[4]),"+f"(d[5]),"+f"(d[6]),"+f"(d[7]),"+f"(d[8]),"+f"(d[9]),"+f"(d[10]),"+f"(d[11]),"+f"(d[12]),"+f"(d[13]),"+f"(d[14]),"+f"(d[15]) : "r"(a0), "r"(a1), "r"(a2), "r"(a3), "l"(db));
}
__device__ __forceinline__ void wg_cv_0_1(float (&d)[128], uint32_t a0, uint32_t a1, uint32_t a2, uint32_t a3, uint64_t db) {
  asm volatile("{\n.reg .pred p;\nsetp.ne.b32 p, 1, 0;\n"
    "wgmma.mma_async.sync.aligned.m64n32k16.f32.bf16.bf16 {%0,%1,%2,%3,%4,%5,%6,%7,%8,%9,%10,%11,%12,%13,%14,%15}, {%16,%17,%18,%19}, %20, p, 1, 1, 0;\n}\n"
    : "+f"(d[0]),"+f"(d[1]),"+f"(d[2]),"+f"(d[3]),"+f"(d[4]),"+f"(d[5]),"+f"(d[6]),"+f"(d[7]),"+f"(d[8]),"+f"(d[9]),"+f"(d[10]),"+f"(d[11]),"+f"(d[12]),"+f"(d[13]),"+f"(d[14]),"+f"(d[15]) : "r"(a0), "r"(a1), "r"(a2), "r"(a3), "l"(db));
}
__device__ __forceinline__ void wg_cv_1_0(float (&d)[128], uint32_t a0, uint32_t a1, uint32_t a2, uint32_t a3, uint64_t db) {
  asm volatile("{\n.reg .pred p;\nsetp.ne.b32 p, 0, 0;\n"
    "wgmma.mma_async.sync.aligned.m64n32k16.f32.bf16.bf16 {%0,%1,%2,%3,%4,%5,%6,%7,%8,%9,%10,%11,%12,%13,%14,%15}, {%16,%17,%18,%19}, %20, p, 1, 1, 0;\n}\n"
    : "+f"(d[16]),"+f"(d[17]),"+f"(d[18]),"+f"(d[19]),"+f"(d[20]),"+f"(d[21]),"+f"(d[22]),"+f"(d[23]),"+f"(d[24]),"+f"(d[25]),"+f"(d[26]),"+f"(d[27]),"+f"(d[28]),"+f"(d[29]),"+f"(d[30]),"+f"(d[31]) : "r"(a0), "r"(a1), "r"(a2), "r"(a3), "l"(db));
}
__device__ __forceinline__ void wg_cv_1_1(float (&d)[128], uint32_t a0, uint32_t a1, uint32_t a2, uint32_t a3, uint64_t db) {
  asm volatile("{\n.reg .pred p;\nsetp.ne.b32 p, 1, 0;\n"
    "wgmma.mma_async.sync.aligned.m64n32k16.f32.bf16.bf16 {%0,%1,%2,%3,%4,%5,%6,%7,%8,%9,%10,%11,%12,%13,%14,%15}, {%16,%17,%18,%19}, %20, p, 1, 1, 0;\n}\n"
    : "+f"(d[16]),"+f"(d[17]),"+f"(d[18]),"+f"(d[19]),"+f"(d[20]),"+f"(d[21]),"+f"(d[22]),"+f"(d[23]),"+f"(d[24]),"+f"(d[25]),"+f"(d[26]),"+f"(d[27]),"+f"(d[28]),"+f"(d[29]),"+f"(d[30]),"+f"(d[31]) : "r"(a0), "r"(a1), "r"(a2), "r"(a3), "l"(db));
}
__device__ __forceinline__ void wg_cv_2_0(float (&d)[128], uint32_t a0, uint32_t a1, uint32_t a2, uint32_t a3, uint64_t db) {
  asm volatile("{\n.reg .pred p;\nsetp.ne.b32 p, 0, 0;\n"
    "wgmma.mma_async.sync.aligned.m64n32k16.f32.bf16.bf16 {%0,%1,%2,%3,%4,%5,%6,%7,%8,%9,%10,%11,%12,%13,%14,%15}, {%16,%17,%18,%19}, %20, p, 1, 1, 0;\n}\n"
    : "+f"(d[32]),"+f"(d[33]),"+f"(d[34]),"+f"(d[35]),"+f"(d[36]),"+f"(d[37]),"+f"(d[38]),"+f"(d[39]),"+f"(d[40]),"+f"(d[41]),"+f"(d[42]),"+f"(d[43]),"+f"(d[44]),"+f"(d[45]),"+f"(d[46]),"+f"(d[47]) : "r"(a0), "r"(a1), "r"(a2), "r"(a3), "l"(db));
}
__device__ __forceinline__ void wg_cv_2_1(float (&d)[128], uint32_t a0, uint32_t a1, uint32_t a2, uint32_t a3, uint64_t db) {
  asm volatile("{\n.reg .pred p;\nsetp.ne.b32 p, 1, 0;\n"
    "wgmma.mma_async.sync.aligned.m64n32k16.f32.bf16.bf16 {%0,%1,%2,%3,%4,%5,%6,%7,%8,%9,%10,%11,%12,%13,%14,%15}, {%16,%17,%18,%19}, %20, p, 1, 1, 0;\n}\n"
    : "+f"(d[32]),"+f"(d[33]),"+f"(d[34]),"+f"(d[35]),"+f"(d[36]),"+f"(d[37]),"+f"(d[38]),"+f"(d[39]),"+f"(d[40]),"+f"(d[41]),"+f"(d[42]),"+f"(d[43]),"+f"(d[44]),"+f"(d[45]),"+f"(d[46]),"+f"(d[47]) : "r"(a0), "r"(a1), "r"(a2), "r"(a3), "l"(db));
}
__device__ __forceinline__ void wg_cv_3_0(float (&d)[128], uint32_t a0, uint32_t a1, uint32_t a2, uint32_t a3, uint64_t db) {
  asm volatile("{\n.reg .pred p;\nsetp.ne.b32 p, 0, 0;\n"
    "wgmma.mma_async.sync.aligned.m64n32k16.f32.bf16.bf16 {%0,%1,%2,%3,%4,%5,%6,%7,%8,%9,%10,%11,%12,%13,%14,%15}, {%16,%17,%18,%19}, %20, p, 1, 1, 0;\n}\n"
    : "+f"(d[48]),"+f"(d[49]),"+f"(d[50]),"+f"(d[51]),"+f"(d[52]),"+f"(d[53]),"+f"(d[54]),"+f"(d[55]),"+f"(d[56]),"+f"(d[57]),"+f"(d[58]),"+f"(d[59]),"+f"(d[60]),"+f"(d[61]),"+f"(d[62]),"+f"(d[63]) : "r"(a0), "r"(a1), "r"(a2), "r"(a3), "l"(db));
}
__device__ __forceinline__ void wg_cv_3_1(float (&d)[128], uint32_t a0, uint32_t a1, uint32_t a2, uint32_t a3, uint64_t db) {
  asm volatile("{\n.reg .pred p;\nsetp.ne.b32 p, 1, 0;\n"
    "wgmma.mma_async.sync.aligned.m64n32k16.f32.bf16.bf16 {%0,%1,%2,%3,%4,%5,%6,%7,%8,%9,%10,%11,%12,%13,%14,%15}, {%16,%17,%18,%19}, %20, p, 1, 1, 0;\n}\n"
    : "+f"(d[48]),"+f"(d[49]),"+f"(d[50]),"+f"(d[51]),"+f"(d[52]),"+f"(d[53]),"+f"(d[54]),"+f"(d[55]),"+f"(d[56]),"+f"(d[57]),"+f"(d[58]),"+f"(d[59]),"+f"(d[60]),"+f"(d[61]),"+f"(d[62]),"+f"(d[63]) : "r"(a0), "r"(a1), "r"(a2), "r"(a3), "l"(db));
}
__device__ __forceinline__ void wg_cv_4_0(float (&d)[128], uint32_t a0, uint32_t a1, uint32_t a2, uint32_t a3, uint64_t db) {
  asm volatile("{\n.reg .pred p;\nsetp.ne.b32 p, 0, 0;\n"
    "wgmma.mma_async.sync.aligned.m64n32k16.f32.bf16.bf16 {%0,%1,%2,%3,%4,%5,%6,%7,%8,%9,%10,%11,%12,%13,%14,%15}, {%16,%17,%18,%19}, %20, p, 1, 1, 0;\n}\n"
    : "+f"(d[64]),"+f"(d[65]),"+f"(d[66]),"+f"(d[67]),"+f"(d[68]),"+f"(d[69]),"+f"(d[70]),"+f"(d[71]),"+f"(d[72]),"+f"(d[73]),"+f"(d[74]),"+f"(d[75]),"+f"(d[76]),"+f"(d[77]),"+f"(d[78]),"+f"(d[79]) : "r"(a0), "r"(a1), "r"(a2), "r"(a3), "l"(db));
}
__device__ __forceinline__ void wg_cv_4_1(float (&d)[128], uint32_t a0, uint32_t a1, uint32_t a2, uint32_t a3, uint64_t db) {
  asm volatile("{\n.reg .pred p;\nsetp.ne.b32 p, 1, 0;\n"
    "wgmma.mma_async.sync.aligned.m64n32k16.f32.bf16.bf16 {%0,%1,%2,%3,%4,%5,%6,%7,%8,%9,%10,%11,%12,%13,%14,%15}, {%16,%17,%18,%19}, %20, p, 1, 1, 0;\n}\n"
    : "+f"(d[64]),"+f"(d[65]),"+f"(d[66]),"+f"(d[67]),"+f"(d[68]),"+f"(d[69]),"+f"(d[70]),"+f"(d[71]),"+f"(d[72]),"+f"(d[73]),"+f"(d[74]),"+f"(d[75]),"+f"(d[76]),"+f"(d[77]),"+f"(d[78]),"+f"(d[79]) : "r"(a0), "r"(a1), "r"(a2), "r"(a3), "l"(db));
}
__device__ __forceinline__ void wg_cv_5_0(float (&d)[128], uint32_t a0, uint32_t a1, uint32_t a2, uint32_t a3, uint64_t db) {
  asm volatile("{\n.reg .pred p;\nsetp.ne.b32 p, 0, 0;\n"
    "wgmma.mma_async.sync.aligned.m64n32k16.f32.bf16.bf16 {%0,%1,%2,%3,%4,%5,%6,%7,%8,%9,%10,%11,%12,%13,%14,%15}, {%16,%17,%18,%19}, %20, p, 1, 1, 0;\n}\n"
    : "+f"(d[80]),"+f"(d[81]),"+f"(d[82]),"+f"(d[83]),"+f"(d[84]),"+f"(d[85]),"+f"(d[86]),"+f"(d[87]),"+f"(d[88]),"+f"(d[89]),"+f"(d[90]),"+f"(d[91]),"+f"(d[92]),"+f"(d[93]),"+f"(d[94]),"+f"(d[95]) : "r"(a0), "r"(a1), "r"(a2), "r"(a3), "l"(db));
}
__device__ __forceinline__ void wg_cv_5_1(float (&d)[128], uint32_t a0, uint32_t a1, uint32_t a2, uint32_t a3, uint64_t db) {
  asm volatile("{\n.reg .pred p;\nsetp.ne.b32 p, 1, 0;\n"
    "wgmma.mma_async.sync.aligned.m64n32k16.f32.bf16.bf16 {%0,%1,%2,%3,%4,%5,%6,%7,%8,%9,%10,%11,%12,%13,%14,%15}, {%16,%17,%18,%19}, %20, p, 1, 1, 0;\n}\n"
    : "+f"(d[80]),"+f"(d[81]),"+f"(d[82]),"+f"(d[83]),"+f"(d[84]),"+f"(d[85]),"+f"(d[86]),"+f"(d[87]),"+f"(d[88]),"+f"(d[89]),"+f"(d[90]),"+f"(d[91]),"+f"(d[92]),"+f"(d[93]),"+f"(d[94]),"+f"(d[95]) : "r"(a0), "r"(a1), "r"(a2), "r"(a3), "l"(db));
}
__device__ __forceinline__ void wg_cv_6_0(float (&d)[128], uint32_t a0, uint32_t a1, uint32_t a2, uint32_t a3, uint64_t db) {
  asm volatile("{\n.reg .pred p;\nsetp.ne.b32 p, 0, 0;\n"
    "wgmma.mma_async.sync.aligned.m64n32k16.f32.bf16.bf16 {%0,%1,%2,%3,%4,%5,%6,%7,%8,%9,%10,%11,%12,%13,%14,%15}, {%16,%17,%18,%19}, %20, p, 1, 1, 0;\n}\n"
    : "+f"(d[96]),"+f"(d[97]),"+f"(d[98]),"+f"(d[99]),"+f"(d[100]),"+f"(d[101]),"+f"(d[102]),"+f"(d[103]),"+f"(d[104]),"+f"(d[105]),"+f"(d[106]),"+f"(d[107]),"+f"(d[108]),"+f"(d[109]),"+f"(d[110]),"+f"(d[111]) : "r"(a0), "r"(a1), "r"(a2), "r"(a3), "l"(db));
}
__device__ __forceinline__ void wg_cv_6_1(float (&d)[128], uint32_t a0, uint32_t a1, uint32_t a2, uint32_t a3, uint64_t db) {
  asm volatile("{\n.reg .pred p;\nsetp.ne.b32 p, 1, 0;\n"
    "wgmma.mma_async.sync.aligned.m64n32k16.f32.bf16.bf16 {%0,%1,%2,%3,%4,%5,%6,%7,%8,%9,%10,%11,%12,%13,%14,%15}, {%16,%17,%18,%19}, %20, p, 1, 1, 0;\n}\n"
    : "+f"(d[96]),"+f"(d[97]),"+f"(d[98]),"+f"(d[99]),"+f"(d[100]),"+f"(d[101]),"+f"(d[102]),"+f"(d[103]),"+f"(d[104]),"+f"(d[105]),"+f"(d[106]),"+f"(d[107]),"+f"(d[108]),"+f"(d[109]),"+f"(d[110]),"+f"(d[111]) : "r"(a0), "r"(a1), "r"(a2), "r"(a3), "l"(db));
}
__device__ __forceinline__ void wg_cv_7_0(float (&d)[128], uint32_t a0, uint32_t a1, uint32_t a2, uint32_t a3, uint64_t db) {
  asm volatile("{\n.reg .pred p;\nsetp.ne.b32 p, 0, 0;\n"
    "wgmma.mma_async.sync.aligned.m64n32k16.f32.bf16.bf16 {%0,%1,%2,%3,%4,%5,%6,%7,%8,%9,%10,%11,%12,%13,%14,%15}, {%16,%17,%18,%19}, %20, p, 1, 1, 0;\n}\n"
    : "+f"(d[112]),"+f"(d[113]),"+f"(d[114]),"+f"(d[115]),"+f"(d[116]),"+f"(d[117]),"+f"(d[118]),"+f"(d[119]),"+f"(d[120]),"+f"(d[121]),"+f"(d[122]),"+f"(d[123]),"+f"(d[124]),"+f"(d[125]),"+f"(d[126]),"+f"(d[127]) : "r"(a0), "r"(a1), "r"(a2), "r"(a3), "l"(db));
}
__device__ __forceinline__ void wg_cv_7_1(float (&d)[128], uint32_t a0, uint32_t a1, uint32_t a2, uint32_t a3, uint64_t db) {
  asm volatile("{\n.reg .pred p;\nsetp.ne.b32 p, 1, 0;\n"
    "wgmma.mma_async.sync.aligned.m64n32k16.f32.bf16.bf16 {%0,%1,%2,%3,%4,%5,%6,%7,%8,%9,%10,%11,%12,%13,%14,%15}, {%16,%17,%18,%19}, %20, p, 1, 1, 0;\n}\n"
    : "+f"(d[112]),"+f"(d[113]),"+f"(d[114]),"+f"(d[115]),"+f"(d[116]),"+f"(d[117]),"+f"(d[118]),"+f"(d[119]),"+f"(d[120]),"+f"(d[121]),"+f"(d[122]),"+f"(d[123]),"+f"(d[124]),"+f"(d[125]),"+f"(d[126]),"+f"(d[127]) : "r"(a0), "r"(a1), "r"(a2), "r"(a3), "l"(db));
}
__device__ __forceinline__ void conv_chain_a(float (&d)[128], const uint32_t (&a)[64], uint64_t db) {
  wg_cv_0_0(d, a[0], a[1], a[2], a[3], db + (uint64_t)(16));
  wg_cv_1_0(d, a[0], a[1], a[2], a[3], db + (uint64_t)(48));
  wg_cv_2_0(d, a[0], a[1], a[2], a[3], db + (uint64_t)(80));
  wg_cv_3_0(d, a[0], a[1], a[2], a[3], db + (uint64_t)(112));
  wg_cv_4_0(d, a[0], a[1], a[2], a[3], db + (uint64_t)(144));
  wg_cv_5_0(d, a[0], a[1], a[2], a[3], db + (uint64_t)(176));
  wg_cv_6_0(d, a[0], a[1], a[2], a[3], db + (uint64_t)(208));
  wg_cv_7_0(d, a[0], a[1], a[2], a[3], db + (uint64_t)(240));
  wg_cv_0_1(d, a[4], a[5], a[6], a[7], db + (uint64_t)(0));
  wg_cv_1_1(d, a[4], a[5], a[6], a[7], db + (uint64_t)(32));
  wg_cv_2_1(d, a[4], a[5], a[6], a[7], db + (uint64_t)(64));
  wg_cv_3_1(d, a[4], a[5], a[6], a[7], db + (uint64_t)(96));
  wg_cv_4_1(d, a[4], a[5], a[6], a[7], db + (uint64_t)(128));
  wg_cv_5_1(d, a[4], a[5], a[6], a[7], db + (uint64_t)(160));
  wg_cv_6_1(d, a[4], a[5], a[6], a[7], db + (uint64_t)(192));
  wg_cv_7_1(d, a[4], a[5], a[6], a[7], db + (uint64_t)(224));
  wg_cv_1_1(d, a[8], a[9], a[10], a[11], db + (uint64_t)(16));
  wg_cv_2_1(d, a[8], a[9], a[10], a[11], db + (uint64_t)(48));
  wg_cv_3_1(d, a[8], a[9], a[10], a[11], db + (uint64_t)(80));
  wg_cv_4_1(d, a[8], a[9], a[10], a[11], db + (uint64_t)(112));
  wg_cv_5_1(d, a[8], a[9], a[10], a[11], db + (uint64_t)(144));
  wg_cv_6_1(d, a[8], a[9], a[10], a[11], db + (uint64_t)(176));
  wg_cv_7_1(d, a[8], a[9], a[10], a[11], db + (uint64_t)(208));
  wg_cv_1_1(d, a[12], a[13], a[14], a[15], db + (uint64_t)(0));
  wg_cv_2_1(d, a[12], a[13], a[14], a[15], db + (uint64_t)(32));
  wg_cv_3_1(d, a[12], a[13], a[14], a[15], db + (uint64_t)(64));
  wg_cv_4_1(d, a[12], a[13], a[14], a[15], db + (uint64_t)(96));
  wg_cv_5_1(d, a[12], a[13], a[14], a[15], db + (uint64_t)(128));
  wg_cv_6_1(d, a[12], a[13], a[14], a[15], db + (uint64_t)(160));
  wg_cv_7_1(d, a[12], a[13], a[14], a[15], db + (uint64_t)(192));
  wg_cv_2_1(d, a[16], a[17], a[18], a[19], db + (uint64_t)(16));
  wg_cv_3_1(d, a[16], a[17], a[18], a[19], db + (uint64_t)(48));
  wg_cv_4_1(d, a[16], a[17], a[18], a[19], db + (uint64_t)(80));
  wg_cv_5_1(d, a[16], a[17], a[18], a[19], db + (uint64_t)(112));
  wg_cv_6_1(d, a[16], a[17], a[18], a[19], db + (uint64_t)(144));
  wg_cv_7_1(d, a[16], a[17], a[18], a[19], db + (uint64_t)(176));
  wg_cv_2_1(d, a[20], a[21], a[22], a[23], db + (uint64_t)(0));
  wg_cv_3_1(d, a[20], a[21], a[22], a[23], db + (uint64_t)(32));
  wg_cv_4_1(d, a[20], a[21], a[22], a[23], db + (uint64_t)(64));
  wg_cv_5_1(d, a[20], a[21], a[22], a[23], db + (uint64_t)(96));
  wg_cv_6_1(d, a[20], a[21], a[22], a[23], db + (uint64_t)(128));
  wg_cv_7_1(d, a[20], a[21], a[22], a[23], db + (uint64_t)(160));
  wg_cv_3_1(d, a[24], a[25], a[26], a[27], db + (uint64_t)(16));
  wg_cv_4_1(d, a[24], a[25], a[26], a[27], db + (uint64_t)(48));
  wg_cv_5_1(d, a[24], a[25], a[26], a[27], db + (uint64_t)(80));
  wg_cv_6_1(d, a[24], a[25], a[26], a[27], db + (uint64_t)(112));
  wg_cv_7_1(d, a[24], a[25], a[26], a[27], db + (uint64_t)(144));
  wg_cv_3_1(d, a[28], a[29], a[30], a[31], db + (uint64_t)(0));
  wg_cv_4_1(d, a[28], a[29], a[30], a[31], db + (uint64_t)(32));
  wg_cv_5_1(d, a[28], a[29], a[30], a[31], db + (uint64_t)(64));
  wg_cv_6_1(d, a[28], a[29], a[30], a[31], db + (uint64_t)(96));
  wg_cv_7_1(d, a[28], a[29], a[30], a[31], db + (uint64_t)(128));
  wg_cv_4_1(d, a[32], a[33], a[34], a[35], db + (uint64_t)(16));
  wg_cv_5_1(d, a[32], a[33], a[34], a[35], db + (uint64_t)(48));
  wg_cv_6_1(d, a[32], a[33], a[34], a[35], db + (uint64_t)(80));
  wg_cv_7_1(d, a[32], a[33], a[34], a[35], db + (uint64_t)(112));
  wg_cv_4_1(d, a[36], a[37], a[38], a[39], db + (uint64_t)(0));
  wg_cv_5_1(d, a[36], a[37], a[38], a[39], db + (uint64_t)(32));
  wg_cv_6_1(d, a[36], a[37], a[38], a[39], db + (uint64_t)(64));
  wg_cv_7_1(d, a[36], a[37], a[38], a[39], db + (uint64_t)(96));
}
__device__ __forceinline__ void conv_chain_b(float (&d)[128], const uint32_t (&a)[64], uint64_t db) {
  wg_cv_5_1(d, a[40], a[41], a[42], a[43], db + (uint64_t)(16));
  wg_cv_6_1(d, a[40], a[41], a[42], a[43], db + (uint64_t)(48));
  wg_cv_7_1(d, a[40], a[41], a[42], a[43], db + (uint64_t)(80));
  wg_cv_5_1(d, a[44], a[45], a[46], a[47], db + (uint64_t)(0));
  wg_cv_6_1(d, a[44], a[45], a[46], a[47], db + (uint64_t)(32));
  wg_cv_7_1(d, a[44], a[45], a[46], a[47], db + (uint64_t)(64));
  wg_cv_6_1(d, a[48], a[49], a[50], a[51], db + (uint64_t)(16));
  wg_cv_7_1(d, a[48], a[49], a[50], a[51], db + (uint64_t)(48));
  wg_cv_6_1(d, a[52], a[53], a[54], a[55], db + (uint64_t)(0));
  wg_cv_7_1(d, a[52], a[53], a[54], a[55], db + (uint64_t)(32));
  wg_cv_7_1(d, a[56], a[57], a[58], a[59], db + (uint64_t)(16));
  wg_cv_7_1(d, a[60], a[61], a[62], a[63], db + (uint64_t)(0));
}

struct Params {
  const __nv_bfloat16 *q, *k, *v, *shift_k, *ssm_k, *ssm_D, *w1, *b1, *w2, *b2;
  __nv_bfloat16* out;
};

__global__ void __cluster_dims__(2, 1, 1) __launch_bounds__(384, 1)
h3_kernel(const __grid_constant__ CUtensorMap tmQA, const __grid_constant__ CUtensorMap tmW1, const __grid_constant__ CUtensorMap tmH,
          const __grid_constant__ CUtensorMap tmH32, const __grid_constant__ CUtensorMap tmW2,
          const __grid_constant__ CUtensorMap tmQE, const __grid_constant__ CUtensorMap tmY, const __grid_constant__ CUtensorMap tmOut,
          const __grid_constant__ CUtensorMap tmK, const __grid_constant__ CUtensorMap tmK36, const __grid_constant__ CUtensorMap tmV,
          const __grid_constant__ CUtensorMap tmKVT, const Params P) {
  extern __shared__ __align__(1024) uint8_t smem_raw[];
  const uint32_t sb = s32(smem_raw);
  uint8_t* sg = smem_raw;
  const int tid = threadIdx.x, lane = tid & 31;
  const int warp = __shfl_sync(0xffffffffu, tid >> 5, 0);
  const int cta = blockIdx.x;
  const int rank = cta & 1, pr = cta >> 1, j = pr >> 3, rb = 2 * (pr & 7) + rank;
  const int nt = j & 3, kh = j >> 2;
  const int c1 = (j < 4 ? 224 * j : 864 + 224 * (j - 4)) - (j == 7 ? 32 : 0);
  const uint32_t bar = sb + M_BAR;
  auto BAR = [&](int i) { return bar + 8 * i; };

  if (tid == 256) {
    if (sb & 1023) __trap();
    for (int s = 0; s < G1_NS; s++) { mbar_init(BAR(B_F1 + s), 1); mbar_init(BAR(B_E1 + s), 4); }
    mbar_init(BAR(B_G1DONE), 1); mbar_init(BAR(B_TBL), 1);
    for (int b = 0; b < 4; b++) mbar_init(BAR(B_HB + b), 8);
    for (int c = 0; c < 5; c++) mbar_init(BAR(B_CF + c), 1);
    for (int s = 0; s < 4; s++) { mbar_init(BAR(B_F2 + s), 1); mbar_init(BAR(B_E2 + s), 4); }
    mbar_init(BAR(B_KRAW), 1); mbar_init(BAR(B_FIN), 2);
    for (int c = 0; c < 5; c++) { mbar_init(BAR(B_SD + c), c == 3 ? 1 : 4); mbar_init(BAR(B_RF + c), c == 3 ? 1 : 4); }
    for (int i = 0; i < 4; i++) mbar_init(BAR(B_KVIN + i), 1);
    mbar_init(BAR(B_RED), 8);
    mbar_init(BAR(B_KT), 2); mbar_init(BAR(B_KT2), 3);
    sts32(sb + M_TASK, 0u); sts32(sb + M_TASK + 4, 0u);
    asm volatile("fence.mbarrier_init.release.cluster;" ::: "memory");
    TS(0);
    for (int s = 0; s < G1_NS; s++) {
      mbar_expect(BAR(B_F1 + s), G1_STAGE);
      tma2d(sb + s * G1_STAGE, &tmQA, s * 64, rb * 128, BAR(B_F1 + s));
    }
    prefetch_map(&tmW1);
  }
  __syncthreads();
  cluster_sync();

  if (warp >= 8) {
    asm volatile("setmaxnreg.dec.sync.aligned.u32 56;");
    if (warp == 8) {
      if (lane == 0) {
        for (int kc = 0; kc < 10; kc++) {
          const int s = kc & 3;
          const uint32_t st = sb + s * G1_STAGE;
          if (kc >= G1_NS) {
            mbar_wait(BAR(B_E1 + s), ((kc >> 2) - 1) & 1);
            if (kc < 8) TS(48 + kc);
            mbar_expect(BAR(B_F1 + s), G1_STAGE);
            tma2d(st, &tmQA, kc * 64, rb * 128, BAR(B_F1 + s));
          }
          const int g0 = rank ? 4 : 0, g1 = rank ? 7 : 4;
          for (int g = g0; g < g1; g++) tma2d_mc(st + 16384 + g * 4096, &tmW1, c1 + g * 32, kc * 64, BAR(B_F1 + s));
          if (kc == 0) { prefetch_map(&tmK36); prefetch_map(&tmK); prefetch_map(&tmV); prefetch_map(&tmKVT); }
          for (int qd = 0; qd < 4; qd++) {
            if (kc != KV_KC0 + ((KV_MAP >> (4 * qd)) & 15)) continue;
            const int tb = cta & 15, cb = cta >> 4;
            mbar_expect(BAR(B_KVIN + qd), qd ? 10240 : 10880);
            if (qd == 0) tma2d(sb + KV_K, &tmK36, cb * 80, tb * 128 - 4, BAR(B_KVIN));
            else tma2d(sb + KV_K + 640 + qd * 5120, &tmK, cb * 80, tb * 128 + qd * 32, BAR(B_KVIN + qd));
            tma2d(sb + KV_V + qd * 5120, &tmV, cb * 80, tb * 128 + qd * 32, BAR(B_KVIN + qd));
          }
          if (kc == 7) {
            prefetch_map(&tmH); prefetch_map(&tmW2); prefetch_map(&tmQE); prefetch_map(&tmY); prefetch_map(&tmOut); prefetch_map(&tmH32);
          }
#define PF_KC 11
          if (kc == PF_KC) prefetch_l2(P.ssm_k + (size_t)cta * 5 * SL, 5 * SL * 2);
        }
        if (PF_KC == 10) prefetch_l2(P.ssm_k + (size_t)cta * 5 * SL, 5 * SL * 2);
      }
      __syncwarp();
      const unsigned ep = __ldcg(&g_launch[cta * 8]) + 1;
      uint32_t b2v[3];
#pragma unroll
      for (int i = 0; i < 3; i++) b2v[i] = __bfloat16_as_ushort(P.b2[nt * 160 + kh * 80 + min(lane + 32 * i, 79)]);
      if (lane == 0) {
        const unsigned ep1 = ep;
        wait_cnt(CNT_KV + (cta >> 4), 16 * ep1);
        TS(38);
        mbar_wait(BAR(B_G1DONE), 0);
        for (int c = 0; c < 5; c++) {
          mbar_expect(BAR(B_CF + c), 4096);
          bulk_g2s(sb + cv_x(c) + CV_XD, g_kvT + (size_t)(cta * 5 + c) * SL, 4096, BAR(B_CF + c));
        }
        prefetch_l2(P.w2 + (size_t)cta * (FF * DM / NCTA), FF * DM / NCTA * 2);
      }
      __syncwarp();
      if (lane == 0) {
        for (int b = 0; b < 4; b++) {
          mbar_wait(BAR(B_HB + b), 0);
          if (b == 3 && (j == 3 || j == 6)) break;
          for (int hw = 0; hw < 2; hw++) tma2d_st(b < 3 ? &tmH : &tmH32, c1 + b * 64, rb * 128 + hw * 64, sb + hw * HST_WG + b * 8192);
        }
        bulk_commit();
      }
      __syncwarp();
      if (lane == 0) {
        const unsigned ep1 = ep;
        bulk_wait_read();
        for (int i = 0; i < 6; i++) { const int e = i < 4 ? (i & 1) : 3; mbar_arrive_rank(BAR(B_E2 + e), 0); mbar_arrive_rank(BAR(B_E2 + e), 1); }
        bulk_wait_all();
        signal_relaxed(CNT_H + rb * 2 + kh);
        TS(37);
      }
      __syncwarp();
      auto g2_load = [&](int kc) {
        const int s = kc & 3;
        mbar_wait(BAR(B_E2 + s), (kc >> 2) & 1);
        const uint32_t st = sb + g2_a(s), sw = sb + g2_b(s);
        mbar_expect(BAR(B_F2 + s), G2_STAGE);
        tma2d(st, &tmH, kh * 864 + kc * 64, rb * 128, BAR(B_F2 + s));
        tma2d(st + 8192, &tmH, kh * 864 + kc * 64, rb * 128 + 64, BAR(B_F2 + s));
        const int sp = (kc & 1) ? 2 : 3;
        const int g0 = rank ? sp : 0, g1 = rank ? 5 : sp;
        for (int g = g0; g < g1; g++) tma2d_mc(sw + g * 4096, &tmW2, nt * 160 + g * 32, kh * 864 + kc * 64, BAR(B_F2 + s));
      };
      if (lane == 0) {
        wait_cnt(CNT_H + rb * 2 + kh, 4 * ep);
        TS(39);
        g2_load(0); g2_load(1); g2_load(3); g2_load(2);
      }
      __syncwarp();
      {
        uint32_t t0 = 0;
        const uint4* sp = reinterpret_cast<const uint4*>(g_stat + rb * 128) + lane * 2;
        uint4 sa, sc;
        while (true) {
          sa = ld_relaxed128(sp); sc = ld_relaxed128(sp + 1);
          if (__all_sync(0xffffffffu, sa.y == ep && sa.w == ep && sc.y == ep && sc.w == ep)) break;
          if (spin_guard(t0, 0x1ff)) break;
        }
        const uint32_t ma = sb + M_STATS + lane * 32;
        sts128(ma, sa.x, __float_as_uint(1.f / bf_hi(sa.x)), sa.z, __float_as_uint(1.f / bf_hi(sa.z)));
        sts128(ma + 16, sc.x, __float_as_uint(1.f / bf_hi(sc.x)), sc.z, __float_as_uint(1.f / bf_hi(sc.z)));
#pragma unroll
        for (int i = 0; i < 3; i++) if (lane + 32 * i < 80) *reinterpret_cast<float*>(sg + M_B2 + (lane + 32 * i) * 4) = bf_lo(b2v[i]);
        __syncwarp();
        if (lane == 0) { mbar_arrive(BAR(B_TBL)); TS(36); }
      }
      if (lane == 0) {
        for (int kc = 4; kc < 14; kc++) g2_load(kc);
        g_launch[cta * 8] = ep;
      }
      __syncwarp();
    } else {
      const int aw = warp - 9, at = tid - 288;
      const unsigned ep1 = __ldcg(&g_launch[cta * 8]) + 1;
      const int tb = cta & 15, cb = cta >> 4;
      const uint32_t dvx = (uint32_t)__bfloat16_as_ushort(P.ssm_D[cta * 5 + min(lane, 4)]) * 0x10001u;
      const int tg = at >= 40, cp = at - (tg ? 40 : 0);
      uint32_t w0, w1, w2, w3;
      {
        const int c = cb * 80 + 2 * min(cp, 39);
        const uint2 sa = __ldg(reinterpret_cast<const uint2*>(P.shift_k + c * 4));
        const uint2 sc = __ldg(reinterpret_cast<const uint2*>(P.shift_k + c * 4 + 4));
        w0 = __byte_perm(sa.x, sc.x, 0x5410); w1 = __byte_perm(sa.x, sc.x, 0x7632);
        w2 = __byte_perm(sa.y, sc.y, 0x5410); w3 = __byte_perm(sa.y, sc.y, 0x7632);
      }
#pragma unroll 1
      for (int qd = 0; qd < 4; qd++) {
        uint32_t o[16];
        mbar_wait(BAR(B_KVIN + qd), 0);
        if (at == 0 && qd == 0) TS(33);
        if (at == 0 && qd == 3) TS(58);
        if (at < 80) {
          const uint32_t kb = sb + KV_K + 160 + (qd * 32 + tg * 16) * 160 + cp * 4, vb = kb + (KV_V - KV_K - 160);
          uint32_t k0 = lds32(kb), k1 = lds32(kb + 160), k2 = lds32(kb + 320);
#pragma unroll
          for (int i = 0; i < 16; i++) {
            const uint32_t k3 = lds32(kb + (i + 3) * 160), vv = lds32(vb + i * 160);
            uint32_t acc = bmul2(k0, w3);
            acc = badd2(acc, bmul2(k1, w2));
            acc = badd2(acc, bmul2(k2, w1));
            acc = badd2(acc, bmul2(k3, w0));
            o[i] = bmul2(acc, vv);
            k0 = k1; k1 = k2; k2 = k3;
          }
        }
        bar_sync(2, 96);
        const uint32_t stg = sb + KV_V + qd * 5120;
        if (at < 80) {
#pragma unroll
          for (int hh = 0; hh < 2; hh++) {
            const uint32_t* p = o + 8 * hh;
            const uint32_t a = stg + cp * 128 + (((tg * 2 + hh) ^ (cp & 3)) << 4), hf = (cp & 4) << 4;
            const uint32_t s0 = (cp & 4) ? 0x7632 : 0x5410, s1 = s0 ^ 0x2222;
            sts128(a + hf, __byte_perm(p[0], p[1], s0), __byte_perm(p[2], p[3], s0), __byte_perm(p[4], p[5], s0), __byte_perm(p[6], p[7], s0));
            sts128(a + (hf ^ 64), __byte_perm(p[0], p[1], s1), __byte_perm(p[2], p[3], s1), __byte_perm(p[4], p[5], s1), __byte_perm(p[6], p[7], s1));
          }
        }
        fence_async_smem();
        bar_sync(2, 96);
        if (at == 32) { tma2d_st(&tmKVT, tb * 128 + qd * 32, cb * 80, stg); bulk_commit(); }
      }
      if (aw == 1) {
        if (lane == 0) {
          bulk_wait_read();
          mbar_expect(BAR(B_KRAW), 5 * 4096);
          for (int c = 0; c < 5; c++) bulk_g2s(sb + KT + c * KT_CH + KT_E, P.ssm_k + (size_t)(cta * 5 + c) * SL, 4096, BAR(B_KRAW));
          bulk_wait_all();
          signal_relaxed(CNT_KV + cb);
          TS(34);
        }
        __syncwarp();
      }
      mbar_wait(BAR(B_KRAW), 0);
      for (int c = aw; c < 5; c += 3) {
        const uint32_t kb = sb + KT + c * KT_CH;
        if (lane < 4) { sts32(kb + lane * 4, 0u); sts32(kb + KT_E - 16 + lane * 4, 0u); }
        uint32_t carry = 0u;
#pragma unroll 1
        for (int ib = 0; ib < 8; ib += 4) {
          uint4 r[4];
#pragma unroll
          for (int it = 0; it < 4; it++) r[it] = lds128(kb + KT_E + ((ib + it) * 32 + lane) * 16);
#pragma unroll
          for (int it = 0; it < 4; it++) {
            const uint32_t off = ((ib + it) * 32 + lane) * 16;
            uint32_t pv = __shfl_sync(0xffffffffu, lane == 31 ? carry : r[it].w, lane - 1);
            carry = r[it].w;
            sts128(kb + KT_E + off, __byte_perm(r[it].x, 0, 0x1032), __byte_perm(r[it].y, 0, 0x1032), __byte_perm(r[it].z, 0, 0x1032), __byte_perm(r[it].w, 0, 0x1032));
            sts128(kb + KT_O + off, __byte_perm(r[it].x, pv, 0x7610), __byte_perm(r[it].y, r[it].x, 0x7610), __byte_perm(r[it].z, r[it].y, 0x7610), __byte_perm(r[it].w, r[it].z, 0x7610));
          }
        }
        __syncwarp();
        if (lane == 0) { mbar_arrive(BAR(c < 2 ? B_KT : B_KT2)); if (c == 0) TS(35); if (c == 4) TS(31); }
      }
#pragma unroll 1
      for (int k = aw; k < 16; k += 3) {
        const int c = k < 12 ? k >> 2 : 4, t = (k & 3) * 32 + lane;
        const uint32_t cbx = sb + cv_x(c) + CV_XD + t * 32, ra = sb + cv_r(c) + t * 4;
        const uint32_t dd = __shfl_sync(0xffffffffu, dvx, c);
        mbar_wait(BAR(B_SD + c), 0);
        uint32_t o0[4], o1[4];
#pragma unroll
        for (int hb = 0; hb < 2; hb++) {
          uint32_t p[4][4];
#pragma unroll
          for (int e = 0; e < 4; e++)
#pragma unroll
            for (int i = 0; i < 4; i++) p[e][i] = lds32(ra + (4 * hb + e) * CV_RP + i * CV_RW);
#pragma unroll
          for (int e = 0; e < 4; e += 2) {
            o0[2 * hb + e / 2] = pack_bf16((bf_lo(p[e][0]) + bf_lo(p[e][1])) + (bf_lo(p[e][2]) + bf_lo(p[e][3])),
                                           (bf_lo(p[e + 1][0]) + bf_lo(p[e + 1][1])) + (bf_lo(p[e + 1][2]) + bf_lo(p[e + 1][3])));
            o1[2 * hb + e / 2] = pack_bf16((bf_hi(p[e][0]) + bf_hi(p[e][1])) + (bf_hi(p[e][2]) + bf_hi(p[e][3])),
                                           (bf_hi(p[e + 1][0]) + bf_hi(p[e + 1][1])) + (bf_hi(p[e + 1][2]) + bf_hi(p[e + 1][3])));
          }
        }
        const uint4 k0 = lds128(cbx), k1 = lds128(cbx + 16);
        __syncwarp();
        if (lane == 0) mbar_arrive(BAR(B_RF + c));
        sts128(cbx, badd2(o0[0], bmul2(k0.x, dd)), badd2(o0[1], bmul2(k0.y, dd)), badd2(o0[2], bmul2(k0.z, dd)), badd2(o0[3], bmul2(k0.w, dd)));
        sts128(cbx + 16, badd2(o1[0], bmul2(k1.x, dd)), badd2(o1[1], bmul2(k1.y, dd)), badd2(o1[2], bmul2(k1.z, dd)), badd2(o1[3], bmul2(k1.w, dd)));
        fence_async_smem();
        __syncwarp();
        if (lane == 0) {
          bulk_s2g(g_yT + (size_t)(cta * 5 + c) * SL + (k & 3) * 512, cbx, 1024);
          bulk_commit();
        }
        if (k < 12) {
          uint4* xs = g_xch + (size_t)(cta ^ 64) * 1536 + k * 128 + lane;
          const uint32_t e = (ep1 ^ 0x8000u) << 16;
#pragma unroll
          for (int i = 0; i < 4; i++) st_relaxed_b128(xs + i * 32, e, e, e, e);
        }
        if (lane == 0 && (k == 3 || k == 7 || k == 11 || k == 15)) TS(60 + (k >> 2));
        __syncwarp();
      }
      if (lane == 0) bulk_wait_all();
      bar_sync(2, 96);
      if (at == 0) {
        mbar_wait(BAR(B_RF + 3), 0);
        signal_relaxed(CNT_Y + (cta >> 4));
        TS(3);
        const int c0 = nt * 160 + kh * 80;
        mbar_expect(BAR(B_FIN), 20480);
        tma2d(sb + FIN_Q, &tmQE, c0, rb * 128, BAR(B_FIN));
        tma2d(sb + FIN_Q + 10240, &tmQE, c0 + 40, rb * 128, BAR(B_FIN));
        wait_cnt(CNT_Y + 2 * nt + kh, 16 * ep1);
        TS(40);
        mbar_expect(BAR(B_FIN), 20480);
        tma2d(sb + FIN_Y, &tmY, rb * 128, c0, BAR(B_FIN));
        tma2d(sb + FIN_Y + 10240, &tmY, rb * 128 + 64, c0, BAR(B_FIN));
      }
      __syncwarp();
    }
  } else {
    asm volatile("setmaxnreg.inc.sync.aligned.u32 224;");
    const int wg = warp >> 2, w = warp & 3, g = lane >> 2, q = lane & 3;
    const bool elect = (tid & 127) == 0;
    const unsigned ep1 = __ldcg(&g_launch[cta * 8]) + 1;
    uint32_t ca[64];
    auto conv_lda = [&](int c, int k0, int k1) {
      const uint32_t ab = sb + KT + c * KT_CH + ((g & 1) ? KT_E : KT_O) + (8 * w + 4 + (g >> 1) - q) * 4;
#pragma unroll
      for (int ks = 0; ks < 16; ks++) {
        if (ks >= k0 && ks < k1) {
          ca[4 * ks + 0] = lds32(ab + ks * 256);
          ca[4 * ks + 1] = lds32(ab + ks * 256 + 128);
          ca[4 * ks + 2] = lds32(ab + ks * 256 - 16);
          ca[4 * ks + 3] = lds32(ab + ks * 256 + 112);
        }
      }
    };
    {
      float d[112];
      bool g1_early = false;
      auto g1_issue = [&](int kc) {
        const int s = kc & 3;
        g1_early = false;
        if (kc > 0 && kc < 7 && !mbar_test(BAR(B_F1 + s), (kc >> 2) & 1)) {
          wg_wait<0>();
          if (elect) { const int ps = (kc - 1) & 3; mbar_arrive_rank(BAR(B_E1 + ps), 0); mbar_arrive_rank(BAR(B_E1 + ps), 1); }
          g1_early = true;
        }
        mbar_wait(BAR(B_F1 + s), (kc >> 2) & 1);
        if (tid == 0) TS(8 + kc);
        const uint32_t st = sb + s * G1_STAGE;
        const uint64_t da = mkdesc(st + wg * 8192, 16, 1024, 1), db = mkdesc(st + 16384, 4096, 512, 2);
        wg_fence();
#pragma unroll
        for (int k = 0; k < 4; k++) wg_ss_224(d, da + k * 2, db + k * 64, (kc | k) != 0);
        wg_commit();
      };
      auto g1_release = [&](int kc) {
        wg_wait<1>();
        if (kc < 7 && elect && !g1_early) { const int ps = (kc - 1) & 3; mbar_arrive_rank(BAR(B_E1 + ps), 0); mbar_arrive_rank(BAR(B_E1 + ps), 1); }
      };
      const __nv_bfloat16* xsrc = P.q + (size_t)(rb * 128 + j * 16 + warp * 2 + (lane >> 4)) * DM + (lane & 15) * 8;
      const __nv_bfloat16* wsrc = P.w1 + (size_t)(tid >> 1) * FF + c1 + min(rb, 13) * 16 + (tid & 1) * 8;
      const bool b4 = lane & 16, b3 = lane & 8, b2 = lane & 4;
      uint4 px[5], pw[5];
      float a[8], mu, m2;
      auto merge = [&](int o, float n2) {
        const float mo = __shfl_xor_sync(0xffffffffu, mu, o), so = __shfl_xor_sync(0xffffffffu, m2, o);
        const float dl = mo - mu;
        mu = 0.5f * (mu + mo); m2 = fmaf(dl * dl, n2, m2 + so);
      };
      auto blkA = [&]() {
      {
        const float c = bf_lo(px[0].x);
        float t1 = 0.f, t2 = 0.f;
#pragma unroll
        for (int i = 0; i < 5; i++) {
          const uint32_t xx[4] = {px[i].x, px[i].y, px[i].z, px[i].w};
#pragma unroll
          for (int e = 0; e < 4; e++) { const float u = bf_lo(xx[e]) - c, v = bf_hi(xx[e]) - c; t1 += u + v; t2 = fmaf(u, u, fmaf(v, v, t2)); }
        }
        const float dm = t1 * (1.f / 40);
        mu = c + dm; m2 = fmaf(-dm, t1, t2);
        merge(8, 20.f);
      }
      };
      auto blkB = [&]() {
      {
#pragma unroll
        for (int e = 0; e < 8; e++) a[e] = 0.f;
#pragma unroll
        for (int i = 0; i < 5; i++) {
          a[0] += bf_lo(pw[i].x); a[1] += bf_hi(pw[i].x); a[2] += bf_lo(pw[i].y); a[3] += bf_hi(pw[i].y);
          a[4] += bf_lo(pw[i].z); a[5] += bf_hi(pw[i].z); a[6] += bf_lo(pw[i].w); a[7] += bf_hi(pw[i].w);
        }
#pragma unroll
        for (int e = 0; e < 4; e++) a[e] = (b4 ? a[e + 4] : a[e]) + __shfl_xor_sync(0xffffffffu, b4 ? a[e] : a[e + 4], 16);
        merge(4, 40.f);
#pragma unroll
        for (int e = 0; e < 2; e++) a[e] = (b3 ? a[e + 2] : a[e]) + __shfl_xor_sync(0xffffffffu, b3 ? a[e] : a[e + 2], 8);
        merge(2, 80.f);
      }
      };
      auto blkC = [&]() {
      {
        a[0] = (b2 ? a[1] : a[0]) + __shfl_xor_sync(0xffffffffu, b2 ? a[0] : a[1], 4);
        merge(1, 160.f);
        a[0] += __shfl_xor_sync(0xffffffffu, a[0], 2);
        if ((lane & 15) == 0) {
          const float vb = bf_round(m2 * (1.f / DM));
          const float sd = bf_round(sqrtf(bf_round(vb + 1e-5f)));
          st_relaxed64(&g_stat[rb * 128 + j * 16 + warp * 2 + (lane >> 4)], pack_bf16(mu, sd), ep1);
        }
        if (!(lane & 2)) sts32(sb + M_RED + warp * 64 + ((lane & 1) * 8 + (lane >> 2)) * 4, __float_as_uint(a[0]));
        __syncwarp();
        if (lane == 0) mbar_arrive(BAR(B_RED));
      }
      };
      auto blkD = [&]() {
      if (warp == 7 && rb < 14) {
        mbar_wait(BAR(B_RED), 0);
        if (lane < 16) {
          float t = 0.f;
#pragma unroll
          for (int i = 0; i < 8; i++) t += __uint_as_float(lds32(sb + M_RED + i * 64 + lane * 4));
          st_relaxed64(&g_cs[j * 224 + rb * 16 + lane], __float_as_uint(t), ep1);
        }
        if (lane == 0) TS(32);
        __syncwarp();
      }
      };
      g1_issue(0);
      px[0] = ldg128(xsrc); px[1] = ldg128(xsrc + 128); pw[0] = ldg128(wsrc);
      g1_issue(1); g1_release(1);
      px[2] = ldg128(xsrc + 256); px[3] = ldg128(xsrc + 384); pw[1] = ldg128(wsrc + (size_t)128 * FF);
      g1_issue(2); g1_release(2);
      px[4] = ldg128(xsrc + 512); pw[2] = ldg128(wsrc + (size_t)256 * FF); pw[3] = ldg128(wsrc + (size_t)384 * FF);
      g1_issue(3); g1_release(3);
      pw[4] = ldg128(wsrc + (size_t)512 * FF);
      uint32_t bb = 0;
      if (tid < 112) bb = __ldg(reinterpret_cast<const uint32_t*>(P.b1 + c1 + 2 * tid));
      g1_issue(4); g1_release(4);
#define ST_SH 2
      if (ST_SH == 0) blkA();
      g1_issue(5); g1_release(5);
      if (ST_SH == 0) blkB(); else if (ST_SH == 1) blkA();
      g1_issue(6); g1_release(6);
      if (ST_SH == 0) blkC(); else if (ST_SH == 1) blkB(); else if (ST_SH == 2 || ST_SH == 5) { blkA(); } else if (ST_SH == 3) { blkA(); blkB(); }
      g1_issue(7); g1_release(7);
      if (ST_SH == 0) blkD(); else if (ST_SH == 1 || ST_SH == 3) blkC(); else if (ST_SH == 2) { blkB(); blkC(); } else if (ST_SH == 4) { blkA(); blkB(); } else { blkB(); }
      g1_issue(8); g1_release(8);
      if (ST_SH >= 4) blkC();
      if (ST_SH != 0) blkD();
      const uint2* sp0 = g_stat + rb * 128 + wg * 64 + w * 16 + g;
      const uint4* cp0 = reinterpret_cast<const uint4*>(g_cs + j * 224) + min(tid, 111);
      uint2 s0 = ld_relaxed64(sp0), s1 = ld_relaxed64(sp0 + 8);
      uint4 cs = ld_relaxed128(cp0);
      g1_issue(9); g1_release(9);
      {
        uint32_t t0 = 0;
        while (!__all_sync(0xffffffffu, s0.y == ep1 && s1.y == ep1 && cs.y == ep1 && cs.w == ep1)) {
          s0 = ld_relaxed64(sp0); s1 = ld_relaxed64(sp0 + 8); cs = ld_relaxed128(cp0);
          if (spin_guard(t0, 0x1fc)) break;
        }
        if (tid < 112) {
          const float x0 = __uint_as_float(cs.x), x1 = __uint_as_float(cs.z);
          const uint32_t hi = pack_bf16(x0, x1);
          const float y0 = x0 - bf_lo(hi), y1 = x1 - bf_hi(hi);
          const uint32_t mid = pack_bf16(y0, y1);
          const uint32_t lo = pack_bf16(y0 - bf_lo(mid), y1 - bf_hi(mid));
          const uint32_t ba = sb + M_BX + (tid >> 4) * 512 + (tid & 3) * 4, ch = (tid >> 2) & 3;
          sts32(ba + (ch << 4), hi); sts32(ba + 64 + (ch << 4), mid);
          sts32(ba + 128 + ((ch ^ 1) << 4), lo); sts32(ba + 192 + ((ch ^ 1) << 4), bb);
          sts32(ba + 256 + (ch << 4), 0u); sts32(ba + 320 + (ch << 4), 0u); sts32(ba + 384 + (ch << 4), 0u); sts32(ba + 448 + (ch << 4), 0u);
          fence_async_smem();
        }
        bar_sync(1, 256);
        if (tid == 0) TS(46);
        const uint32_t a0 = q == 0 ? ((s0.x & 0xFFFFu) * 0x10001u) ^ 0x80008000u : (q == 1 ? s0.x ^ 0x8000u : 0u);
        const uint32_t a1 = q == 0 ? ((s1.x & 0xFFFFu) * 0x10001u) ^ 0x80008000u : (q == 1 ? s1.x ^ 0x8000u : 0u);
        wg_fence();
        wg_rs_224(d, a0, a1, 0u, 0u, mkdesc(sb + M_BX, 512, 0, 2));
        wg_commit();
      }
      wg_wait<1>();
      bar_sync(1, 256);
      if (tid == 0) mbar_arrive(BAR(B_G1DONE));
      {
        const int t = tid & 127;
        if (t < 68) for (int c = wg; c < 5; c += 2) sts32(sb + cv_x(c) + t * 4, 0u);
        if (t < 96) { const int ww = 1 + (t >> 5), jj = (t >> 2) & 7, pp = t & 3; if (pp < ww) for (int h = 0; h < 2 - wg; h++) sts32(sb + cv_r(wg + 2 * h) + ww * CV_RW + jj * CV_RP + pp * 4, 0u); }
      }
      wg_wait<0>();
      if (tid == 0) TS(1);
      const float r0 = 0.5f / bf_hi(s0.x), r1 = 0.5f / bf_hi(s1.x);
      const int mi = lane >> 3, row = w * 16 + (mi & 1) * 8 + (lane & 7);
      const uint32_t hs = sb + wg * HST_WG;
      constexpr float C1 = 2.f * 0.7978845608028654f, C2 = 8.f * 0.7978845608028654f * 0.044715f;
      auto gelu2 = [&](float hx) { const float u = hx * fmaf(hx * hx, C2, C1); return fmaf(hx, tanh_fast(u), hx); };
#pragma unroll
      for (int nb = 0; nb < 28; nb += 2) {
        uint32_t p[4];
#pragma unroll
        for (int e = 0; e < 2; e++) {
          const float* dd = d + 4 * (nb + e);
          const float h0 = dd[0] * r0, h1 = dd[1] * r0, h2 = dd[2] * r1, h3 = dd[3] * r1;
          p[2 * e] = pack_bf16(gelu2(h0), gelu2(h1));
          p[2 * e + 1] = pack_bf16(gelu2(h2), gelu2(h3));
        }
        const int nbm = nb + (mi >> 1);
        if (nb < 24) stsm4(hs + (nb >> 3) * 8192 + row * 128 + (((nbm & 7) ^ (row & 7)) << 4), p[0], p[1], p[2], p[3]);
        else stsm4(hs + 24576 + row * 64 + (((nbm - 24) ^ ((row >> 1) & 3)) << 4), p[0], p[1], p[2], p[3]);
        if ((nb & 7) == 6 || nb == 26) {
          fence_async_smem();
          __syncwarp();
          if (lane == 0) mbar_arrive(BAR(B_HB + (nb >> 3)));
        }
        if (nb == A_NB0) mbar_wait(BAR(B_KT), 0);
        if (nb >= A_NB0) conv_lda(wg, (nb - A_NB0) / 2 * 16 / ((28 - A_NB0) / 2), ((nb - A_NB0) / 2 + 1) * 16 / ((28 - A_NB0) / 2));
      }
      fence_async_smem();
      bar_sync(3 + wg, 128);
      if (tid == 0) TS(2);
    }
    {
      for (int c = wg; c < 5; c += 2) {
        float d[128];
        mbar_wait(BAR(B_CF + c), 0);
        const uint64_t db = mkdesc(sb + cv_x(c), 16, 128, 0);
        if (c > 0) bar_sync(5 + (c & 1), 256);
        if (elect) TS(41 + c);
        if (c >= 3 && elect) { mbar_arrive_rank(BAR(B_E2 + 2), 0); mbar_arrive_rank(BAR(B_E2 + 2), 1); }
        wg_fence();
        conv_chain_a(d, ca, db);
        wg_commit();
        conv_chain_b(d, ca, db);
        wg_commit();
        wg_wait<1>();
        if (c < 4) bar_arrive(5 + ((c + 1) & 1), 256);
        wg_wait<0>();
        if (elect && c == 4) TS(59);
        if (c >= 3) mbar_wait(BAR(B_RF + (c == 3 ? 1 : 0)), 0);
        const uint32_t Rw = sb + cv_r(c);
        if (elect && c == 4) TS(7);
        if (elect && c == 2) TS(56);
        if (elect && c == 3) TS(57);
        const uint32_t wa = Rw + w * CV_RW + g * CV_RP + (q + w) * 4;
#pragma unroll
        for (int nb = 0; nb < 32; nb++) {
          float x = d[4 * nb], y = d[4 * nb + 1];
          if (nb > 0) { x += d[4 * nb - 2]; y += d[4 * nb - 1]; }
          sts32(wa + nb * 16, pack_bf16(x, y));
        }
        if (c != 3) {
          __syncwarp();
          if (lane == 0) mbar_arrive(BAR(B_SD + c));
        } else {
          const uint32_t dd = (uint32_t)__bfloat16_as_ushort(P.ssm_D[cta * 5 + 3]) * 0x10001u;
          bar_sync(4, 128);
          const int t = tid & 127;
          float2 y[8];
#pragma unroll
          for (int jj = 0; jj < 8; jj++) {
            const uint32_t ra = Rw + jj * CV_RP + t * 4;
            const uint32_t p0 = lds32(ra), p1 = lds32(ra + CV_RW), p2 = lds32(ra + 2 * CV_RW), p3 = lds32(ra + 3 * CV_RW);
            y[jj].x = (bf_lo(p0) + bf_lo(p1)) + (bf_lo(p2) + bf_lo(p3));
            y[jj].y = (bf_hi(p0) + bf_hi(p1)) + (bf_hi(p2) + bf_hi(p3));
          }
          const uint32_t cbx = sb + cv_x(3) + CV_XD + t * 32;
          const uint4 k0 = lds128(cbx), k1 = lds128(cbx + 16);
          sts128(cbx, badd2(pack_bf16(y[0].x, y[1].x), bmul2(k0.x, dd)), badd2(pack_bf16(y[2].x, y[3].x), bmul2(k0.y, dd)),
                 badd2(pack_bf16(y[4].x, y[5].x), bmul2(k0.z, dd)), badd2(pack_bf16(y[6].x, y[7].x), bmul2(k0.w, dd)));
          sts128(cbx + 16, badd2(pack_bf16(y[0].y, y[1].y), bmul2(k1.x, dd)), badd2(pack_bf16(y[2].y, y[3].y), bmul2(k1.y, dd)),
                 badd2(pack_bf16(y[4].y, y[5].y), bmul2(k1.z, dd)), badd2(pack_bf16(y[6].y, y[7].y), bmul2(k1.w, dd)));
          fence_async_smem();
          bar_sync(4, 128);
          if (elect) { bulk_s2g(g_yT + (size_t)(cta * 5 + 3) * SL, sb + cv_x(3) + CV_XD, 4096); bulk_commit(); TS(48); }
        }
        if (c < 3) { if (c < 2) mbar_wait(BAR(B_KT2), 0); conv_lda(c + 2, 0, 16); }
      }
      if (tid == 0) TS(51);
    }
    {
      float d[80];
      for (int kc = 0; kc < 13; kc++) {
        const int s = kc & 3;
        const bool rel = kc > 0 && kc < 11;
        bool early = false;
        if (rel && !mbar_test(BAR(B_F2 + s), (kc >> 2) & 1)) {
          wg_wait<0>();
          if (elect) { const int ps = (kc - 1) & 3; mbar_arrive_rank(BAR(B_E2 + ps), 0); mbar_arrive_rank(BAR(B_E2 + ps), 1); }
          early = true;
        }
        mbar_wait(BAR(B_F2 + s), (kc >> 2) & 1);
        if (tid == 0) TS(18 + kc);
        const uint64_t da = mkdesc(sb + g2_a(s) + wg * 8192, 16, 1024, 1), db = mkdesc(sb + g2_b(s), 4096, 512, 2);
        wg_fence();
        wg_ss_160(d, da, db, kc != 0);
        wg_ss_160(d, da + 2, db + 64, 1);
        wg_ss_160(d, da + 4, db + 128, 1);
        wg_ss_160(d, da + 6, db + 192, 1);
        wg_commit();
        wg_wait<1>();
        if (rel && !early && elect) { const int ps = (kc - 1) & 3; mbar_arrive_rank(BAR(B_E2 + ps), 0); mbar_arrive_rank(BAR(B_E2 + ps), 1); }
        if (kc == Y3_KC && wg == 1 && elect) { bulk_wait_all(); mbar_arrive(BAR(B_RF + 3)); }
      }
      {
        mbar_wait(BAR(B_F2 + 1), 1);
        const uint64_t da = mkdesc(sb + g2_a(1) + wg * 8192, 16, 1024, 1), db = mkdesc(sb + g2_b(1), 4096, 512, 2);
        wg_fence();
        wg_ss_160(d, da, db, 1);
        wg_ss_160(d, da + 2, db + 64, 1);
        wg_commit();
      }
      wg_wait<0>();
      if (tid == 0) TS(4);
      const uint32_t tag = ep1 << 16;
      float keep[40];
      const uint4* src = g_xch + (size_t)cta * 1536 + tid;
      uint4 v[6];
#pragma unroll
      for (int i = 0; i < 6; i++) v[i] = ld_relaxed_b128(src + i * 256);
      mbar_wait(BAR(B_FIN), 0);
      {
        uint4* dst = g_xch + (size_t)(cta ^ 64) * 1536 + tid;
        uint32_t p[20];
#pragma unroll
        for (int i = 0; i < 20; i++) p[i] = pack_bf16(kh ? d[2 * i] : d[40 + 2 * i], kh ? d[2 * i + 1] : d[41 + 2 * i]);
#pragma unroll
        for (int i = 0; i < 6; i++) {
          const uint32_t h = i < 4 ? ((i & 1) ? p[18 + (i >> 1)] >> 16 : p[18 + (i >> 1)] & 0xFFFFu) : 0u;
          st_relaxed_b128(dst + i * 256, p[3 * i], p[3 * i + 1], p[3 * i + 2], h | tag);
        }
      }
      if (tid == 0) TS(49);
      mbar_wait(BAR(B_TBL), 0);
      if (tid == 0) TS(47);
      const int mi = lane >> 3;
      const int row = wg * 64 + w * 16 + (mi & 1) * 8 + (lane & 7);
      uint32_t xq[20], sv[20];
      float2 bb[10];
      {
        const uint2 s0 = lds64(sb + M_STATS + (wg * 64 + w * 16 + g) * 8), s1 = lds64(sb + M_STATS + (wg * 64 + w * 16 + g + 8) * 8);
        const uint32_t m0 = (s0.x & 0xFFFFu) * 0x10001u, m1 = (s1.x & 0xFFFFu) * 0x10001u;
#pragma unroll
        for (int nb = 0; nb < 10; nb += 2) {
          const int nbm = nb + (mi >> 1);
          const uint32_t qa = sb + FIN_Q + (nbm >= 5 ? 10240 + (nbm - 5) * 16 : nbm * 16) + row * 80;
          const int chr = nbm * 8 + (lane & 7);
          const uint32_t ya = sb + FIN_Y + wg * 10240 + chr * 128 + (((2 * w + (mi & 1)) ^ (chr & 7)) << 4);
          uint32_t y[4];
          ldsm4(qa, xq[2 * nb], xq[2 * nb + 1], xq[2 * nb + 2], xq[2 * nb + 3]);
          ldsm4t(ya, y[0], y[1], y[2], y[3]);
#pragma unroll
          for (int e = 0; e < 4; e++) {
            const int hi = e & 1;
            const uint32_t dm = bsub2(xq[2 * nb + e], hi ? m1 : m0);
            const float rs = __uint_as_float(hi ? s1.y : s0.y);
            sv[2 * nb + e] = bmul2(pack_bf16(bf_lo(dm) * rs, bf_hi(dm) * rs), y[e]);
          }
        }
#pragma unroll
        for (int nb = 0; nb < 10; nb++) bb[nb] = lds64f(sb + M_B2 + (nb * 8 + 2 * q) * 4);
      }
#pragma unroll
      for (int i = 0; i < 10; i++) {
        keep[4 * i] = 0.5f * ((kh ? d[40 + 4 * i] : d[4 * i]) + bb[i].x); keep[4 * i + 1] = 0.5f * ((kh ? d[41 + 4 * i] : d[4 * i + 1]) + bb[i].y);
        keep[4 * i + 2] = 0.5f * ((kh ? d[42 + 4 * i] : d[4 * i + 2]) + bb[i].x); keep[4 * i + 3] = 0.5f * ((kh ? d[43 + 4 * i] : d[4 * i + 3]) + bb[i].y);
      }
      {
        uint32_t t0 = 0;
        while (true) {
          bool ok = true;
#pragma unroll
          for (int i = 0; i < 6; i++) ok = ok && (v[i].w ^ tag) < 0x10000u;
          if (ok || spin_guard(t0, 0x1fe)) break;
#pragma unroll
          for (int i = 0; i < 6; i++) if ((v[i].w ^ tag) >= 0x10000u) v[i] = ld_relaxed_b128(src + i * 256);
        }
      }
      if (tid == 0) TS(5);
      {
        auto word = [&](int k) {
          if (k >= 18) return __byte_perm(v[2 * (k - 18)].w, v[2 * (k - 18) + 1].w, 0x5410);
          const uint4& u = v[k / 3];
          return k % 3 == 0 ? u.x : (k % 3 == 1 ? u.y : u.z);
        };
        uint32_t o[20];
#pragma unroll
        for (int k = 0; k < 20; k++) {
          const uint32_t pw = word(k);
          const float h0 = fmaf(0.5f, bf_lo(pw), keep[2 * k]), h1 = fmaf(0.5f, bf_hi(pw), keep[2 * k + 1]);
          o[k] = badd2(xq[k], bmul2(sv[k], pack_bf16(fmaf(h0, tanh_fast(h0), h0), fmaf(h1, tanh_fast(h1), h1))));
        }
#pragma unroll
        for (int nb = 0; nb < 10; nb += 2) {
          const int nbm = nb + (mi >> 1);
          stsm4(sb + FIN_Q + (nbm >= 5 ? 10240 + (nbm - 5) * 16 : nbm * 16) + row * 80, o[2 * nb], o[2 * nb + 1], o[2 * nb + 2], o[2 * nb + 3]);
        }
      }
      if (tid == 0) TS(50);
      fence_async_smem();
      bar_sync(3 + wg, 128);
      if (elect) {
        const int c0 = nt * 160 + kh * 80;
        tma2d_st(&tmOut, c0, rb * 128 + wg * 64, sb + FIN_Q + wg * 5120);
        tma2d_st(&tmOut, c0 + 40, rb * 128 + wg * 64, sb + FIN_Q + 10240 + wg * 5120);
        bulk_commit();
        bulk_wait_read();
      }
      if (tid == 0) TS(6);
    }
  }
}

typedef CUresult (*EncFn)(CUtensorMap*, CUtensorMapDataType, cuuint32_t, void*, const cuuint64_t*, const cuuint64_t*, const cuuint32_t*, const cuuint32_t*,
                          CUtensorMapInterleave, CUtensorMapSwizzle, CUtensorMapL2promotion, CUtensorMapFloatOOBfill);

static void make_map(EncFn enc, CUtensorMap* tm, const void* ptr, int cols, int rows, int bc, int br, CUtensorMapSwizzle sw) {
  cuuint64_t gd[2] = {(cuuint64_t)cols, (cuuint64_t)rows};
  cuuint64_t gs[1] = {(cuuint64_t)cols * 2};
  cuuint32_t bd[2] = {(cuuint32_t)bc, (cuuint32_t)br};
  cuuint32_t es[2] = {1, 1};
  CUresult r = enc(tm, CU_TENSOR_MAP_DATA_TYPE_BFLOAT16, 2, const_cast<void*>(ptr), gd, gs, bd, es, CU_TENSOR_MAP_INTERLEAVE_NONE, sw,
      CU_TENSOR_MAP_L2_PROMOTION_L2_128B, CU_TENSOR_MAP_FLOAT_OOB_FILL_NONE);
  (void)r;
}

}

extern "C" void kernel_launch(void* const* d_in, const int* in_sizes, int n_in, void* d_out, int out_size) {
  using namespace h3;
  (void)in_sizes; (void)n_in; (void)out_size;
  static EncFn enc = nullptr;
  static void *p_h = nullptr, *p_yT = nullptr, *p_kvT = nullptr;
  if (!enc) {
    void* fn = nullptr; cudaDriverEntryPointQueryResult qr;
    cudaGetDriverEntryPoint("cuTensorMapEncodeTiled", &fn, cudaEnableDefault, &qr);
    enc = (EncFn)fn;
    cudaGetSymbolAddress(&p_h, g_h);
    cudaGetSymbolAddress(&p_yT, g_yT);
    cudaGetSymbolAddress(&p_kvT, g_kvT);
    cudaFuncSetAttribute(h3_kernel, cudaFuncAttributeMaxDynamicSharedMemorySize, SMEM_BYTES);
  }
  Params P;
  P.q = (const __nv_bfloat16*)d_in[0]; P.k = (const __nv_bfloat16*)d_in[1]; P.v = (const __nv_bfloat16*)d_in[2];
  P.shift_k = (const __nv_bfloat16*)d_in[3]; P.ssm_k = (const __nv_bfloat16*)d_in[4]; P.ssm_D = (const __nv_bfloat16*)d_in[5];
  P.out = (__nv_bfloat16*)d_out;
  P.w1 = (const __nv_bfloat16*)d_in[7]; P.b1 = (const __nv_bfloat16*)d_in[8]; P.w2 = (const __nv_bfloat16*)d_in[9]; P.b2 = (const __nv_bfloat16*)d_in[10];
  CUtensorMap tmQA, tmW1, tmH, tmH32, tmW2, tmQE, tmY, tmOut, tmK, tmK36, tmV, tmKVT;
  make_map(enc, &tmQA, P.q, DM, SL, 64, 128, CU_TENSOR_MAP_SWIZZLE_128B);
  make_map(enc, &tmW1, P.w1, FF, DM, 32, 64, CU_TENSOR_MAP_SWIZZLE_64B);
  make_map(enc, &tmH, p_h, FF, SL, 64, 64, CU_TENSOR_MAP_SWIZZLE_128B);
  make_map(enc, &tmH32, p_h, FF, SL, 32, 64, CU_TENSOR_MAP_SWIZZLE_64B);
  make_map(enc, &tmW2, P.w2, DM, FF, 32, 64, CU_TENSOR_MAP_SWIZZLE_64B);
  make_map(enc, &tmQE, P.q, DM, SL, 40, 128, CU_TENSOR_MAP_SWIZZLE_NONE);
  make_map(enc, &tmY, p_yT, SL, DM, 64, 80, CU_TENSOR_MAP_SWIZZLE_128B);
  make_map(enc, &tmOut, d_out, DM, SL, 40, 64, CU_TENSOR_MAP_SWIZZLE_NONE);
  make_map(enc, &tmK, P.k, DM, SL, 80, 32, CU_TENSOR_MAP_SWIZZLE_NONE);
  make_map(enc, &tmK36, P.k, DM, SL, 80, 36, CU_TENSOR_MAP_SWIZZLE_NONE);
  make_map(enc, &tmV, P.v, DM, SL, 80, 32, CU_TENSOR_MAP_SWIZZLE_NONE);
  make_map(enc, &tmKVT, p_kvT, SL, DM, 32, 80, CU_TENSOR_MAP_SWIZZLE_64B);
  h3_kernel<<<NCTA, 384, SMEM_BYTES>>>(tmQA, tmW1, tmH, tmH32, tmW2, tmQE, tmY, tmOut, tmK, tmK36, tmV, tmKVT, P);
}
```

```cpp
#include <cuda_runtime.h>
#include <cuda_bf16.h>
#include <cuda.h>
#include <stdint.h>

namespace h3 {

constexpr int SL = 2048, DM = 640, FF = 1728, HP = 1792;
constexpr int NCTA = 128;

__device__ __align__(1024) __nv_bfloat16 g_h[SL * HP];
__device__ __align__(1024) __nv_bfloat16 g_kvT[DM * SL];
__device__ __align__(1024) __nv_bfloat16 g_yT[DM * SL];
__device__ __align__(1024) uint2 g_stat[SL];
__device__ __align__(1024) uint32_t g_cs[8 * 224];
__device__ __align__(1024) unsigned g_cnt[64 * 32];
__device__ __align__(1024) unsigned g_launch[NCTA * 8];
constexpr int CNT_KV = 0, CNT_Y = 10, CNT_H = 16;

constexpr int G1_STAGE = 49152, G1_TX = 16384 + 24576 + 3072;
constexpr int HST = 49152;
constexpr int P0 = 81920, P1 = 140288, P2 = 156672;
constexpr int XCH = 4368, XD = 272, X0 = 173056, X4 = 221184;
constexpr int KVS = 196608, KV_BUF = 8960;
constexpr int KT_CH = 8240, KT_O = 16, KT_E = 4144, KT0 = 98304;
constexpr int FIN_Q = X0, YST = FIN_Q + 20480, FIN_Y = 98304;
constexpr int MISC = 226816;
constexpr int SIDE = KVS + 2 * KV_BUF;
constexpr int M_BX = MISC;
constexpr int M_RED = M_BX;
constexpr int M_STAT = M_BX + 3584;
constexpr int M_B2 = M_STAT + 512;
constexpr int M_AUX = M_B2 + 320;
constexpr int M_ZERO = M_AUX + 96;
constexpr int M_BAR = M_ZERO + 16;
constexpr int M_TS = M_BAR + 76 * 8;
constexpr int SMEM_BYTES = M_TS + 256;
__host__ __device__ constexpr int cv_x(int c) { return c == 4 ? X4 : X0 + c * XCH; }
__host__ __device__ constexpr int cv_p(int c) { return c == 2 ? P2 : ((c == 0 || c == 3) ? P0 : P1); }
__host__ __device__ constexpr int cv_t(int c) { return KT0 + c * KT_CH; }
__host__ __device__ constexpr int g2_a(int s) { return s == 0 ? 0 : (s == 1 ? 40960 : (s == 2 ? 98304 : P2)); }
__host__ __device__ constexpr int g2_b(int s) { return s == 0 ? 16384 : (s == 1 ? 57344 : (s == 2 ? 114688 : KVS)); }
static_assert(SIDE + 12288 <= MISC && X4 + XCH <= MISC && KVS + 24576 <= X4 && X0 + 4 * XCH <= YST && YST + 3072 <= KVS, "smem");
static_assert(KT0 + 5 * KT_CH <= P1 && P1 + 16384 <= P2 && P2 + 16384 <= X0 && SMEM_BYTES <= 232448 && MISC % 512 == 0 && M_BAR % 8 == 0, "smem");
constexpr int B_F1 = 0, B_E1 = 4, B_FR = 8, B_F2 = 12, B_E2 = 16, B_KRAW = 20, B_KT = 22, B_XF = 27, B_HB = 32, B_SD = 40, B_RF = 45,
              B_TD = 48, B_FINQ = 50, B_FINY = 51, B_RED = 52, B_BX = 53, B_KIN = 54, B_XR = 59, B_OUT = 61, B_SIDE = 66, B_YSLOT = 67, B_XD = 68, B_KIN1 = 70;
constexpr int NB_INIT = 1, NB_INIT2 = 2, NB_AUX = 3, NB_LEAD = 4, NB_GELU = 5, NB_TURN = 6  , NB_END = 8, NB_INIT3 = 9;

#define KV_MAP 0x53
#define KV_LATE 1
#define PF_KV 0
#define PF_G1 0
#define WS_PROMO CU_TENSOR_MAP_L2_PROMOTION_L2_128B
#define RAW_LATE 0
#define PF_RAW 0x77665
#define SIDE_LD 4
#define SIDE_USE 0x554
#define REL_K 0
#define CS_WAIT 200
#define GELU_NB 8
#define H_ORD 0x73625410
#define W2_PF 0
#define H_FLY 8
#define TBP 3
#define TBW 2
#define A_NB0 12
#define RED_GATE 0
#define XP_KC 4
#define YP_N 4
#define HOLD_KC 11
#define END_KC 13
#define REG_AUX "56"
#define REG_CON "224"
#define LDQ ".nc.L1::no_allocate"
#define LDP ""

__device__ __forceinline__ uint32_t s32(const void* p) { return (uint32_t)__cvta_generic_to_shared(p); }
__device__ __forceinline__ uint32_t clk() { uint32_t t; asm volatile("mov.u32 %0, %%clock;" : "=r"(t)); return t; }
__device__ __forceinline__ bool elect_one() {
  uint32_t p; asm volatile("{\n.reg .pred P;\nelect.sync _|P, 0xffffffff;\nselp.u32 %0, 1, 0, P;\n}" : "=r"(p)); return p;
}
#define ONE(...) do { if (elect_one()) { __VA_ARGS__; } __syncwarp(); } while (0)
__device__ __forceinline__ void mbar_init(uint32_t a, int c) { asm volatile("mbarrier.init.shared::cta.b64 [%0], %1;" ::"r"(a), "r"(c) : "memory"); }
__device__ __forceinline__ void mbar_expect(uint32_t a, int b) { asm volatile("mbarrier.arrive.expect_tx.shared::cta.b64 _, [%0], %1;" ::"r"(a), "r"(b) : "memory"); }
__device__ __forceinline__ void mbar_arrive(uint32_t a) { asm volatile("mbarrier.arrive.shared::cta.b64 _, [%0];" ::"r"(a) : "memory"); }
__device__ __forceinline__ bool spin_guard(uint32_t& n, uint32_t) {
  return ++n > (1u << 20);
}
__device__ __forceinline__ void mbar_wait(uint32_t a, int ph) {
  asm volatile("{\n.reg .pred p;\n.reg .u32 n;\nmov.u32 n, 0;\nW:\n.pragma \"nounroll\";\nmbarrier.try_wait.parity.shared::cta.b64 p, [%0], %1;\n"
               "add.u32 n, n, 1;\nsetp.ge.or.u32 p, n, 0x100000, p;\n@!p bra W;\n}" ::"r"(a), "r"(ph) : "memory");
}
__device__ __forceinline__ bool mbar_test(uint32_t a, int ph) {
  uint32_t ok;
  asm volatile("{\n.reg .pred p;\nmbarrier.test_wait.parity.shared::cta.b64 p, [%1], %2;\nselp.u32 %0, 1, 0, p;\n}" : "=r"(ok) : "r"(a), "r"(ph) : "memory");
  return __all_sync(0xffffffffu, ok);
}
__device__ __forceinline__ void tma2d(uint32_t dst, const CUtensorMap* tm, int c0, int c1, uint32_t bar) {
  asm volatile("cp.async.bulk.tensor.2d.shared::cluster.global.mbarrier::complete_tx::bytes [%0], [%1, {%3, %4}], [%2];"
               ::"r"(dst), "l"(tm), "r"(bar), "r"(c0), "r"(c1) : "memory");
}
__device__ __forceinline__ void tma3d(uint32_t dst, const CUtensorMap* tm, int c0, int c1, int c2, uint32_t bar) {
  asm volatile("cp.async.bulk.tensor.3d.shared::cluster.global.mbarrier::complete_tx::bytes [%0], [%1, {%3, %4, %5}], [%2];"
               ::"r"(dst), "l"(tm), "r"(bar), "r"(c0), "r"(c1), "r"(c2) : "memory");
}
__device__ __forceinline__ void tma2d_st(const CUtensorMap* tm, int c0, int c1, uint32_t src) {
  asm volatile("cp.async.bulk.tensor.2d.global.shared::cta.bulk_group [%0, {%2, %3}], [%1];" ::"l"(tm), "r"(src), "r"(c0), "r"(c1) : "memory");
}
__device__ __forceinline__ void tma3d_st(const CUtensorMap* tm, int c0, int c1, int c2, uint32_t src) {
  asm volatile("cp.async.bulk.tensor.3d.global.shared::cta.bulk_group [%0, {%2, %3, %4}], [%1];" ::"l"(tm), "r"(src), "r"(c0), "r"(c1), "r"(c2) : "memory");
}
__device__ __forceinline__ void bulk_g2s(uint32_t dst, const void* src, int bytes, uint32_t bar) {
  asm volatile("cp.async.bulk.shared::cluster.global.mbarrier::complete_tx::bytes [%0], [%1], %2, [%3];" ::"r"(dst), "l"(src), "r"(bytes), "r"(bar) : "memory");
}
__device__ __forceinline__ void bulk_commit() { asm volatile("cp.async.bulk.commit_group;" ::: "memory"); }
__device__ __forceinline__ void bulk_wait_read() { asm volatile("cp.async.bulk.wait_group.read 0;" ::: "memory"); }
__device__ __forceinline__ void bulk_wait_all() { asm volatile("cp.async.bulk.wait_group 0;" ::: "memory"); }
__device__ __forceinline__ void fence_async_smem() { asm volatile("fence.proxy.async.shared::cta;" ::: "memory"); }
__device__ __forceinline__ void fence_async_all() { asm volatile("fence.proxy.async;" ::: "memory"); }
#define RFENCE 0
__device__ __forceinline__ void fence_rd1() { if (RFENCE & 1) asm volatile("fence.acq_rel.gpu;" ::: "memory"); }
__device__ __forceinline__ void fence_rd2() { if (RFENCE & 2) asm volatile("fence.proxy.async;" ::: "memory"); if (RFENCE & 4) asm volatile("fence.proxy.async.global;" ::: "memory"); }
__device__ __forceinline__ void fence_gpu() { asm volatile("fence.acq_rel.gpu;" ::: "memory"); }
#define bar_sync(id, n) asm volatile("bar.sync %0, %1;" ::"n"(id), "n"(n) : "memory")
#define bar_arrive(id, n) asm volatile("bar.arrive %0, %1;" ::"n"(id), "n"(n) : "memory")
__device__ __forceinline__ void wg_fence() { asm volatile("wgmma.fence.sync.aligned;" ::: "memory"); }
__device__ __forceinline__ void wg_commit() { asm volatile("wgmma.commit_group.sync.aligned;" ::: "memory"); }
template <int N> __device__ __forceinline__ void wg_wait() { asm volatile("wgmma.wait_group.sync.aligned %0;" ::"n"(N) : "memory"); }
__device__ __forceinline__ uint64_t mkdesc(uint32_t addr, uint32_t lbo, uint32_t sbo, int sw) {
  return (uint64_t)((addr & 0x3FFFF) >> 4) | ((uint64_t)(lbo >> 4) << 16) | ((uint64_t)(sbo >> 4) << 32) | ((uint64_t)sw << 62);
}
__device__ __forceinline__ uint32_t ldg32(const void* p) { uint32_t v; asm volatile("ld.global" LDQ ".b32 %0, [%1];" : "=r"(v) : "l"(p)); return v; }
template <int OFF> __device__ __forceinline__ uint32_t ldg32o(const void* p) { uint32_t v; asm volatile("ld.global" LDQ ".b32 %0, [%1+%2];" : "=r"(v) : "l"(p), "n"(OFF)); return v; }
template <int I> __device__ __forceinline__ void kv_loads(const void* kp, const void* vp, uint32_t (&kk)[16], uint32_t (&o)[16]) {
  kk[I] = ldg32o<I * DM * 2>(kp); o[I] = ldg32o<I * DM * 2>(vp);
  if constexpr (I < 15) kv_loads<I + 1>(kp, vp, kk, o);
}
__device__ __forceinline__ uint4 ldg128(const void* p) {
  uint4 v; asm volatile("ld.global" LDQ LDP ".v4.b32 {%0,%1,%2,%3}, [%4];" : "=r"(v.x), "=r"(v.y), "=r"(v.z), "=r"(v.w) : "l"(p)); return v;
}
__device__ __forceinline__ void stg128(void* p, uint32_t x, uint32_t y, uint32_t z, uint32_t w) {
  asm volatile("st.global.v4.b32 [%0], {%1,%2,%3,%4};" ::"l"(p), "r"(x), "r"(y), "r"(z), "r"(w) : "memory");
}
__device__ __forceinline__ uint4 ld_relaxed128(const void* p) {
  uint4 v; asm volatile("ld.relaxed.gpu.global.v4.b32 {%0,%1,%2,%3}, [%4];" : "=r"(v.x), "=r"(v.y), "=r"(v.z), "=r"(v.w) : "l"(p) : "memory"); return v;
}
__device__ __forceinline__ uint2 ld_relaxed64(const void* p) {
  uint2 v; asm volatile("ld.relaxed.gpu.global.v2.b32 {%0,%1}, [%2];" : "=r"(v.x), "=r"(v.y) : "l"(p) : "memory"); return v;
}
__device__ __forceinline__ uint4 ld_relaxed_b128(const void* p) {
  uint4 v; asm volatile("{\n.reg .b128 t;\nld.relaxed.gpu.global.b128 t, [%4];\nmov.b128 {%0,%1,%2,%3}, t;\n}" : "=r"(v.x), "=r"(v.y), "=r"(v.z), "=r"(v.w) : "l"(p) : "memory"); return v;
}
__device__ __forceinline__ void st_relaxed_b128(void* p, uint32_t x, uint32_t y, uint32_t z, uint32_t w) {
  asm volatile("{\n.reg .b128 t;\nmov.b128 t, {%1,%2,%3,%4};\nst.relaxed.gpu.global.b128 [%0], t;\n}" ::"l"(p), "r"(x), "r"(y), "r"(z), "r"(w) : "memory");
}
__device__ __forceinline__ void st_relaxed64(void* p, uint32_t x, uint32_t y) {
  asm volatile("{\n.reg .b64 t;\nmov.b64 t, {%1,%2};\nst.relaxed.gpu.global.b64 [%0], t;\n}" ::"l"(p), "r"(x), "r"(y) : "memory");
}
__device__ __forceinline__ void st_relaxed32(void* p, uint32_t x) { asm volatile("st.relaxed.gpu.global.b32 [%0], %1;" ::"l"(p), "r"(x) : "memory"); }
__device__ __forceinline__ uint32_t ld_relaxed32(const void* p) { uint32_t v; asm volatile("ld.relaxed.gpu.global.b32 %0, [%1];" : "=r"(v) : "l"(p) : "memory"); return v; }
__device__ __forceinline__ void st_relaxed128(void* p, uint32_t x, uint32_t y, uint32_t z, uint32_t w) {
  asm volatile("{\n.reg .b64 t, u;\nmov.b64 t, {%1,%2};\nmov.b64 u, {%3,%4};\nst.relaxed.gpu.global.v2.b64 [%0], {t, u};\n}" ::"l"(p), "r"(x), "r"(y), "r"(z), "r"(w) : "memory");
}
__device__ __forceinline__ void signal_cnt(int idx) {
  asm volatile("red.relaxed.gpu.global.add.u32 [%0], 1;" ::"l"(&g_cnt[idx * 32]) : "memory");
}
__device__ __forceinline__ void wait_cnt(int idx, unsigned target) {
  uint32_t n = 0;
#pragma unroll 1
  while (!__all_sync(0xffffffffu, (int)(ld_relaxed32(&g_cnt[idx * 32]) - target) >= 0)) {
    if (spin_guard(n, 0x100 + idx)) break;
  }
  fence_rd1(); fence_rd2();
}
__device__ __forceinline__ void bulk_s2g(void* dst, uint32_t src, int bytes) {
  asm volatile("cp.async.bulk.global.shared::cta.bulk_group [%0], [%1], %2;" ::"l"(dst), "r"(src), "r"(bytes) : "memory");
}
__device__ __forceinline__ void bulk_add_s2g(void* dst, uint32_t src, int bytes) {
  asm volatile("cp.reduce.async.bulk.global.shared::cta.bulk_group.add.noftz.bf16 [%0], [%1], %2;" ::"l"(dst), "r"(src), "r"(bytes) : "memory");
}
__device__ __forceinline__ void prefetch_l2(const void* p, int bytes) { asm volatile("cp.async.bulk.prefetch.L2.global [%0], %1;" ::"l"(p), "r"(bytes) : "memory"); }
__device__ __forceinline__ void prefetch_tile(const CUtensorMap* tm, int c0, int c1) {
  asm volatile("cp.async.bulk.prefetch.tensor.2d.L2.global.tile [%0, {%1, %2}];" ::"l"(tm), "r"(c0), "r"(c1) : "memory");
}
__device__ __forceinline__ void prefetch_map(const CUtensorMap* tm) { asm volatile("prefetch.tensormap [%0];" ::"l"(tm) : "memory"); }
__device__ __forceinline__ uint32_t pack_bf16(float lo, float hi) {
  uint32_t r; asm("cvt.rn.bf16x2.f32 %0, %1, %2;" : "=r"(r) : "f"(hi), "f"(lo)); return r;
}
__device__ __forceinline__ float bf_lo(uint32_t v) { return __uint_as_float(v << 16); }
__device__ __forceinline__ float bf_hi(uint32_t v) { return __uint_as_float(v & 0xFFFF0000u); }
__device__ __forceinline__ float bf_round(float x) { return __bfloat162float(__float2bfloat16_rn(x)); }
__device__ __forceinline__ uint32_t bmul2(uint32_t a, uint32_t b) { uint32_t r; asm("mul.rn.bf16x2 %0, %1, %2;" : "=r"(r) : "r"(a), "r"(b)); return r; }
__device__ __forceinline__ uint32_t bfma2(uint32_t a, uint32_t b, uint32_t c) { uint32_t r; asm("fma.rn.bf16x2 %0, %1, %2, %3;" : "=r"(r) : "r"(a), "r"(b), "r"(c)); return r; }
__device__ __forceinline__ uint32_t badd2(uint32_t a, uint32_t b) { uint32_t r; asm("add.rn.bf16x2 %0, %1, %2;" : "=r"(r) : "r"(a), "r"(b)); return r; }
__device__ __forceinline__ uint32_t bsub2(uint32_t a, uint32_t b) { uint32_t r; asm("sub.rn.bf16x2 %0, %1, %2;" : "=r"(r) : "r"(a), "r"(b)); return r; }
__device__ __forceinline__ float tanh_fast(float x) { float r; asm("tanh.approx.f32 %0, %1;" : "=f"(r) : "f"(x)); return r; }
__device__ __forceinline__ float rcp_fast(float x) { float r; asm("rcp.approx.ftz.f32 %0, %1;" : "=f"(r) : "f"(x)); return r; }
__device__ __forceinline__ float sqrt_fast(float x) { float r; asm("sqrt.approx.ftz.f32 %0, %1;" : "=f"(r) : "f"(x)); return r; }
__device__ __forceinline__ uint32_t lds32(uint32_t a) { uint32_t v; asm volatile("ld.shared.b32 %0, [%1];" : "=r"(v) : "r"(a)); return v; }
__device__ __forceinline__ uint4 lds128(uint32_t a) { uint4 v; asm volatile("ld.shared.v4.b32 {%0,%1,%2,%3}, [%4];" : "=r"(v.x), "=r"(v.y), "=r"(v.z), "=r"(v.w) : "r"(a)); return v; }
__device__ __forceinline__ float2 lds64f(uint32_t a) { float2 v; asm volatile("ld.shared.v2.f32 {%0,%1}, [%2];" : "=f"(v.x), "=f"(v.y) : "r"(a)); return v; }
__device__ __forceinline__ void sts64f(uint32_t a, float x, float y) { asm volatile("st.shared.v2.f32 [%0], {%1,%2};" ::"r"(a), "f"(x), "f"(y) : "memory"); }
__device__ __forceinline__ void sts32(uint32_t a, uint32_t x) { asm volatile("st.shared.b32 [%0], %1;" ::"r"(a), "r"(x) : "memory"); }
__device__ __forceinline__ void sts128(uint32_t a, uint32_t x, uint32_t y, uint32_t z, uint32_t w) { asm volatile("st.shared.v4.b32 [%0], {%1,%2,%3,%4};" ::"r"(a), "r"(x), "r"(y), "r"(z), "r"(w) : "memory"); }
__device__ __forceinline__ void stsm4(uint32_t a, uint32_t r0, uint32_t r1, uint32_t r2, uint32_t r3) {
  asm volatile("stmatrix.sync.aligned.m8n8.x4.shared.b16 [%0], {%1,%2,%3,%4};" ::"r"(a), "r"(r0), "r"(r1), "r"(r2), "r"(r3) : "memory");
}
__device__ __forceinline__ void stsm4t(uint32_t a, uint32_t r0, uint32_t r1, uint32_t r2, uint32_t r3) {
  asm volatile("stmatrix.sync.aligned.m8n8.x4.trans.shared.b16 [%0], {%1,%2,%3,%4};" ::"r"(a), "r"(r0), "r"(r1), "r"(r2), "r"(r3) : "memory");
}
__device__ __forceinline__ void stsm2(uint32_t a, uint32_t r0, uint32_t r1) {
  asm volatile("stmatrix.sync.aligned.m8n8.x2.shared.b16 [%0], {%1,%2};" ::"r"(a), "r"(r0), "r"(r1) : "memory");
}
__device__ __forceinline__ void ldsm4(uint32_t a, uint32_t& r0, uint32_t& r1, uint32_t& r2, uint32_t& r3) {
  asm volatile("ldmatrix.sync.aligned.m8n8.x4.shared.b16 {%0,%1,%2,%3}, [%4];" : "=r"(r0), "=r"(r1), "=r"(r2), "=r"(r3) : "r"(a) : "memory");
}
__device__ __forceinline__ void ldsm4t(uint32_t a, uint32_t& r0, uint32_t& r1, uint32_t& r2, uint32_t& r3) {
  asm volatile("ldmatrix.sync.aligned.m8n8.x4.trans.shared.b16 {%0,%1,%2,%3}, [%4];" : "=r"(r0), "=r"(r1), "=r"(r2), "=r"(r3) : "r"(a) : "memory");
}
__device__ __forceinline__ uint32_t mapa(uint32_t a, uint32_t rank) { uint32_t r; asm("mapa.shared::cluster.u32 %0, %1, %2;" : "=r"(r) : "r"(a), "r"(rank)); return r; }
__device__ __forceinline__ void mbar_arrive_remote(uint32_t a) { asm volatile("mbarrier.arrive.relaxed.cluster.shared::cluster.b64 _, [%0];" ::"r"(a) : "memory"); }
__device__ __forceinline__ void st_async128(uint32_t a, uint32_t x, uint32_t y, uint32_t z, uint32_t w, uint32_t bar) {
  asm volatile("st.async.weak.shared::cluster.mbarrier::complete_tx::bytes.v4.b32 [%0], {%1,%2,%3,%4}, [%5];" ::"r"(a), "r"(x), "r"(y), "r"(z), "r"(w), "r"(bar) : "memory");
}
#define TS(i)

#define TSKV
__device__ __forceinline__ void wg_ss_216(float (&d)[108], uint64_t da, uint64_t db, int sd) {
  asm volatile("{\n.reg .pred p;\nsetp.ne.b32 p, %110, 0;\n"
    "wgmma.mma_async.sync.aligned.m64n216k16.f32.bf16.bf16 {%0,%1,%2,%3,%4,%5,%6,%7,%8,%9,%10,%11,%12,%13,%14,%15,%16,%17,%18,%19,%20,%21,%22,%23,%24,%25,%26,%27,%28,%29,%30,%31,%32,%33,%34,%35,%36,%37,%38,%39,%40,%41,%42,%43,%44,%45,%46,%47,%48,%49,%50,%51,%52,%53,%54,%55,%56,%57,%58,%59,%60,%61,%62,%63,%64,%65,%66,%67,%68,%69,%70,%71,%72,%73,%74,%75,%76,%77,%78,%79,%80,%81,%82,%83,%84,%85,%86,%87,%88,%89,%90,%91,%92,%93,%94,%95,%96,%97,%98,%99,%100,%101,%102,%103,%104,%105,%106,%107}, %108, %109, p, 1, 1, 0, 1;\n}\n"
    : "+f"(d[0]),"+f"(d[1]),"+f"(d[2]),"+f"(d[3]),"+f"(d[4]),"+f"(d[5]),"+f"(d[6]),"+f"(d[7]),"+f"(d[8]),"+f"(d[9]),"+f"(d[10]),"+f"(d[11]),"+f"(d[12]),"+f"(d[13]),"+f"(d[14]),"+f"(d[15]),"+f"(d[16]),"+f"(d[17]),"+f"(d[18]),"+f"(d[19]),"+f"(d[20]),"+f"(d[21]),"+f"(d[22]),"+f"(d[23]),"+f"(d[24]),"+f"(d[25]),"+f"(d[26]),"+f"(d[27]),"+f"(d[28]),"+f"(d[29]),"+f"(d[30]),"+f"(d[31]),"+f"(d[32]),"+f"(d[33]),"+f"(d[34]),"+f"(d[35]),"+f"(d[36]),"+f"(d[37]),"+f"(d[38]),"+f"(d[39]),"+f"(d[40]),"+f"(d[41]),"+f"(d[42]),"+f"(d[43]),"+f"(d[44]),"+f"(d[45]),"+f"(d[46]),"+f"(d[47]),"+f"(d[48]),"+f"(d[49]),"+f"(d[50]),"+f"(d[51]),"+f"(d[52]),"+f"(d[53]),"+f"(d[54]),"+f"(d[55]),"+f"(d[56]),"+f"(d[57]),"+f"(d[58]),"+f"(d[59]),"+f"(d[60]),"+f"(d[61]),"+f"(d[62]),"+f"(d[63]),"+f"(d[64]),"+f"(d[65]),"+f"(d[66]),"+f"(d[67]),"+f"(d[68]),"+f"(d[69]),"+f"(d[70]),"+f"(d[71]),"+f"(d[72]),"+f"(d[73]),"+f"(d[74]),"+f"(d[75]),"+f"(d[76]),"+f"(d[77]),"+f"(d[78]),"+f"(d[79]),"+f"(d[80]),"+f"(d[81]),"+f"(d[82]),"+f"(d[83]),"+f"(d[84]),"+f"(d[85]),"+f"(d[86]),"+f"(d[87]),"+f"(d[88]),"+f"(d[89]),"+f"(d[90]),"+f"(d[91]),"+f"(d[92]),"+f"(d[93]),"+f"(d[94]),"+f"(d[95]),"+f"(d[96]),"+f"(d[97]),"+f"(d[98]),"+f"(d[99]),"+f"(d[100]),"+f"(d[101]),"+f"(d[102]),"+f"(d[103]),"+f"(d[104]),"+f"(d[105]),"+f"(d[106]),"+f"(d[107]) : "l"(da), "l"(db), "r"(sd));
}
__device__ __forceinline__ void wg_ss_160(float (&d)[80], uint64_t da, uint64_t db, int sd) {
  asm volatile("{\n.reg .pred p;\nsetp.ne.b32 p, %82, 0;\n"
    "wgmma.mma_async.sync.aligned.m64n160k16.f32.bf16.bf16 {%0,%1,%2,%3,%4,%5,%6,%7,%8,%9,%10,%11,%12,%13,%14,%15,%16,%17,%18,%19,%20,%21,%22,%23,%24,%25,%26,%27,%28,%29,%30,%31,%32,%33,%34,%35,%36,%37,%38,%39,%40,%41,%42,%43,%44,%45,%46,%47,%48,%49,%50,%51,%52,%53,%54,%55,%56,%57,%58,%59,%60,%61,%62,%63,%64,%65,%66,%67,%68,%69,%70,%71,%72,%73,%74,%75,%76,%77,%78,%79}, %80, %81, p, 1, 1, 0, 1;\n}\n"
    : "+f"(d[0]),"+f"(d[1]),"+f"(d[2]),"+f"(d[3]),"+f"(d[4]),"+f"(d[5]),"+f"(d[6]),"+f"(d[7]),"+f"(d[8]),"+f"(d[9]),"+f"(d[10]),"+f"(d[11]),"+f"(d[12]),"+f"(d[13]),"+f"(d[14]),"+f"(d[15]),"+f"(d[16]),"+f"(d[17]),"+f"(d[18]),"+f"(d[19]),"+f"(d[20]),"+f"(d[21]),"+f"(d[22]),"+f"(d[23]),"+f"(d[24]),"+f"(d[25]),"+f"(d[26]),"+f"(d[27]),"+f"(d[28]),"+f"(d[29]),"+f"(d[30]),"+f"(d[31]),"+f"(d[32]),"+f"(d[33]),"+f"(d[34]),"+f"(d[35]),"+f"(d[36]),"+f"(d[37]),"+f"(d[38]),"+f"(d[39]),"+f"(d[40]),"+f"(d[41]),"+f"(d[42]),"+f"(d[43]),"+f"(d[44]),"+f"(d[45]),"+f"(d[46]),"+f"(d[47]),"+f"(d[48]),"+f"(d[49]),"+f"(d[50]),"+f"(d[51]),"+f"(d[52]),"+f"(d[53]),"+f"(d[54]),"+f"(d[55]),"+f"(d[56]),"+f"(d[57]),"+f"(d[58]),"+f"(d[59]),"+f"(d[60]),"+f"(d[61]),"+f"(d[62]),"+f"(d[63]),"+f"(d[64]),"+f"(d[65]),"+f"(d[66]),"+f"(d[67]),"+f"(d[68]),"+f"(d[69]),"+f"(d[70]),"+f"(d[71]),"+f"(d[72]),"+f"(d[73]),"+f"(d[74]),"+f"(d[75]),"+f"(d[76]),"+f"(d[77]),"+f"(d[78]),"+f"(d[79]) : "l"(da), "l"(db), "r"(sd));
}
__device__ __forceinline__ void wg_rs_216(float (&d)[108], uint32_t a0, uint32_t a1, uint32_t a2, uint32_t a3, uint64_t db) {
  asm volatile("{\n.reg .pred p;\nsetp.ne.b32 p, 1, 0;\n"
    "wgmma.mma_async.sync.aligned.m64n216k16.f32.bf16.bf16 {%0,%1,%2,%3,%4,%5,%6,%7,%8,%9,%10,%11,%12,%13,%14,%15,%16,%17,%18,%19,%20,%21,%22,%23,%24,%25,%26,%27,%28,%29,%30,%31,%32,%33,%34,%35,%36,%37,%38,%39,%40,%41,%42,%43,%44,%45,%46,%47,%48,%49,%50,%51,%52,%53,%54,%55,%56,%57,%58,%59,%60,%61,%62,%63,%64,%65,%66,%67,%68,%69,%70,%71,%72,%73,%74,%75,%76,%77,%78,%79,%80,%81,%82,%83,%84,%85,%86,%87,%88,%89,%90,%91,%92,%93,%94,%95,%96,%97,%98,%99,%100,%101,%102,%103,%104,%105,%106,%107}, {%108,%109,%110,%111}, %112, p, 1, 1, 1;\n}\n"
    : "+f"(d[0]),"+f"(d[1]),"+f"(d[2]),"+f"(d[3]),"+f"(d[4]),"+f"(d[5]),"+f"(d[6]),"+f"(d[7]),"+f"(d[8]),"+f"(d[9]),"+f"(d[10]),"+f"(d[11]),"+f"(d[12]),"+f"(d[13]),"+f"(d[14]),"+f"(d[15]),"+f"(d[16]),"+f"(d[17]),"+f"(d[18]),"+f"(d[19]),"+f"(d[20]),"+f"(d[21]),"+f"(d[22]),"+f"(d[23]),"+f"(d[24]),"+f"(d[25]),"+f"(d[26]),"+f"(d[27]),"+f"(d[28]),"+f"(d[29]),"+f"(d[30]),"+f"(d[31]),"+f"(d[32]),"+f"(d[33]),"+f"(d[34]),"+f"(d[35]),"+f"(d[36]),"+f"(d[37]),"+f"(d[38]),"+f"(d[39]),"+f"(d[40]),"+f"(d[41]),"+f"(d[42]),"+f"(d[43]),"+f"(d[44]),"+f"(d[45]),"+f"(d[46]),"+f"(d[47]),"+f"(d[48]),"+f"(d[49]),"+f"(d[50]),"+f"(d[51]),"+f"(d[52]),"+f"(d[53]),"+f"(d[54]),"+f"(d[55]),"+f"(d[56]),"+f"(d[57]),"+f"(d[58]),"+f"(d[59]),"+f"(d[60]),"+f"(d[61]),"+f"(d[62]),"+f"(d[63]),"+f"(d[64]),"+f"(d[65]),"+f"(d[66]),"+f"(d[67]),"+f"(d[68]),"+f"(d[69]),"+f"(d[70]),"+f"(d[71]),"+f"(d[72]),"+f"(d[73]),"+f"(d[74]),"+f"(d[75]),"+f"(d[76]),"+f"(d[77]),"+f"(d[78]),"+f"(d[79]),"+f"(d[80]),"+f"(d[81]),"+f"(d[82]),"+f"(d[83]),"+f"(d[84]),"+f"(d[85]),"+f"(d[86]),"+f"(d[87]),"+f"(d[88]),"+f"(d[89]),"+f"(d[90]),"+f"(d[91]),"+f"(d[92]),"+f"(d[93]),"+f"(d[94]),"+f"(d[95]),"+f"(d[96]),"+f"(d[97]),"+f"(d[98]),"+f"(d[99]),"+f"(d[100]),"+f"(d[101]),"+f"(d[102]),"+f"(d[103]),"+f"(d[104]),"+f"(d[105]),"+f"(d[106]),"+f"(d[107]) : "r"(a0), "r"(a1), "r"(a2), "r"(a3), "l"(db));
}
__device__ __forceinline__ void wg_cv_0_0(float (&d)[128], uint32_t a0, uint32_t a1, uint32_t a2, uint32_t a3, uint64_t db) {
  asm volatile("{\n.reg .pred p;\nsetp.ne.b32 p, 0, 0;\n"
    "wgmma.mma_async.sync.aligned.m64n32k16.f32.bf16.bf16 {%0,%1,%2,%3,%4,%5,%6,%7,%8,%9,%10,%11,%12,%13,%14,%15}, {%16,%17,%18,%19}, %20, p, 1, 1, 0;\n}\n"
    : "+f"(d[0]),"+f"(d[1]),"+f"(d[2]),"+f"(d[3]),"+f"(d[4]),"+f"(d[5]),"+f"(d[6]),"+f"(d[7]),"+f"(d[8]),"+f"(d[9]),"+f"(d[10]),"+f"(d[11]),"+f"(d[12]),"+f"(d[13]),"+f"(d[14]),"+f"(d[15]) : "r"(a0), "r"(a1), "r"(a2), "r"(a3), "l"(db));
}
__device__ __forceinline__ void wg_cv_0_1(float (&d)[128], uint32_t a0, uint32_t a1, uint32_t a2, uint32_t a3, uint64_t db) {
  asm volatile("{\n.reg .pred p;\nsetp.ne.b32 p, 1, 0;\n"
    "wgmma.mma_async.sync.aligned.m64n32k16.f32.bf16.bf16 {%0,%1,%2,%3,%4,%5,%6,%7,%8,%9,%10,%11,%12,%13,%14,%15}, {%16,%17,%18,%19}, %20, p, 1, 1, 0;\n}\n"
    : "+f"(d[0]),"+f"(d[1]),"+f"(d[2]),"+f"(d[3]),"+f"(d[4]),"+f"(d[5]),"+f"(d[6]),"+f"(d[7]),"+f"(d[8]),"+f"(d[9]),"+f"(d[10]),"+f"(d[11]),"+f"(d[12]),"+f"(d[13]),"+f"(d[14]),"+f"(d[15]) : "r"(a0), "r"(a1), "r"(a2), "r"(a3), "l"(db));
}
__device__ __forceinline__ void wg_cv_1_0(float (&d)[128], uint32_t a0, uint32_t a1, uint32_t a2, uint32_t a3, uint64_t db) {
  asm volatile("{\n.reg .pred p;\nsetp.ne.b32 p, 0, 0;\n"
    "wgmma.mma_async.sync.aligned.m64n32k16.f32.bf16.bf16 {%0,%1,%2,%3,%4,%5,%6,%7,%8,%9,%10,%11,%12,%13,%14,%15}, {%16,%17,%18,%19}, %20, p, 1, 1, 0;\n}\n"
    : "+f"(d[16]),"+f"(d[17]),"+f"(d[18]),"+f"(d[19]),"+f"(d[20]),"+f"(d[21]),"+f"(d[22]),"+f"(d[23]),"+f"(d[24]),"+f"(d[25]),"+f"(d[26]),"+f"(d[27]),"+f"(d[28]),"+f"(d[29]),"+f"(d[30]),"+f"(d[31]) : "r"(a0), "r"(a1), "r"(a2), "r"(a3), "l"(db));
}
__device__ __forceinline__ void wg_cv_1_1(float (&d)[128], uint32_t a0, uint32_t a1, uint32_t a2, uint32_t a3, uint64_t db) {
  asm volatile("{\n.reg .pred p;\nsetp.ne.b32 p, 1, 0;\n"
    "wgmma.mma_async.sync.aligned.m64n32k16.f32.bf16.bf16 {%0,%1,%2,%3,%4,%5,%6,%7,%8,%9,%10,%11,%12,%13,%14,%15}, {%16,%17,%18,%19}, %20, p, 1, 1, 0;\n}\n"
    : "+f"(d[16]),"+f"(d[17]),"+f"(d[18]),"+f"(d[19]),"+f"(d[20]),"+f"(d[21]),"+f"(d[22]),"+f"(d[23]),"+f"(d[24]),"+f"(d[25]),"+f"(d[26]),"+f"(d[27]),"+f"(d[28]),"+f"(d[29]),"+f"(d[30]),"+f"(d[31]) : "r"(a0), "r"(a1), "r"(a2), "r"(a3), "l"(db));
}
__device__ __forceinline__ void wg_cv_2_0(float (&d)[128], uint32_t a0, uint32_t a1, uint32_t a2, uint32_t a3, uint64_t db) {
  asm volatile("{\n.reg .pred p;\nsetp.ne.b32 p, 0, 0;\n"
    "wgmma.mma_async.sync.aligned.m64n32k16.f32.bf16.bf16 {%0,%1,%2,%3,%4,%5,%6,%7,%8,%9,%10,%11,%12,%13,%14,%15}, {%16,%17,%18,%19}, %20, p, 1, 1, 0;\n}\n"
    : "+f"(d[32]),"+f"(d[33]),"+f"(d[34]),"+f"(d[35]),"+f"(d[36]),"+f"(d[37]),"+f"(d[38]),"+f"(d[39]),"+f"(d[40]),"+f"(d[41]),"+f"(d[42]),"+f"(d[43]),"+f"(d[44]),"+f"(d[45]),"+f"(d[46]),"+f"(d[47]) : "r"(a0), "r"(a1), "r"(a2), "r"(a3), "l"(db));
}
__device__ __forceinline__ void wg_cv_2_1(float (&d)[128], uint32_t a0, uint32_t a1, uint32_t a2, uint32_t a3, uint64_t db) {
  asm volatile("{\n.reg .pred p;\nsetp.ne.b32 p, 1, 0;\n"
    "wgmma.mma_async.sync.aligned.m64n32k16.f32.bf16.bf16 {%0,%1,%2,%3,%4,%5,%6,%7,%8,%9,%10,%11,%12,%13,%14,%15}, {%16,%17,%18,%19}, %20, p, 1, 1, 0;\n}\n"
    : "+f"(d[32]),"+f"(d[33]),"+f"(d[34]),"+f"(d[35]),"+f"(d[36]),"+f"(d[37]),"+f"(d[38]),"+f"(d[39]),"+f"(d[40]),"+f"(d[41]),"+f"(d[42]),"+f"(d[43]),"+f"(d[44]),"+f"(d[45]),"+f"(d[46]),"+f"(d[47]) : "r"(a0), "r"(a1), "r"(a2), "r"(a3), "l"(db));
}
__device__ __forceinline__ void wg_cv_3_0(float (&d)[128], uint32_t a0, uint32_t a1, uint32_t a2, uint32_t a3, uint64_t db) {
  asm volatile("{\n.reg .pred p;\nsetp.ne.b32 p, 0, 0;\n"
    "wgmma.mma_async.sync.aligned.m64n32k16.f32.bf16.bf16 {%0,%1,%2,%3,%4,%5,%6,%7,%8,%9,%10,%11,%12,%13,%14,%15}, {%16,%17,%18,%19}, %20, p, 1, 1, 0;\n}\n"
    : "+f"(d[48]),"+f"(d[49]),"+f"(d[50]),"+f"(d[51]),"+f"(d[52]),"+f"(d[53]),"+f"(d[54]),"+f"(d[55]),"+f"(d[56]),"+f"(d[57]),"+f"(d[58]),"+f"(d[59]),"+f"(d[60]),"+f"(d[61]),"+f"(d[62]),"+f"(d[63]) : "r"(a0), "r"(a1), "r"(a2), "r"(a3), "l"(db));
}
__device__ __forceinline__ void wg_cv_3_1(float (&d)[128], uint32_t a0, uint32_t a1, uint32_t a2, uint32_t a3, uint64_t db) {
  asm volatile("{\n.reg .pred p;\nsetp.ne.b32 p, 1, 0;\n"
    "wgmma.mma_async.sync.aligned.m64n32k16.f32.bf16.bf16 {%0,%1,%2,%3,%4,%5,%6,%7,%8,%9,%10,%11,%12,%13,%14,%15}, {%16,%17,%18,%19}, %20, p, 1, 1, 0;\n}\n"
    : "+f"(d[48]),"+f"(d[49]),"+f"(d[50]),"+f"(d[51]),"+f"(d[52]),"+f"(d[53]),"+f"(d[54]),"+f"(d[55]),"+f"(d[56]),"+f"(d[57]),"+f"(d[58]),"+f"(d[59]),"+f"(d[60]),"+f"(d[61]),"+f"(d[62]),"+f"(d[63]) : "r"(a0), "r"(a1), "r"(a2), "r"(a3), "l"(db));
}
__device__ __forceinline__ void wg_cv_4_0(float (&d)[128], uint32_t a0, uint32_t a1, uint32_t a2, uint32_t a3, uint64_t db) {
  asm volatile("{\n.reg .pred p;\nsetp.ne.b32 p, 0, 0;\n"
    "wgmma.mma_async.sync.aligned.m64n32k16.f32.bf16.bf16 {%0,%1,%2,%3,%4,%5,%6,%7,%8,%9,%10,%11,%12,%13,%14,%15}, {%16,%17,%18,%19}, %20, p, 1, 1, 0;\n}\n"
    : "+f"(d[64]),"+f"(d[65]),"+f"(d[66]),"+f"(d[67]),"+f"(d[68]),"+f"(d[69]),"+f"(d[70]),"+f"(d[71]),"+f"(d[72]),"+f"(d[73]),"+f"(d[74]),"+f"(d[75]),"+f"(d[76]),"+f"(d[77]),"+f"(d[78]),"+f"(d[79]) : "r"(a0), "r"(a1), "r"(a2), "r"(a3), "l"(db));
}
__device__ __forceinline__ void wg_cv_4_1(float (&d)[128], uint32_t a0, uint32_t a1, uint32_t a2, uint32_t a3, uint64_t db) {
  asm volatile("{\n.reg .pred p;\nsetp.ne.b32 p, 1, 0;\n"
    "wgmma.mma_async.sync.aligned.m64n32k16.f32.bf16.bf16 {%0,%1,%2,%3,%4,%5,%6,%7,%8,%9,%10,%11,%12,%13,%14,%15}, {%16,%17,%18,%19}, %20, p, 1, 1, 0;\n}\n"
    : "+f"(d[64]),"+f"(d[65]),"+f"(d[66]),"+f"(d[67]),"+f"(d[68]),"+f"(d[69]),"+f"(d[70]),"+f"(d[71]),"+f"(d[72]),"+f"(d[73]),"+f"(d[74]),"+f"(d[75]),"+f"(d[76]),"+f"(d[77]),"+f"(d[78]),"+f"(d[79]) : "r"(a0), "r"(a1), "r"(a2), "r"(a3), "l"(db));
}
__device__ __forceinline__ void wg_cv_5_0(float (&d)[128], uint32_t a0, uint32_t a1, uint32_t a2, uint32_t a3, uint64_t db) {
  asm volatile("{\n.reg .pred p;\nsetp.ne.b32 p, 0, 0;\n"
    "wgmma.mma_async.sync.aligned.m64n32k16.f32.bf16.bf16 {%0,%1,%2,%3,%4,%5,%6,%7,%8,%9,%10,%11,%12,%13,%14,%15}, {%16,%17,%18,%19}, %20, p, 1, 1, 0;\n}\n"
    : "+f"(d[80]),"+f"(d[81]),"+f"(d[82]),"+f"(d[83]),"+f"(d[84]),"+f"(d[85]),"+f"(d[86]),"+f"(d[87]),"+f"(d[88]),"+f"(d[89]),"+f"(d[90]),"+f"(d[91]),"+f"(d[92]),"+f"(d[93]),"+f"(d[94]),"+f"(d[95]) : "r"(a0), "r"(a1), "r"(a2), "r"(a3), "l"(db));
}
__device__ __forceinline__ void wg_cv_5_1(float (&d)[128], uint32_t a0, uint32_t a1, uint32_t a2, uint32_t a3, uint64_t db) {
  asm volatile("{\n.reg .pred p;\nsetp.ne.b32 p, 1, 0;\n"
    "wgmma.mma_async.sync.aligned.m64n32k16.f32.bf16.bf16 {%0,%1,%2,%3,%4,%5,%6,%7,%8,%9,%10,%11,%12,%13,%14,%15}, {%16,%17,%18,%19}, %20, p, 1, 1, 0;\n}\n"
    : "+f"(d[80]),"+f"(d[81]),"+f"(d[82]),"+f"(d[83]),"+f"(d[84]),"+f"(d[85]),"+f"(d[86]),"+f"(d[87]),"+f"(d[88]),"+f"(d[89]),"+f"(d[90]),"+f"(d[91]),"+f"(d[92]),"+f"(d[93]),"+f"(d[94]),"+f"(d[95]) : "r"(a0), "r"(a1), "r"(a2), "r"(a3), "l"(db));
}
__device__ __forceinline__ void wg_cv_6_0(float (&d)[128], uint32_t a0, uint32_t a1, uint32_t a2, uint32_t a3, uint64_t db) {
  asm volatile("{\n.reg .pred p;\nsetp.ne.b32 p, 0, 0;\n"
    "wgmma.mma_async.sync.aligned.m64n32k16.f32.bf16.bf16 {%0,%1,%2,%3,%4,%5,%6,%7,%8,%9,%10,%11,%12,%13,%14,%15}, {%16,%17,%18,%19}, %20, p, 1, 1, 0;\n}\n"
    : "+f"(d[96]),"+f"(d[97]),"+f"(d[98]),"+f"(d[99]),"+f"(d[100]),"+f"(d[101]),"+f"(d[102]),"+f"(d[103]),"+f"(d[104]),"+f"(d[105]),"+f"(d[106]),"+f"(d[107]),"+f"(d[108]),"+f"(d[109]),"+f"(d[110]),"+f"(d[111]) : "r"(a0), "r"(a1), "r"(a2), "r"(a3), "l"(db));
}
__device__ __forceinline__ void wg_cv_6_1(float (&d)[128], uint32_t a0, uint32_t a1, uint32_t a2, uint32_t a3, uint64_t db) {
  asm volatile("{\n.reg .pred p;\nsetp.ne.b32 p, 1, 0;\n"
    "wgmma.mma_async.sync.aligned.m64n32k16.f32.bf16.bf16 {%0,%1,%2,%3,%4,%5,%6,%7,%8,%9,%10,%11,%12,%13,%14,%15}, {%16,%17,%18,%19}, %20, p, 1, 1, 0;\n}\n"
    : "+f"(d[96]),"+f"(d[97]),"+f"(d[98]),"+f"(d[99]),"+f"(d[100]),"+f"(d[101]),"+f"(d[102]),"+f"(d[103]),"+f"(d[104]),"+f"(d[105]),"+f"(d[106]),"+f"(d[107]),"+f"(d[108]),"+f"(d[109]),"+f"(d[110]),"+f"(d[111]) : "r"(a0), "r"(a1), "r"(a2), "r"(a3), "l"(db));
}
__device__ __forceinline__ void wg_cv_7_0(float (&d)[128], uint32_t a0, uint32_t a1, uint32_t a2, uint32_t a3, uint64_t db) {
  asm volatile("{\n.reg .pred p;\nsetp.ne.b32 p, 0, 0;\n"
    "wgmma.mma_async.sync.aligned.m64n32k16.f32.bf16.bf16 {%0,%1,%2,%3,%4,%5,%6,%7,%8,%9,%10,%11,%12,%13,%14,%15}, {%16,%17,%18,%19}, %20, p, 1, 1, 0;\n}\n"
    : "+f"(d[112]),"+f"(d[113]),"+f"(d[114]),"+f"(d[115]),"+f"(d[116]),"+f"(d[117]),"+f"(d[118]),"+f"(d[119]),"+f"(d[120]),"+f"(d[121]),"+f"(d[122]),"+f"(d[123]),"+f"(d[124]),"+f"(d[125]),"+f"(d[126]),"+f"(d[127]) : "r"(a0), "r"(a1), "r"(a2), "r"(a3), "l"(db));
}
__device__ __forceinline__ void wg_cv_7_1(float (&d)[128], uint32_t a0, uint32_t a1, uint32_t a2, uint32_t a3, uint64_t db) {
  asm volatile("{\n.reg .pred p;\nsetp.ne.b32 p, 1, 0;\n"
    "wgmma.mma_async.sync.aligned.m64n32k16.f32.bf16.bf16 {%0,%1,%2,%3,%4,%5,%6,%7,%8,%9,%10,%11,%12,%13,%14,%15}, {%16,%17,%18,%19}, %20, p, 1, 1, 0;\n}\n"
    : "+f"(d[112]),"+f"(d[113]),"+f"(d[114]),"+f"(d[115]),"+f"(d[116]),"+f"(d[117]),"+f"(d[118]),"+f"(d[119]),"+f"(d[120]),"+f"(d[121]),"+f"(d[122]),"+f"(d[123]),"+f"(d[124]),"+f"(d[125]),"+f"(d[126]),"+f"(d[127]) : "r"(a0), "r"(a1), "r"(a2), "r"(a3), "l"(db));
}
template <class F> __device__ __forceinline__ void conv_chain_1(float (&d)[128], uint32_t (&a)[64], uint64_t db, uint32_t ab, F hand) {
  wg_cv_7_0(d, a[60], a[61], a[62], a[63], db + (uint64_t)(0));
  wg_cv_6_0(d, a[52], a[53], a[54], a[55], db + (uint64_t)(0));
  wg_cv_7_1(d, a[56], a[57], a[58], a[59], db + (uint64_t)(16));
  wg_cv_5_0(d, a[44], a[45], a[46], a[47], db + (uint64_t)(0));
  wg_cv_6_1(d, a[48], a[49], a[50], a[51], db + (uint64_t)(16));
  wg_cv_7_1(d, a[52], a[53], a[54], a[55], db + (uint64_t)(32));
  wg_cv_5_1(d, a[40], a[41], a[42], a[43], db + (uint64_t)(16));
  wg_cv_6_1(d, a[44], a[45], a[46], a[47], db + (uint64_t)(32));
  wg_cv_7_1(d, a[48], a[49], a[50], a[51], db + (uint64_t)(48));
  wg_cv_6_1(d, a[40], a[41], a[42], a[43], db + (uint64_t)(48));
  wg_cv_7_1(d, a[44], a[45], a[46], a[47], db + (uint64_t)(64));
  wg_cv_7_1(d, a[40], a[41], a[42], a[43], db + (uint64_t)(80));
  wg_commit();
  wg_cv_7_1(d, a[36], a[37], a[38], a[39], db + (uint64_t)(96));
  wg_cv_6_1(d, a[36], a[37], a[38], a[39], db + (uint64_t)(64));
  wg_cv_5_1(d, a[36], a[37], a[38], a[39], db + (uint64_t)(32));
  wg_cv_4_0(d, a[36], a[37], a[38], a[39], db + (uint64_t)(0));
  wg_commit(); wg_wait<1>();
  wg_cv_7_1(d, a[32], a[33], a[34], a[35], db + (uint64_t)(112));
  wg_cv_6_1(d, a[32], a[33], a[34], a[35], db + (uint64_t)(80));
  wg_cv_5_1(d, a[32], a[33], a[34], a[35], db + (uint64_t)(48));
  a[60] = lds32(ab + (3840));
  a[61] = lds32(ab + (3968));
  a[62] = lds32(ab + (3824));
  a[63] = lds32(ab + (3952));
  wg_cv_4_1(d, a[32], a[33], a[34], a[35], db + (uint64_t)(16));
  wg_cv_7_1(d, a[28], a[29], a[30], a[31], db + (uint64_t)(128));
  wg_cv_6_1(d, a[28], a[29], a[30], a[31], db + (uint64_t)(96));
  wg_cv_5_1(d, a[28], a[29], a[30], a[31], db + (uint64_t)(64));
  a[56] = lds32(ab + (3584));
  a[57] = lds32(ab + (3712));
  a[58] = lds32(ab + (3568));
  a[59] = lds32(ab + (3696));
  wg_cv_4_1(d, a[28], a[29], a[30], a[31], db + (uint64_t)(32));
  wg_cv_3_0(d, a[28], a[29], a[30], a[31], db + (uint64_t)(0));
  wg_cv_7_1(d, a[24], a[25], a[26], a[27], db + (uint64_t)(144));
  wg_cv_6_1(d, a[24], a[25], a[26], a[27], db + (uint64_t)(112));
  a[52] = lds32(ab + (3328));
  a[53] = lds32(ab + (3456));
  a[54] = lds32(ab + (3312));
  a[55] = lds32(ab + (3440));
  wg_cv_5_1(d, a[24], a[25], a[26], a[27], db + (uint64_t)(80));
  wg_cv_4_1(d, a[24], a[25], a[26], a[27], db + (uint64_t)(48));
  wg_cv_3_1(d, a[24], a[25], a[26], a[27], db + (uint64_t)(16));
  wg_commit();
  wg_cv_7_1(d, a[20], a[21], a[22], a[23], db + (uint64_t)(160));
  wg_cv_6_1(d, a[20], a[21], a[22], a[23], db + (uint64_t)(128));
  wg_cv_5_1(d, a[20], a[21], a[22], a[23], db + (uint64_t)(96));
  wg_cv_4_1(d, a[20], a[21], a[22], a[23], db + (uint64_t)(64));
  wg_commit(); wg_wait<1>();
  a[48] = lds32(ab + (3072));
  a[49] = lds32(ab + (3200));
  a[50] = lds32(ab + (3056));
  a[51] = lds32(ab + (3184));
  wg_cv_3_1(d, a[20], a[21], a[22], a[23], db + (uint64_t)(32));
  wg_cv_2_0(d, a[20], a[21], a[22], a[23], db + (uint64_t)(0));
  wg_cv_7_1(d, a[16], a[17], a[18], a[19], db + (uint64_t)(176));
  wg_cv_6_1(d, a[16], a[17], a[18], a[19], db + (uint64_t)(144));
  a[44] = lds32(ab + (2816));
  a[45] = lds32(ab + (2944));
  a[46] = lds32(ab + (2800));
  a[47] = lds32(ab + (2928));
  wg_cv_5_1(d, a[16], a[17], a[18], a[19], db + (uint64_t)(112));
  wg_cv_4_1(d, a[16], a[17], a[18], a[19], db + (uint64_t)(80));
  wg_cv_3_1(d, a[16], a[17], a[18], a[19], db + (uint64_t)(48));
  wg_cv_2_1(d, a[16], a[17], a[18], a[19], db + (uint64_t)(16));
  a[40] = lds32(ab + (2560));
  a[41] = lds32(ab + (2688));
  a[42] = lds32(ab + (2544));
  a[43] = lds32(ab + (2672));
  wg_cv_7_1(d, a[12], a[13], a[14], a[15], db + (uint64_t)(192));
  wg_cv_6_1(d, a[12], a[13], a[14], a[15], db + (uint64_t)(160));
  wg_cv_5_1(d, a[12], a[13], a[14], a[15], db + (uint64_t)(128));
  wg_cv_4_1(d, a[12], a[13], a[14], a[15], db + (uint64_t)(96));
  a[36] = lds32(ab + (2304));
  a[37] = lds32(ab + (2432));
  a[38] = lds32(ab + (2288));
  a[39] = lds32(ab + (2416));
  wg_cv_3_1(d, a[12], a[13], a[14], a[15], db + (uint64_t)(64));
  wg_cv_2_1(d, a[12], a[13], a[14], a[15], db + (uint64_t)(32));
  wg_cv_1_0(d, a[12], a[13], a[14], a[15], db + (uint64_t)(0));
  wg_cv_7_1(d, a[8], a[9], a[10], a[11], db + (uint64_t)(208));
  a[32] = lds32(ab + (2048));
  a[33] = lds32(ab + (2176));
  a[34] = lds32(ab + (2032));
  a[35] = lds32(ab + (2160));
  wg_cv_6_1(d, a[8], a[9], a[10], a[11], db + (uint64_t)(176));
  wg_cv_5_1(d, a[8], a[9], a[10], a[11], db + (uint64_t)(144));
  wg_cv_4_1(d, a[8], a[9], a[10], a[11], db + (uint64_t)(112));
  wg_cv_3_1(d, a[8], a[9], a[10], a[11], db + (uint64_t)(80));
  a[28] = lds32(ab + (1792));
  a[29] = lds32(ab + (1920));
  a[30] = lds32(ab + (1776));
  a[31] = lds32(ab + (1904));
  wg_cv_2_1(d, a[8], a[9], a[10], a[11], db + (uint64_t)(48));
  wg_cv_1_1(d, a[8], a[9], a[10], a[11], db + (uint64_t)(16));
  wg_commit();
  wg_cv_7_1(d, a[4], a[5], a[6], a[7], db + (uint64_t)(224));
  wg_cv_6_1(d, a[4], a[5], a[6], a[7], db + (uint64_t)(192));
  wg_cv_5_1(d, a[4], a[5], a[6], a[7], db + (uint64_t)(160));
  wg_cv_4_1(d, a[4], a[5], a[6], a[7], db + (uint64_t)(128));
  wg_commit(); wg_wait<1>();
  a[24] = lds32(ab + (1536));
  a[25] = lds32(ab + (1664));
  a[26] = lds32(ab + (1520));
  a[27] = lds32(ab + (1648));
  hand();
  wg_cv_3_1(d, a[4], a[5], a[6], a[7], db + (uint64_t)(96));
  wg_cv_2_1(d, a[4], a[5], a[6], a[7], db + (uint64_t)(64));
  wg_cv_1_1(d, a[4], a[5], a[6], a[7], db + (uint64_t)(32));
  wg_cv_0_0(d, a[4], a[5], a[6], a[7], db + (uint64_t)(0));
  a[20] = lds32(ab + (1280));
  a[21] = lds32(ab + (1408));
  a[22] = lds32(ab + (1264));
  a[23] = lds32(ab + (1392));
  wg_cv_7_1(d, a[0], a[1], a[2], a[3], db + (uint64_t)(240));
  wg_cv_6_1(d, a[0], a[1], a[2], a[3], db + (uint64_t)(208));
  wg_cv_5_1(d, a[0], a[1], a[2], a[3], db + (uint64_t)(176));
  wg_cv_4_1(d, a[0], a[1], a[2], a[3], db + (uint64_t)(144));
  a[16] = lds32(ab + (1024));
  a[17] = lds32(ab + (1152));
  a[18] = lds32(ab + (1008));
  a[19] = lds32(ab + (1136));
  wg_cv_3_1(d, a[0], a[1], a[2], a[3], db + (uint64_t)(112));
  wg_cv_2_1(d, a[0], a[1], a[2], a[3], db + (uint64_t)(80));
  wg_cv_1_1(d, a[0], a[1], a[2], a[3], db + (uint64_t)(48));
  wg_cv_0_1(d, a[0], a[1], a[2], a[3], db + (uint64_t)(16));
  wg_commit();
  a[12] = lds32(ab + (768));
  a[13] = lds32(ab + (896));
  a[14] = lds32(ab + (752));
  a[15] = lds32(ab + (880));
  a[8] = lds32(ab + (512));
  a[9] = lds32(ab + (640));
  a[10] = lds32(ab + (496));
  a[11] = lds32(ab + (624));
}
template <class F> __device__ __forceinline__ void conv_chain_0(float (&d)[128], uint32_t (&a)[64], uint64_t db, uint32_t ab, F hand) {
  wg_cv_7_0(d, a[60], a[61], a[62], a[63], db + (uint64_t)(0));
  wg_cv_6_0(d, a[52], a[53], a[54], a[55], db + (uint64_t)(0));
  wg_cv_7_1(d, a[56], a[57], a[58], a[59], db + (uint64_t)(16));
  wg_cv_5_0(d, a[44], a[45], a[46], a[47], db + (uint64_t)(0));
  wg_cv_6_1(d, a[48], a[49], a[50], a[51], db + (uint64_t)(16));
  wg_cv_7_1(d, a[52], a[53], a[54], a[55], db + (uint64_t)(32));
  wg_cv_5_1(d, a[40], a[41], a[42], a[43], db + (uint64_t)(16));
  wg_cv_6_1(d, a[44], a[45], a[46], a[47], db + (uint64_t)(32));
  wg_cv_7_1(d, a[48], a[49], a[50], a[51], db + (uint64_t)(48));
  wg_cv_6_1(d, a[40], a[41], a[42], a[43], db + (uint64_t)(48));
  wg_cv_7_1(d, a[44], a[45], a[46], a[47], db + (uint64_t)(64));
  wg_cv_7_1(d, a[40], a[41], a[42], a[43], db + (uint64_t)(80));
  wg_commit();
  wg_cv_7_1(d, a[36], a[37], a[38], a[39], db + (uint64_t)(96));
  wg_cv_6_1(d, a[36], a[37], a[38], a[39], db + (uint64_t)(64));
  wg_cv_5_1(d, a[36], a[37], a[38], a[39], db + (uint64_t)(32));
  wg_cv_4_0(d, a[36], a[37], a[38], a[39], db + (uint64_t)(0));
  wg_cv_7_1(d, a[32], a[33], a[34], a[35], db + (uint64_t)(112));
  wg_cv_6_1(d, a[32], a[33], a[34], a[35], db + (uint64_t)(80));
  wg_cv_5_1(d, a[32], a[33], a[34], a[35], db + (uint64_t)(48));
  wg_cv_4_1(d, a[32], a[33], a[34], a[35], db + (uint64_t)(16));
  wg_cv_7_1(d, a[28], a[29], a[30], a[31], db + (uint64_t)(128));
  wg_cv_6_1(d, a[28], a[29], a[30], a[31], db + (uint64_t)(96));
  wg_cv_5_1(d, a[28], a[29], a[30], a[31], db + (uint64_t)(64));
  wg_cv_4_1(d, a[28], a[29], a[30], a[31], db + (uint64_t)(32));
  wg_cv_3_0(d, a[28], a[29], a[30], a[31], db + (uint64_t)(0));
  wg_cv_7_1(d, a[24], a[25], a[26], a[27], db + (uint64_t)(144));
  wg_cv_6_1(d, a[24], a[25], a[26], a[27], db + (uint64_t)(112));
  wg_cv_5_1(d, a[24], a[25], a[26], a[27], db + (uint64_t)(80));
  wg_cv_4_1(d, a[24], a[25], a[26], a[27], db + (uint64_t)(48));
  wg_cv_3_1(d, a[24], a[25], a[26], a[27], db + (uint64_t)(16));
  wg_commit();
  wg_cv_7_1(d, a[20], a[21], a[22], a[23], db + (uint64_t)(160));
  wg_cv_6_1(d, a[20], a[21], a[22], a[23], db + (uint64_t)(128));
  wg_cv_5_1(d, a[20], a[21], a[22], a[23], db + (uint64_t)(96));
  wg_cv_4_1(d, a[20], a[21], a[22], a[23], db + (uint64_t)(64));
  wg_cv_3_1(d, a[20], a[21], a[22], a[23], db + (uint64_t)(32));
  wg_cv_2_0(d, a[20], a[21], a[22], a[23], db + (uint64_t)(0));
  wg_cv_7_1(d, a[16], a[17], a[18], a[19], db + (uint64_t)(176));
  wg_cv_6_1(d, a[16], a[17], a[18], a[19], db + (uint64_t)(144));
  wg_cv_5_1(d, a[16], a[17], a[18], a[19], db + (uint64_t)(112));
  wg_cv_4_1(d, a[16], a[17], a[18], a[19], db + (uint64_t)(80));
  wg_cv_3_1(d, a[16], a[17], a[18], a[19], db + (uint64_t)(48));
  wg_cv_2_1(d, a[16], a[17], a[18], a[19], db + (uint64_t)(16));
  wg_cv_7_1(d, a[12], a[13], a[14], a[15], db + (uint64_t)(192));
  wg_cv_6_1(d, a[12], a[13], a[14], a[15], db + (uint64_t)(160));
  wg_cv_5_1(d, a[12], a[13], a[14], a[15], db + (uint64_t)(128));
  wg_cv_4_1(d, a[12], a[13], a[14], a[15], db + (uint64_t)(96));
  wg_cv_3_1(d, a[12], a[13], a[14], a[15], db + (uint64_t)(64));
  wg_cv_2_1(d, a[12], a[13], a[14], a[15], db + (uint64_t)(32));
  wg_cv_1_0(d, a[12], a[13], a[14], a[15], db + (uint64_t)(0));
  wg_cv_7_1(d, a[8], a[9], a[10], a[11], db + (uint64_t)(208));
  wg_cv_6_1(d, a[8], a[9], a[10], a[11], db + (uint64_t)(176));
  wg_cv_5_1(d, a[8], a[9], a[10], a[11], db + (uint64_t)(144));
  wg_cv_4_1(d, a[8], a[9], a[10], a[11], db + (uint64_t)(112));
  wg_cv_3_1(d, a[8], a[9], a[10], a[11], db + (uint64_t)(80));
  wg_cv_2_1(d, a[8], a[9], a[10], a[11], db + (uint64_t)(48));
  wg_cv_1_1(d, a[8], a[9], a[10], a[11], db + (uint64_t)(16));
  wg_commit();
  wg_cv_7_1(d, a[4], a[5], a[6], a[7], db + (uint64_t)(224));
  wg_cv_6_1(d, a[4], a[5], a[6], a[7], db + (uint64_t)(192));
  wg_cv_5_1(d, a[4], a[5], a[6], a[7], db + (uint64_t)(160));
  wg_cv_4_1(d, a[4], a[5], a[6], a[7], db + (uint64_t)(128));
  hand();
  wg_cv_3_1(d, a[4], a[5], a[6], a[7], db + (uint64_t)(96));
  wg_cv_2_1(d, a[4], a[5], a[6], a[7], db + (uint64_t)(64));
  wg_cv_1_1(d, a[4], a[5], a[6], a[7], db + (uint64_t)(32));
  wg_cv_0_0(d, a[4], a[5], a[6], a[7], db + (uint64_t)(0));
  wg_cv_7_1(d, a[0], a[1], a[2], a[3], db + (uint64_t)(240));
  wg_cv_6_1(d, a[0], a[1], a[2], a[3], db + (uint64_t)(208));
  wg_cv_5_1(d, a[0], a[1], a[2], a[3], db + (uint64_t)(176));
  wg_cv_4_1(d, a[0], a[1], a[2], a[3], db + (uint64_t)(144));
  wg_cv_3_1(d, a[0], a[1], a[2], a[3], db + (uint64_t)(112));
  wg_cv_2_1(d, a[0], a[1], a[2], a[3], db + (uint64_t)(80));
  wg_cv_1_1(d, a[0], a[1], a[2], a[3], db + (uint64_t)(48));
  wg_cv_0_1(d, a[0], a[1], a[2], a[3], db + (uint64_t)(16));
  wg_commit();
}
constexpr int CV_RELOADED = 2;

struct Params {
  const __nv_bfloat16 *q, *k, *v, *shift_k, *ssm_k, *ssm_D, *w1, *b1, *w2, *b2;
  __nv_bfloat16* out;
};
struct Maps { CUtensorMap qa, w1, w1x, qs, ws, k, v, hs, hx, ha, hn, w2, w2x, kvs, qf, y, out; };

__global__ void __cluster_dims__(2, 1, 1) __launch_bounds__(384, 1) h3_kernel(const __grid_constant__ Maps M, const Params P) {
  extern __shared__ __align__(1024) uint8_t smem_raw[];
  constexpr uint32_t sc = 1024;
  const int tid = threadIdx.x, lane = tid & 31;
  const int warp = __shfl_sync(0xffffffffu, tid >> 5, 0);
  const uint32_t sb = __shfl_sync(0xffffffffu, s32(smem_raw), 0);
  const int b = blockIdx.x, pr = b >> 1;
  const int G = pr < 4 ? 0 : (pr < 36 ? (pr - 4) & 7 : 1 + (pr - 36) % 7), gi = pr < 4 ? 4 + pr : (pr < 36 ? (pr - 4) >> 3 : 4 + (pr - 36) / 7);
  const int kh = b & 1, nt = (G & 1) * 2 + (gi & 1), rb = (G >> 1) * 4 + (gi >> 1);
  const int j = kh * 4 + nt;
  const uint32_t bar = sb + M_BAR;
  auto BAR = [&](int i) { return bar + 8 * i; };
  auto g1_load = [&](int kc) {
    const uint32_t st = sb + (kc & 3) * G1_STAGE, fb = BAR(B_F1 + (kc & 3));
    mbar_expect(fb, G1_TX);
    tma2d(st, &M.qa, kc * 64, rb * 128, fb);
    tma3d(st + 16384, &M.w1, 0, kc * 64, 3 * j, fb);
    tma2d(st + 40960, &M.w1x, 1536 + 24 * j, kc * 64, fb);
  };
  auto kv_load = [&](int r, int hf) {
    const uint32_t st = sb + KVS + (r == 4 ? 2 : r & 1) * KV_BUF, fb = BAR((hf ? B_KIN1 : B_KIN) + r);
    mbar_expect(fb, KV_BUF / 2);
    tma2d(st + 4096 + hf * 2432, &M.k, 128 * r + 64 * (b & 1), 32 * (b >> 1) + 16 * hf - 3, fb);
    tma2d(st + hf * 2048, &M.v, 128 * r + 64 * (b & 1), 32 * (b >> 1) + 16 * hf, fb);
  };
  auto x_load = [&](int c) {
    mbar_expect(BAR(B_XF + c), 4096);
    bulk_g2s(sb + cv_x(c) + XD, g_kvT + (size_t)(128 * c + b) * SL, 4096, BAR(B_XF + c));
  };
  if (warp == 8) {
    if (lane == 0) {
      TS(0);
#pragma unroll
      for (int s = 0; s < 4; s++) mbar_init(BAR(B_F1 + s), 1);
      mbar_init(BAR(B_SIDE), 1);
    }
    __syncwarp();
    bar_arrive(NB_INIT, 384);
    ONE(g1_load(0));
  }
  if ((sb & 0xFFFFFFu) != sc) { if (warp == 8) mbar_wait(BAR(B_F1), 0); return; }

  if (warp >= 8) {
    asm volatile("setmaxnreg.dec.sync.aligned.u32 " REG_AUX ";");
    auto table = [&](int c, int aw) {
      const uint32_t kb = sb + cv_t(c);
      const uint32_t dd = lds32(sb + M_AUX + aw * 32 + c * 4);
      if (lane < 2) sts128(kb + lane * (KT_E - 16), 0u, 0u, 0u, 0u);
      uint4 r[8];
#pragma unroll
      for (int it = 0; it < 8; it++) r[it] = lds128(kb + KT_E + (it * 32 + lane) * 16);
      if (lane == 0) { r[0].x = __byte_perm(badd2(r[0].x, dd), r[0].x, 0x7610); sts32(kb + KT_E, r[0].x); }
#pragma unroll
      for (int it = 0; it < 8; it++) {
        const uint32_t pv = __shfl_sync(0xffffffffu, lane == 31 ? (it ? r[it ? it - 1 : 0].w : 0u) : r[it].w, lane - 1);
        sts128(kb + KT_O + (it * 32 + lane) * 16, __byte_perm(pv, r[it].x, 0x5432), __byte_perm(r[it].x, r[it].y, 0x5432),
               __byte_perm(r[it].y, r[it].z, 0x5432), __byte_perm(r[it].z, r[it].w, 0x5432));
      }
      __syncwarp();
      if (lane == 0) mbar_arrive(BAR(B_KT + c));
    };
    if (warp == 8) {
      auto side_load = [&]() {
        mbar_expect(BAR(B_SIDE), 12288);
        tma2d(sb + SIDE, &M.qs, 448, rb * 128 + j * 16, BAR(B_SIDE));
        tma2d(sb + SIDE + 6144, &M.ws, rb < 12 ? 192 * j + 16 * rb : 1536 + 24 * j + 16 * (rb & 1), 448, BAR(B_SIDE));
      };
      auto g1_ahead = [&]() {
        prefetch_tile(&M.qs, 256, rb * 128 + j * 16);
        prefetch_l2(P.w1 + 256 * FF + b * (192 * FF / NCTA), 192 * FF / NCTA * 2);
        if (PF_G1 & 8) prefetch_l2(P.w1 + 448 * FF + b * (192 * FF / NCTA), 192 * FF / NCTA * 2);
      };
      ONE(g1_load(1); g1_load(2); if ((PF_G1 & 7) == 2) g1_ahead(); g1_load(3); if ((PF_G1 & 7) == 3) g1_ahead());
      bar_sync(NB_INIT2, 128);
#pragma unroll
      for (int kc = 3; kc < 10; kc++) {
        if (kc > 3) mbar_wait(BAR(B_E1 + (kc & 3)), (kc >> 3) & 1);
        ONE(if (kc > 3) g1_load(kc);
            if (kc == SIDE_LD) side_load();
            if (kc == (KV_MAP & 15)) { kv_load(0, 0); kv_load(0, 1); }
            if (kc == (KV_MAP >> 4)) { kv_load(1, 0); kv_load(1, 1); }
            for (int r = 2; r < 5; r++) if (kc == ((PF_KV >> (4 * r)) & 15)) for (int hf = 0; hf < 2; hf++) {
              prefetch_tile(&M.k, 128 * r + 64 * (b & 1), 32 * (b >> 1) + 16 * hf - 3); prefetch_tile(&M.v, 128 * r + 64 * (b & 1), 32 * (b >> 1) + 16 * hf);
            }
            for (int c = 0; c < 5; c++) if (kc == ((PF_RAW >> (4 * c)) & 15)) prefetch_l2(P.ssm_k + (size_t)(128 * c + b) * SL, 4096));
      }
      ONE(prefetch_map(&M.hs); prefetch_map(&M.hx); prefetch_map(&M.ha); prefetch_map(&M.hn); prefetch_map(&M.w2); prefetch_map(&M.w2x));
      mbar_wait(BAR(B_FR + RAW_LATE), 0);
      ONE(mbar_expect(BAR(B_KRAW), 4096); mbar_expect(BAR(B_KRAW + 1), 4 * 4096);
          for (int c = 0; c < 5; c++) bulk_g2s(sb + cv_t(c) + KT_E, P.ssm_k + (size_t)(128 * c + b) * SL, 4096, BAR(B_KRAW + (c >= 1))));
      bar_sync(NB_INIT3, 64);
      const unsigned ep = lds32(sb + M_AUX + 20);
      mbar_wait(BAR(B_KRAW), 0);
      if (lane == 0) TS(35);
#pragma unroll 1
      for (int c = 0; c < TBP; c++) { table(c, 0); mbar_wait(BAR(B_KRAW + 1), 0); }
      if (lane == 0) TS(55);
      const int hc = kh * 896 + nt * 192, hx = kh * 896 + 768 + nt * 24;
#pragma unroll 1
      for (int n = 0; n < 32; n += 4) {
        const int i = (H_ORD >> n) & 7, hw = i >> 2, blk = i & 3;
        if (n == 4 * W2_PF) ONE(prefetch_l2(P.w2 + (size_t)b * (FF * DM / NCTA), FF * DM / NCTA * 2));
        mbar_wait(BAR(B_HB + i), 0);
        fence_async_smem();
        asm volatile("cp.async.bulk.wait_group %0;" ::"n"(H_FLY - 1) : "memory");
        ONE(tma2d_st(blk < 3 ? &M.hs : &M.hx, blk < 3 ? hc + blk * 64 : hx, rb * 128 + hw * 64, sb + hw * HST + blk * 8192); bulk_commit());
      }
      const int cf = (nt * 160 + (nt & 1) * 32) >> 6, ch = nt * 160 + ((nt & 1) ? 0 : 128);
      auto g2_load_b = [&](int kc) {
        const int s = kc & 3, wr = kc < 2 ? 1536 + kh * 96 + (1 - kc) * 64 : kh * 768 + (kc - 2) * 64;
        const uint32_t fb = BAR(B_F2 + s);
        mbar_expect(fb, kc == 0 ? 8192 + 20480 : 16384 + 20480);
        tma3d(sb + g2_b(s), &M.w2, 0, wr, cf, fb);
        tma2d(sb + g2_b(s) + 16384, &M.w2x, ch, wr, fb);
      };
      auto g2_load_a = [&](int kc) {
        const int s = kc & 3;
        tma2d(sb + g2_a(s), kc == 0 ? &M.hn : &M.ha, kh * 896 + (kc < 2 ? 768 + (1 - kc) * 64 : (kc - 2) * 64), rb * 128, BAR(B_F2 + s));
      };
      bulk_wait_all();
      ONE(signal_cnt(CNT_H + rb * 2 + kh); TS(37));
      wait_cnt(CNT_H + rb * 2 + kh, 4 * ep);
      ONE(TS(39); g2_load_b(0); g2_load_a(0); g2_load_b(1); g2_load_a(1); prefetch_map(&M.qf); prefetch_map(&M.y); prefetch_map(&M.out));
      mbar_wait(BAR(B_TD), 0);
      ONE(g2_load_b(3));
      mbar_wait(BAR(B_TD + 1), 0);
      ONE(g2_load_b(2); g2_load_a(2));
      mbar_wait(BAR(B_SD + 3), 0);
      ONE(mbar_expect(BAR(B_FINQ), 20480); tma3d(sb + FIN_Q, &M.qf, 0, rb * 128 + kh * 64, nt * 5, BAR(B_FINQ)));
      mbar_wait(BAR(B_RF + 2), 0);
      ONE(g2_load_a(3); TS(38));
#pragma unroll 1
      for (int kc = 4; kc < 14; kc++) {
        mbar_wait(BAR(B_E2 + (kc & 3)), ((kc >> 2) - 1) & 1);
        ONE(g2_load_b(kc); g2_load_a(kc));
      }
      if (lane == 0) g_launch[b * 8] = ep;
#pragma unroll 1
      for (int i = 0; i < 5; i++) {
        int gi = i + (nt & 1); if (gi == 5) gi = 0;
        mbar_wait(BAR(B_OUT + i), 0);
        fence_async_smem();
        ONE(tma2d_st(&M.out, nt * 160 + gi * 32, rb * 128 + kh * 64, sb + FIN_Q + gi * 4096));
      }
      ONE(bulk_commit());
      bulk_wait_read();
    } else {
      const int aw = warp - 9, at = tid - 288;
      if (aw == 0) {
        if (lane == 0) {
#pragma unroll
          for (int s = 0; s < 4; s++) { mbar_init(BAR(B_E1 + s), 2); mbar_init(BAR(B_FR + s), 2); mbar_init(BAR(B_F2 + s), 1); mbar_init(BAR(B_E2 + s), 2); }
          mbar_init(BAR(B_KRAW), 1); mbar_init(BAR(B_KRAW + 1), 1);
          mbar_init(BAR(B_RED), 8); mbar_init(BAR(B_BX), 1);
        }
      } else if (aw == 1) {
        if (lane == 0) {
#pragma unroll
          for (int c = 0; c < 5; c++) { mbar_init(BAR(B_KT + c), 1); mbar_init(BAR(B_XF + c), 1); mbar_init(BAR(B_SD + c), 4); }
        }
      } else if (lane == 0) {
#pragma unroll
        for (int i = 0; i < 8; i++) mbar_init(BAR(B_HB + i), 4);
#pragma unroll
        for (int c = 0; c < 3; c++) mbar_init(BAR(B_RF + c), 3);
        for (int r = 0; r < 5; r++) { mbar_init(BAR(B_KIN + r), 1); mbar_init(BAR(B_KIN1 + r), 1); }
        mbar_init(BAR(B_YSLOT), 2); mbar_init(BAR(B_XR), 1);
        for (int i = 0; i < 5; i++) mbar_init(BAR(B_OUT + i), 4);
        mbar_init(BAR(B_XD), 1); mbar_expect(BAR(B_XD), 8192); mbar_init(BAR(B_XD + 1), 1); mbar_expect(BAR(B_XD + 1), 12288);
        asm volatile("fence.mbarrier_init.release.cluster;" ::: "memory");
        mbar_init(BAR(B_TD), 2); mbar_init(BAR(B_TD + 1), 8); mbar_init(BAR(B_FINQ), 1); mbar_init(BAR(B_FINY), 1);
      }
      __syncwarp();
      bar_arrive(NB_INIT, 384);
      if (aw == 1) ONE(prefetch_map(&M.qs); prefetch_map(&M.ws); prefetch_map(&M.k); prefetch_map(&M.v));
      const uint32_t dv0 = ld_relaxed32(lane < 5 ? static_cast<const void*>(P.ssm_D + 128 * lane + (b & ~1)) : &g_launch[b * 8]);
      const uint32_t b2v = ldg32(reinterpret_cast<const uint32_t*>(P.b2 + nt * 160) + (min(at, 79) + 16 * (nt & 1)) % 80);
      const int l27 = min(lane, 26), col = l27 < 24 ? 192 * j + 8 * l27 : 1536 + 24 * j + 8 * (l27 - 24);
      uint4 sk = ldg128(aw < 2 ? P.shift_k + (64 * (b & 1) + 2 * lane) * 4 : P.b1 + col);
      bar_sync(NB_INIT2, 128);
      if (aw == 0) ONE(prefetch_map(&M.kvs));
      if (lane < 4) sts32(sb + M_ZERO + lane * 4, 0u);
      if (lane < 8) sts32(sb + M_AUX + aw * 32 + lane * 4, lane >= 5 ? dv0 + 1 : ((b & 1) ? dv0 >> 16 : dv0 & 0xFFFFu));
      if (at < 80) sts32(sb + M_B2 + at * 4, bmul2(b2v, 0x3f003f00u));
      __syncwarp();
      if (aw == 0) bar_arrive(NB_INIT3, 64);
      uint32_t kvok;
      if (aw == 2) {
        const unsigned ep = lds32(sb + M_AUX + 64 + 20);
        const uint4 bb = sk;
        const uint32_t ba = sb + M_BX + (l27 >> 2) * 512 + ((l27 & 3) << 4);
        mbar_wait(BAR(B_RED), 0);
        float c0 = 0.f, c1 = 0.f, s1 = 0.f, s2 = 0.f;
        const float c = bf_round(__uint_as_float(lds32(sb + M_RED + (lane >> 1) * 64)) * (1.f / 80));
#pragma unroll
        for (int i = 0; i < 4; i++) { const float2 u = lds64f(sb + M_RED + 1024 + i * 256 + lane * 8); c0 += u.x; c1 += u.y; }
        c0 += __shfl_xor_sync(0xffffffffu, c0, 8); c1 += __shfl_xor_sync(0xffffffffu, c1, 8);
        const float cc = 80.f * c * c;
#pragma unroll
        for (int i = 0; i < 2; i++) {
          const uint4 u = lds128(sb + M_RED + lane * 32 + ((i + (lane >> 2)) & 1) * 16);
          s1 += fmaf(-80.f, c, __uint_as_float(u.x)) + fmaf(-80.f, c, __uint_as_float(u.z));
          s2 += (fmaf(-2.f * c, __uint_as_float(u.x), __uint_as_float(u.y)) + cc) + (fmaf(-2.f * c, __uint_as_float(u.z), __uint_as_float(u.w)) + cc);
        }
        c0 += __shfl_xor_sync(0xffffffffu, c0, 16); c1 += __shfl_xor_sync(0xffffffffu, c1, 16);
        if (rb < 14 && lane < 8) st_relaxed64(&g_cs[j * 224 + rb * 16 + 2 * lane], (__float_as_uint(c0) & ~15u) | (ep & 15u), (__float_as_uint(c1) & ~15u) | (ep & 15u));
        s1 += __shfl_xor_sync(0xffffffffu, s1, 1); s2 += __shfl_xor_sync(0xffffffffu, s2, 1);
        s1 *= 1.f / DM;
        const float vb = bf_round(fmaxf(fmaf(s2, 1.f / DM, -s1 * s1), 0.f));
        const float sd = bf_round(sqrt_fast(bf_round(vb + 1e-5f)));
        if (!(lane & 1)) st_relaxed64(&g_stat[rb * 128 + j * 16 + (lane >> 1)], pack_bf16(c + s1, sd), ep);
        if (lane == 0) TS(30);
        sts128((ba + 128) ^ 16, 0u, 0u, 0u, 0u); sts128((ba + 192) ^ 16, bb.x, bb.y, bb.z, bb.w);
#pragma unroll
        for (int i = 4; i < 8; i++) sts128((ba + i * 64) ^ ((i >> 1) << 4), 0u, 0u, 0u, 0u);
        if (!KV_LATE) ONE(kv_load(4, 0); kv_load(4, 1));
        if (CS_WAIT) __nanosleep(CS_WAIT);
        uint32_t x[8], n = 0;
        uint4 sa, sc;
        const unsigned* cp = &g_cnt[(CNT_KV + min(lane, 4) * 2 + (b >> 6)) * 32];
#pragma unroll 1
        while (true) {
          const uint4 u0 = ld_relaxed128(g_cs + j * 224 + l27 * 8), u1 = ld_relaxed128(g_cs + j * 224 + l27 * 8 + 4);
          sa = ld_relaxed128(g_stat + rb * 128 + lane * 4); sc = ld_relaxed128(g_stat + rb * 128 + lane * 4 + 2);
          kvok = ld_relaxed32(cp);
          const uint32_t tg = ep & 15u;
          x[0] = u0.x ^ tg; x[1] = u0.y ^ tg; x[2] = u0.z ^ tg; x[3] = u0.w ^ tg; x[4] = u1.x ^ tg; x[5] = u1.y ^ tg; x[6] = u1.z ^ tg; x[7] = u1.w ^ tg;
          const uint32_t bad = ((x[0] | x[1] | x[2] | x[3] | x[4] | x[5] | x[6] | x[7]) & 15u) | (sa.y ^ ep) | (sa.w ^ ep) | (sc.y ^ ep) | (sc.w ^ ep);
          if (__all_sync(0xffffffffu, bad == 0) || spin_guard(n, 0x131)) break;
        }
        sts128(sb + M_STAT + lane * 16, sa.x, sa.z, sc.x, sc.z);
        uint32_t hi[4], lo[4];
#pragma unroll
        for (int i = 0; i < 4; i++) {
          const float x0 = __uint_as_float(x[2 * i]), x1 = __uint_as_float(x[2 * i + 1]);
          hi[i] = pack_bf16(x0, x1); lo[i] = pack_bf16(x0 - bf_lo(hi[i]), x1 - bf_hi(hi[i]));
        }
        sts128(ba, hi[0], hi[1], hi[2], hi[3]); sts128(ba + 64, lo[0], lo[1], lo[2], lo[3]);
        fence_async_smem();
        __syncwarp();
        ONE(mbar_arrive(BAR(B_BX)); TS(54); if (KV_LATE) { kv_load(4, 0); kv_load(4, 1); });
      }
      if (aw < 2) {
        auto done = [&](int r) {
          bulk_wait_all();
          ONE(signal_cnt(CNT_KV + r * 2 + (b & 1)); if (r < 2) kv_load(r + 2, aw); if (r == 4) mbar_arrive(BAR(B_TD));
              TSKV if (aw == 0 && r == 0) TS(33); if (aw == 0 && r == 4) TS(34));
        };
        bool pend = false;
#pragma unroll 1
        for (int r = 0; r < 5; r++) {
          const int c0 = 128 * r + 64 * (b & 1);
          const uint32_t buf = sb + KVS + (r == 4 ? 2 : r & 1) * KV_BUF, stg = buf + aw * 2048, vb = stg + lane * 4, kb = buf + 4096 + aw * 2432 + lane * 4;
          const uint32_t w0 = __byte_perm(sk.x, sk.z, 0x5410), w1 = __byte_perm(sk.x, sk.z, 0x7632);
          const uint32_t w2 = __byte_perm(sk.y, sk.w, 0x5410), w3 = __byte_perm(sk.y, sk.w, 0x7632);
          if (r < 4) sk = ldg128(P.shift_k + (c0 + 128 + 2 * lane) * 4);
          mbar_wait(BAR((aw ? B_KIN1 : B_KIN) + r), 0);
          if (at == 0 && r == 0) TS(56);
          uint32_t kk[19], o[16];
#pragma unroll
          for (int i = 0; i < 19; i++) { kk[i] = lds32(kb + i * 128); if (i >= 3) o[i - 3] = lds32(vb + (i - 3) * 128); }
#pragma unroll
          for (int i = 0; i < 16; i++) o[i] = bmul2(bfma2(kk[i + 3], w0, bfma2(kk[i + 2], w1, bfma2(kk[i + 1], w2, bmul2(kk[i], w3)))), o[i]);
          __syncwarp();
          const uint32_t a0 = stg + lane * 64 + ((lane & 6) << 3);
          const uint32_t s0 = (lane & 4) ? 0x7632 : 0x5410, s1 = s0 ^ 0x2222;
#pragma unroll
          for (int hh = 0; hh < 2; hh++) {
            const uint32_t* u = o + 8 * hh;
            const uint32_t a = a0 ^ (hh << 4);
            sts128(a, __byte_perm(u[1], u[0], s0), __byte_perm(u[3], u[2], s0), __byte_perm(u[5], u[4], s0), __byte_perm(u[7], u[6], s0));
            sts128(a ^ 32, __byte_perm(u[1], u[0], s1), __byte_perm(u[3], u[2], s1), __byte_perm(u[5], u[4], s1), __byte_perm(u[7], u[6], s1));
          }
          if (pend) done(r - 1);
          fence_async_smem();
          __syncwarp();
          ONE(tma2d_st(&M.kvs, 32 * (b >> 1) + 16 * aw, c0, stg); bulk_commit());
          pend = r < 4 && mbar_test(BAR((aw ? B_KIN1 : B_KIN) + r + 1), 0);
          if (!pend) done(r);
        }
      }
      const unsigned ep = lds32(sb + M_AUX + aw * 32 + 20);
      if (aw < 2) {
        mbar_wait(BAR(B_KRAW + 1), 0);
#pragma unroll 1
        for (int c = TBP + aw; c < 5 && TBW == 0; c += 2) table(c, aw);
      } else {
        auto pad = [&](int c0, int c1) {
          if (lane < 17) for (int c = c0; c < c1; c++) sts128(sb + cv_x(c) + lane * 16, 0u, 0u, 0u, 0u);
          fence_async_smem();
          __syncwarp();
        };
        mbar_wait(BAR(B_FR + 1), 0);
        pad(0, 4);
        const unsigned* cp = &g_cnt[(CNT_KV + min(lane, 4) * 2 + (b >> 6)) * 32];
        uint32_t n = 0;
#pragma unroll 1
        for (int c = 0, tb = TBW == 2 ? TBP : 5; c < 5 || tb < 5;) {
          const uint32_t ok = __ballot_sync(0xffffffffu, (int)(kvok - 128 * ep) >= 0) | (spin_guard(n, 0x140) ? 31u : 0u);
#pragma unroll 1
          for (; c < 5 && (ok >> c & 1); c++) {
            if (c == 4) { mbar_wait(BAR(B_TD), 0); pad(4, 5); }
            ONE(x_load(c); if (c == 1) TS(36); if (c >= 3) TS(28 + c));
          }
          if (c < 5) kvok = ld_relaxed32(cp);
          if (TBW == 2 && tb < 5) { mbar_wait(BAR(B_KRAW + 1), 0); table(tb, 2); tb++; }
        }
      }
      if (RED_GATE) mbar_wait(BAR(RED_GATE == 1 ? B_TD + 1 : B_SD + RED_GATE - 1), 0);
#pragma unroll 1
      for (int k = aw, i = 0; k < 20; k += 3, i ^= 1) {
        const int c = k >> 2, ck = (k & 3) * 64 + lane;
        const uint32_t ra = sb + cv_p(c) + ck * 16, ya = sb + (i ? M_BX : YST) + aw * 1024;
        mbar_wait(BAR(B_SD + c), 0);
        uint4 p[2][4];
#pragma unroll
        for (int u = 0; u < 2; u++)
#pragma unroll
          for (int w = 0; w < 4; w++) p[u][w] = lds128((u == 0 && ck < 2 * w) ? sb + M_ZERO : ra + u * 512 + w * (4096 - 32));
        asm volatile("cp.async.bulk.wait_group.read 1;" ::: "memory");
        __syncwarp();
#pragma unroll
        for (int u = 0; u < 2; u++) {
          auto sum = [&](uint32_t a0, uint32_t a1, uint32_t a2, uint32_t a3) { return badd2(badd2(badd2(a3, a2), a1), a0); };
          sts128(ya + lane * 16 + u * 512, sum(p[u][0].x, p[u][1].x, p[u][2].x, p[u][3].x), sum(p[u][0].y, p[u][1].y, p[u][2].y, p[u][3].y),
                 sum(p[u][0].z, p[u][1].z, p[u][2].z, p[u][3].z), sum(p[u][0].w, p[u][1].w, p[u][2].w, p[u][3].w));
        }
        __syncwarp();
        if (c < 3 && (k & 3) && lane == 0) mbar_arrive(BAR(B_RF + c));
        fence_async_smem();
        __syncwarp();
        ONE(bulk_s2g(g_yT + (size_t)(128 * c + b) * SL + (k & 3) * 512, ya, 1024); bulk_commit(); if ((k & 3) == 3) TS(59 + c));
      }
      bulk_wait_all();
      bar_sync(NB_AUX, 96);
      if (aw == 0) {
        ONE(signal_cnt(CNT_Y); TS(3));
        wait_cnt(CNT_Y, 128 * ep);
        ONE(TS(40); mbar_arrive(BAR(B_XR)));
        mbar_wait(BAR(B_YSLOT), 0);
        ONE(mbar_expect(BAR(B_FINY), 20480); tma2d(sb + FIN_Y, &M.y, rb * 128 + kh * 64, nt * 160, BAR(B_FINY)));
      }
    }
  } else {
    asm volatile("setmaxnreg.inc.sync.aligned.u32 " REG_CON ";");
    const int wg = warp >> 2, w = warp & 3, g = lane >> 2, q = lane & 3;
    const bool elect = (tid & 127) == 0;
    uint32_t ca[64];
    const uint32_t ab0 = sb + ((g & 1) ? KT_E : KT_O) + (8 * w + 4 + (g >> 1) - q) * 4;
    auto conv_lda = [&](int c, int k0, int k1) {
      const uint32_t ab = ab0 + cv_t(c);
#pragma unroll
      for (int ks = 15; ks >= 0; ks--) {
        if (ks >= k0 && ks < k1) {
          ca[4 * ks + 0] = lds32(ab + ks * 256);
          ca[4 * ks + 1] = lds32(ab + ks * 256 + 128);
          ca[4 * ks + 2] = lds32(ab + ks * 256 - 16);
          ca[4 * ks + 3] = lds32(ab + ks * 256 + 112);
        }
      }
    };
    {
      float d[108];
      auto g1_release = [&](int kc) { if (elect) mbar_arrive(BAR(kc < 6 ? B_E1 + (kc & 3) : B_FR + kc - 6)); };
      auto g1_wait = [&](int kc) { mbar_wait(BAR(B_F1 + (kc & 3)), (kc >> 2) & 1); };
      auto g1_issue = [&](int kc) {
        const int s = kc & 3;
        if (kc == 0) { mbar_wait(BAR(B_F1), 0); if (wg == 1) bar_sync(NB_LEAD, 256); }
        if (tid == 0) TS(8 + kc);
        const uint32_t st = sc + s * G1_STAGE;
        const uint64_t da = mkdesc(st + wg * 8192, 16, 1024, 1), db = mkdesc(st + 16384, 8192, 1024, 1);
        wg_fence();
#pragma unroll
        for (int k = 0; k < 4; k++) {
          wg_ss_216(d, da + k * 2, db + k * 128, (kc | k) != 0);
          if (k == REL_K || k == 3) wg_commit();
          if (k == REL_K && kc > 0) { wg_wait<1>(); g1_release(kc - 1); }
        }
        if (kc == 0 && wg == 0) bar_arrive(NB_LEAD, 256);
      };
      const int t7 = tid & 127, wr = 2 * (t7 >> 3), wc = 2 * min(rb, 13) + ((t7 >> 2) & 1);
      const uint32_t sa0 = sb + (wg ? 16384 + (wc >> 3) * 8192 + wr * 128 + (((wc ^ wr) & 7) << 4) + (t7 & 3) * 4 : j * 2048 + t7 * 16);
      const uint32_t sa1 = sb + SIDE + (wg ? 6144 + t7 * 4 : (t7 >> 3) * 384 + (t7 & 7) * 16);
      float t1 = 0.f, t2 = 0.f, t3 = 0.f, t4 = 0.f;
      auto piece = [&](int i) {
        if (wg == 0) {
          const uint4 x = lds128(i < 7 ? sa0 + (i & 3) * G1_STAGE : sa1 + (i - 7) * 128);
          const uint32_t xx[4] = {x.x, x.y, x.z, x.w};
#pragma unroll
          for (int e = 0; e < 4; e++) { const float u = bf_lo(xx[e]), v = bf_hi(xx[e]); t1 += u; t3 += v; t2 = fmaf(u, u, t2); t4 = fmaf(v, v, t4); }
        } else {
          uint32_t xx[4];
#pragma unroll
          for (int e = 0; e < 4; e++) xx[e] = lds32(i < 7 ? (sa0 ^ ((e & 1) * 144)) + (e >> 1) * 4096 + (i & 3) * G1_STAGE : sa1 + (i - 7) * 2048 + e * 512);
          t1 += bf_lo(xx[0]); t2 += bf_hi(xx[0]); t3 += bf_lo(xx[1]); t4 += bf_hi(xx[1]);
          t1 += bf_lo(xx[2]); t2 += bf_hi(xx[2]); t3 += bf_lo(xx[3]); t4 += bf_hi(xx[3]);
        }
      };
      bar_sync(NB_INIT, 384);
#pragma unroll
      for (int kc = 0; kc < 10; kc++) {
        g1_issue(kc);
        if (kc == 0) { mbar_wait(BAR(B_F1), 0); piece(0); }
#pragma unroll
        for (int i = 0; i < 3; i++) if (kc == ((SIDE_USE >> (4 * i)) & 15)) { mbar_wait(BAR(B_SIDE), 0); piece(7 + i); }
        if (kc < 9) g1_wait(kc + 1);
        if (kc < 6) piece(kc + 1);
        if (kc == 5) {
          sts64f(sb + M_RED + tid * 8, t1 + t3, t2 + t4);
          __syncwarp();
          if (lane == 0) mbar_arrive(BAR(B_RED));
        }
      }
      uint2 s0, s1;
      {
        mbar_wait(BAR(B_BX), 0);
        s0.x = lds32(sb + M_STAT + (wg * 64 + w * 16 + g) * 4); s1.x = lds32(sb + M_STAT + (wg * 64 + w * 16 + g + 8) * 4);
        if (tid == 0) TS(46);
        const uint32_t f0 = q == 0 ? ((s0.x & 0xFFFFu) * 0x10001u) ^ 0x80008000u : (q == 1 ? s0.x ^ 0x8000u : 0u);
        const uint32_t f1 = q == 0 ? ((s1.x & 0xFFFFu) * 0x10001u) ^ 0x80008000u : (q == 1 ? s1.x ^ 0x8000u : 0u);
        wg_fence();
        wg_rs_216(d, f0, f1, 0u, 0u, mkdesc(sc + M_BX, 512, 0, 2));
        wg_commit();
      }
      wg_wait<1>();
      if (elect) mbar_arrive(BAR(B_FR + 3));
      const float r0 = 0.25f * rcp_fast(bf_hi(s0.x)), r1 = 0.25f * rcp_fast(bf_hi(s1.x));
      if (wg == 0) mbar_wait(BAR(B_FR + 2), 0);
      wg_wait<0>();
      if (elect) TS(1 + 47 * wg);
      if (wg == 1) bar_sync(NB_GELU, 256);
      const int mi = lane >> 3, row = w * 16 + (mi & 1) * 8 + (lane & 7);
      const uint32_t hs = sb + wg * HST;
      constexpr float C1 = 4.f * 0.7978845608028654f, C2 = 64.f * 0.7978845608028654f * 0.044715f;
      auto gelu2 = [&](float hx) { const float u = hx * fmaf(hx * hx, C2, C1); return fmaf(hx, tanh_fast(u), hx); };
#pragma unroll
      for (int nb = 0; nb < 28; nb += 2) {
        uint32_t p[4];
#pragma unroll
        for (int e = 0; e < 2; e++) {
          if (nb + e < 27) {
            const float* dd = d + 4 * (nb + e);
            p[2 * e] = pack_bf16(gelu2(dd[0] * r0), gelu2(dd[1] * r0));
            p[2 * e + 1] = pack_bf16(gelu2(dd[2] * r1), gelu2(dd[3] * r1));
          }
        }
        const int nbm = nb + (mi >> 1);
        if (nb < 24) stsm4(hs + (nb >> 3) * 8192 + row * 128 + (((nbm & 7) ^ (row & 7)) << 4), p[0], p[1], p[2], p[3]);
        else if (nb == 24) stsm4(hs + 24576 + row * 48 + (mi >> 1) * 16, p[0], p[1], p[2], p[3]);
        else stsm2(hs + 24576 + row * 48 + 32, p[0], p[1]);
        if ((nb & 7) == 6 || nb == 26) {
          __syncwarp();
          if (lane == 0) mbar_arrive(BAR(B_HB + wg * 4 + (nb >> 3)));
        }
        if (nb == GELU_NB && wg == 0) bar_arrive(NB_GELU, 256);
        if (nb == A_NB0) mbar_wait(BAR(B_KT + wg), 0);
        if (nb >= A_NB0 && A_NB0 < 28) conv_lda(wg, 16 - ((nb - A_NB0) / 2 + 1) * 16 / (A_NB0 < 28 ? (28 - A_NB0) / 2 : 1), 16 - (nb - A_NB0) / 2 * 16 / (A_NB0 < 28 ? (28 - A_NB0) / 2 : 1));
      }
      if (A_NB0 >= 28) { mbar_wait(BAR(B_KT + wg), 0); conv_lda(wg, 0, 16); }
      if (elect) TS(2 + 47 * wg);
    }
#pragma unroll 1
    for (int c = wg; c < 5; c += 2) {
      float d[128];
      mbar_wait(BAR(B_XF + c), 0);
      if (c < 3) mbar_wait(BAR(B_KT + c + 2), 0);
      const uint64_t db = mkdesc(sc + cv_x(c), 16, 128, 0);
      if (c > 0) { if (wg) bar_sync(NB_TURN + 1, 256); else bar_sync(NB_TURN, 256); }
      wg_fence();
      auto hand = [&]() { if (wg) bar_arrive(NB_TURN, 256); else bar_arrive(NB_TURN + 1, 256); };
      if (c < 3) conv_chain_1(d, ca, db, ab0 + cv_t(c + 2), hand); else conv_chain_0(d, ca, db, 0, hand);
      mbar_wait(BAR(c >= 3 ? B_RF + c - 3 : B_FR + 3), 0);
      wg_wait<0>();
      if (elect) TS(41 + c);
      const uint32_t wa = sb + cv_p(c) + w * 4096 + lane * 16;
#pragma unroll
      for (int n4 = 0; n4 < 32; n4 += 4) {
        uint32_t p[4];
#pragma unroll
        for (int e = 0; e < 4; e++) {
          const int nb = n4 + e;
          float x = d[4 * nb], y = d[4 * nb + 1];
          if (nb > 0) { x += d[4 * nb - 2]; y += d[4 * nb - 1]; }
          p[e] = pack_bf16(x, y);
        }
        stsm4t(wa + n4 * 128, p[0], p[1], p[2], p[3]);
      }
      __syncwarp();
      if (lane == 0) mbar_arrive(BAR(B_SD + c));
      if (c < 3) {
        conv_lda(c + 2, 0, CV_RELOADED);
        __syncwarp();
        if (c > 0 && lane == 0) mbar_arrive(BAR(B_TD + 1));
      }
    }
    if (elect) TS(51 + wg);
    {
      float d[80];
      const uint32_t aoff = (wg ^ kh) * 8192;
      auto g2_release = [&](int kc) { if (elect) mbar_arrive(BAR(kc == 10 ? B_YSLOT : B_E2 + (kc & 3))); };
      auto g2_mma = [&](int kc, int first, bool rel) {
        const int s = kc & 3;
        mbar_wait(BAR(B_F2 + s), (kc >> 2) & 1);
        const uint64_t da = mkdesc(sc + g2_a(s) + aoff, 16, 1024, 1), db = mkdesc(sc + g2_b(s), 8192, 1024, 1);
        wg_fence();
#pragma unroll
        for (int k = 0; k < (kc ? 4 : 2); k++) {
          wg_ss_160(d, da + k * 2, db + k * 128, k ? 1 : first);
          if ((k == REL_K && rel) || k == (kc ? 3 : 1)) wg_commit();
          if (k == REL_K && rel) { wg_wait<1>(); g2_release(kc - 1); }
        }
      };
      if (wg == 1) {
#pragma unroll
        for (int nb = 0; nb < 20; nb++) {
          const uint32_t v = lds32(sb + M_B2 + nb * 16 + q * 4);
          d[4 * nb] = d[4 * nb + 2] = bf_lo(v); d[4 * nb + 1] = d[4 * nb + 3] = bf_hi(v);
        }
        bar_sync(NB_TURN + 1, 256);
        g2_mma(0, 1, false);
#pragma unroll
        for (int kc = 1; kc < 14; kc++) {
          g2_mma(kc, 1, kc < 12);
          if (kc == END_KC) bar_arrive(NB_END, 256);
        }
        mbar_wait(BAR(B_XR), 0);
        wg_wait<0>();
        if (elect) TS(53);
        const uint32_t ra = mapa(sb, kh ^ 1), rbar = ra + M_BAR + 8 * B_XD, dst = ra + (tid & 127) * 16;
#pragma unroll
        for (int i = 0; i < 10; i++) {
          const float* dd = d + 8 * i;
          st_async128(dst + (i < 5 ? P0 + i * 2048 : P1 + (i - 5) * 2048), pack_bf16(dd[0], dd[1]), pack_bf16(dd[2], dd[3]), pack_bf16(dd[4], dd[5]), pack_bf16(dd[6], dd[7]), rbar + 8 * (i >= 4));
        }
        if (elect) TS(7);
      } else {
        const int mi = lane >> 3, row = (mi & 1) * 8 + (lane & 7);
        const uint32_t qa = sb + FIN_Q + (w * 16 + row) * 64;
        auto q_addr = [&](int np) {
          int gi = (np >> 1) + (nt & 1); if (gi == 5) gi = 0;
          return qa + gi * 4096 + ((((np & 1) * 2 + (mi >> 1)) ^ ((row >> 1) & 3)) << 4);
        };
        uint32_t sv[40];
        uint32_t m0, m1; float rs0, rs1;
        g2_mma(0, 0, false);
#pragma unroll
        for (int kc = 1; kc < 10; kc++) {
          if (tid == 0) TS(17 + kc);
          g2_mma(kc, 1, true);
          if (kc == XP_KC - 1) {
            const uint32_t s0 = lds32(sb + M_STAT + (kh * 64 + w * 16 + g) * 4), s1 = lds32(sb + M_STAT + (kh * 64 + w * 16 + g + 8) * 4);
            m0 = (s0 & 0xFFFFu) * 0x10001u; m1 = (s1 & 0xFFFFu) * 0x10001u;
            rs0 = rcp_fast(bf_hi(s0)); rs1 = rcp_fast(bf_hi(s1));
          }
          if (kc >= XP_KC && XP_KC < 10) {
            mbar_wait(BAR(B_FINQ), 0);
#pragma unroll
            for (int np = 10 * (kc - XP_KC) / (XP_KC < 10 ? 10 - XP_KC : 1); np < 10 * (kc + 1 - XP_KC) / (XP_KC < 10 ? 10 - XP_KC : 1); np++) {
              uint32_t xq[4];
              ldsm4(q_addr(np), xq[0], xq[1], xq[2], xq[3]);
#pragma unroll
              for (int e = 0; e < 4; e++) {
                const uint32_t dm = bsub2(xq[e], (e & 1) ? m1 : m0);
                const float rs = (e & 1) ? rs1 : rs0;
                sv[4 * np + e] = pack_bf16(bf_lo(dm) * rs, bf_hi(dm) * rs);
              }
            }
          }
        }
        auto y_prep = [&](int n0, int n1) {
          if (n1 > n0) mbar_wait(BAR(B_FINY), 0);
#pragma unroll
          for (int np = n0; np < n1; np++) {
            int cb = 2 * np + 4 * (nt & 1); if (cb >= 20) cb -= 20;
            cb += mi >> 1;
            const uint32_t ya = sb + FIN_Y + cb * 1024 + (lane & 7) * 128 + (((2 * w + (mi & 1)) ^ (lane & 7)) << 4);
            uint32_t y[4];
            ldsm4t(ya, y[0], y[1], y[2], y[3]);
#pragma unroll
            for (int e = 0; e < 4; e++) sv[4 * np + e] = bmul2(sv[4 * np + e], y[e]);
          }
        };
        if (tid == 0) TS(27);
#pragma unroll
        for (int kc = 10; kc < 14; kc++) {
          g2_mma(kc, 1, kc == 10 || (kc == 11 && HOLD_KC > 10));
          if (kc == HOLD_KC) {
            if (kc == 10) { wg_wait<0>(); g2_release(10); }
            if (tid == 0) TS(28);
            bar_sync(NB_END, 256);
          }
          if (kc == 12) y_prep(0, YP_N);
        }
        if (tid == 0) TS(29);
        y_prep(YP_N, 10);
        if (tid == 0) TS(47);
        mbar_wait(BAR(B_XD), 0);
        if (tid == 0) TS(5);
        uint4 v0 = lds128(sb + tid * 16 + P0), v1 = lds128(sb + tid * 16 + P0 + 2048);
        wg_wait<0>();
        if (tid == 0) TS(4);
#pragma unroll
        for (int np = 0; np < 10; np++) {
          const uint32_t pw[4] = {v0.x, v0.y, v0.z, v0.w};
          v0 = v1;
          if (np < 8) {
            if (np == 2) mbar_wait(BAR(B_XD + 1), 0);
            v1 = lds128(sb + tid * 16 + (np + 2 < 5 ? P0 + (np + 2) * 2048 : P1 + (np - 3) * 2048));
          }
          uint32_t o[4];
          ldsm4(q_addr(np), o[0], o[1], o[2], o[3]);
#pragma unroll
          for (int e = 0; e < 4; e++) {
            const float h0 = d[8 * np + 2 * e] + bf_lo(pw[e]), h1 = d[8 * np + 2 * e + 1] + bf_hi(pw[e]);
            o[e] = bfma2(sv[4 * np + e], pack_bf16(fmaf(h0, tanh_fast(h0), h0), fmaf(h1, tanh_fast(h1), h1)), o[e]);
          }
          stsm4(q_addr(np), o[0], o[1], o[2], o[3]);
          if (np & 1) {
            if (np == 9 && tid == 0) TS(50);
            __syncwarp();
            if (lane == 0) mbar_arrive(BAR(B_OUT + (np >> 1)));
          }
        }
      }
    }
  }
}

typedef CUresult (*EncFn)(CUtensorMap*, CUtensorMapDataType, cuuint32_t, void*, const cuuint64_t*, const cuuint64_t*, const cuuint32_t*, const cuuint32_t*,
                          CUtensorMapInterleave, CUtensorMapSwizzle, CUtensorMapL2promotion, CUtensorMapFloatOOBfill);

static void make_map(EncFn enc, CUtensorMap* tm, const void* ptr, int cols, int rows, int bc, int br, int grp, CUtensorMapSwizzle sw,
                     CUtensorMapL2promotion promo = CU_TENSOR_MAP_L2_PROMOTION_NONE) {
  cuuint64_t gd[3] = {(cuuint64_t)(grp ? bc : cols), (cuuint64_t)rows, (cuuint64_t)(cols / bc)};
  cuuint64_t gs[2] = {(cuuint64_t)cols * 2, (cuuint64_t)bc * 2};
  cuuint32_t bd[3] = {(cuuint32_t)bc, (cuuint32_t)br, (cuuint32_t)grp};
  cuuint32_t es[3] = {1, 1, 1};
  CUresult r = enc(tm, CU_TENSOR_MAP_DATA_TYPE_BFLOAT16, grp ? 3 : 2, const_cast<void*>(ptr), gd, gs, bd, es, CU_TENSOR_MAP_INTERLEAVE_NONE, sw,
                   promo, CU_TENSOR_MAP_FLOAT_OOB_FILL_NONE);
  (void)r;
}

}

extern "C" void kernel_launch(void* const* d_in, const int* in_sizes, int n_in, void* d_out, int out_size) {
  using namespace h3;
  (void)in_sizes; (void)n_in; (void)out_size;
  static EncFn enc = nullptr;
  static void *p_h = nullptr, *p_yT = nullptr, *p_kvT = nullptr;
  if (!enc) {
    void* fn = nullptr; cudaDriverEntryPointQueryResult qr;
    cudaGetDriverEntryPoint("cuTensorMapEncodeTiled", &fn, cudaEnableDefault, &qr);
    enc = (EncFn)fn;
    cudaGetSymbolAddress(&p_h, g_h);
    cudaGetSymbolAddress(&p_yT, g_yT);
    cudaGetSymbolAddress(&p_kvT, g_kvT);
    cudaFuncSetAttribute(h3_kernel, cudaFuncAttributeMaxDynamicSharedMemorySize, SMEM_BYTES);
  }
  Params P;
  P.q = (const __nv_bfloat16*)d_in[0]; P.k = (const __nv_bfloat16*)d_in[1]; P.v = (const __nv_bfloat16*)d_in[2];
  P.shift_k = (const __nv_bfloat16*)d_in[3]; P.ssm_k = (const __nv_bfloat16*)d_in[4]; P.ssm_D = (const __nv_bfloat16*)d_in[5];
  P.out = (__nv_bfloat16*)d_out;
  P.w1 = (const __nv_bfloat16*)d_in[7]; P.b1 = (const __nv_bfloat16*)d_in[8]; P.w2 = (const __nv_bfloat16*)d_in[9]; P.b2 = (const __nv_bfloat16*)d_in[10];
  const CUtensorMapSwizzle S128 = CU_TENSOR_MAP_SWIZZLE_128B, S64 = CU_TENSOR_MAP_SWIZZLE_64B, S0 = CU_TENSOR_MAP_SWIZZLE_NONE;
  Maps M;
  make_map(enc, &M.qa, P.q, DM, SL, 64, 128, 0, S128);
  make_map(enc, &M.w1, P.w1, FF, DM, 64, 64, 3, S128);
  make_map(enc, &M.w1x, P.w1, FF, DM, 24, 64, 0, S128, WS_PROMO);
  make_map(enc, &M.qs, P.q, DM, SL, 192, 16, 0, S0);
  make_map(enc, &M.ws, P.w1, FF, DM, 16, 192, 0, S0, WS_PROMO);
  make_map(enc, &M.k, P.k, DM, SL, 64, 19, 0, S0);
  make_map(enc, &M.v, P.v, DM, SL, 64, 16, 0, S0);
  make_map(enc, &M.hs, p_h, HP, SL, 64, 64, 0, S128);
  make_map(enc, &M.hx, p_h, HP, SL, 24, 64, 0, S0);
  make_map(enc, &M.ha, p_h, HP, SL, 64, 128, 0, S128);
  make_map(enc, &M.hn, p_h, HP, SL, 32, 128, 0, S128);
  make_map(enc, &M.w2, P.w2, DM, FF, 64, 64, 2, S128);
  make_map(enc, &M.w2x, P.w2, DM, FF, 32, 64, 0, S128);
  make_map(enc, &M.kvs, p_kvT, SL, DM, 16, 64, 0, CU_TENSOR_MAP_SWIZZLE_32B);
  make_map(enc, &M.qf, P.q, DM, SL, 32, 64, 5, S64);
  make_map(enc, &M.y, p_yT, SL, DM, 64, 160, 0, S128);
  make_map(enc, &M.out, d_out, DM, SL, 32, 64, 0, S64);
  h3_kernel<<<NCTA, 384, SMEM_BYTES>>>(M, P);
}
```

```cpp
#include <cuda_runtime.h>
#include <cuda_bf16.h>
#include <cuda.h>
#include <stdint.h>

namespace h3 {

constexpr int SL = 2048, DM = 640, FF = 1728, HP = 1792;
constexpr int NCTA = 128;

__device__ __align__(1024) __nv_bfloat16 g_h[SL * HP];
__device__ __align__(1024) __nv_bfloat16 g_kvT[DM * SL];
__device__ __align__(1024) __nv_bfloat16 g_yT[DM * SL];
__device__ __align__(1024) uint2 g_stat[2 * SL];
__device__ __align__(1024) uint32_t g_cs[2 * 8 * 256];
__device__ __align__(1024) unsigned g_cnt[64 * 32];
__device__ __align__(1024) unsigned g_launch[NCTA * 8];
constexpr int CNT_KV = 0, CNT_Y = 10, CNT_H = 16;

constexpr int G1_STAGE = 49152, G1_TX = 16384 + 24576 + 3072;
constexpr int HST = 49152;
constexpr int P0 = 81920, P1 = 140288, P2 = 156672;
constexpr int XCH = 4368, XD = 272, X0 = 173056, X4 = 221184;
constexpr int KVS = 196608, KV_BUF = 8960;
constexpr int KT_CH = 8240, KT_O = 16, KT_E = 4144, KT0 = 98304;
constexpr int FIN_Q = X0, FIN_Y = 98304;
constexpr int MISC = 226816;
constexpr int M_BX = MISC;
constexpr int M_RED0 = KVS + 3 * KV_BUF, M_RED1 = M_BX;
constexpr int M_STAT = M_BX + 3584;
constexpr int M_B2 = M_STAT + 512;
constexpr int M_AUX = M_B2 + 320;
constexpr int M_ZERO = M_AUX + 96;
constexpr int M_BAR = M_ZERO + 16;
constexpr int M_TS = M_BAR + 80 * 8;
constexpr int SMEM_BYTES = M_TS + 256;
__host__ __device__ constexpr int cv_x(int c) { return c == 4 ? X4 : X0 + c * XCH; }
__host__ __device__ constexpr int cv_p(int c) { return c == 2 ? P2 : ((c == 0 || c == 3) ? P0 : P1); }
__host__ __device__ constexpr int cv_t(int c) { return KT0 + c * KT_CH; }
__host__ __device__ constexpr int g2_a(int s) { return s == 0 ? 0 : (s == 1 ? 40960 : (s == 2 ? 98304 : P2)); }
__host__ __device__ constexpr int g2_b(int s) { return s == 0 ? 16384 : (s == 1 ? 57344 : (s == 2 ? 114688 : KVS)); }
static_assert(M_RED0 + 2048 <= MISC && X4 + XCH <= MISC && KVS + 24576 <= X4 && X0 + 4 * XCH <= KVS && FIN_Q + 20480 <= KVS, "smem");
static_assert(KT0 + 5 * KT_CH <= P1 && P1 + 16384 <= P2 && P2 + 16384 <= X0 && SMEM_BYTES <= 232448 && MISC % 512 == 0 && M_BAR % 8 == 0, "smem");
constexpr int B_F1 = 0, B_E1 = 4, B_FR = 8, B_F2 = 12, B_E2 = 16, B_KRAW = 20, B_KT = 22, B_XF = 27, B_HB = 32, B_SD = 40, B_RF = 45,
              B_TD = 48, B_FINQ = 50, B_FINY = 51, B_RED = 52, B_BX = 53, B_KIN = 54, B_XR = 59, B_OUT = 61, B_SIDE = 66, B_YSLOT = 67, B_XD = 68, B_KIN1 = 70, B_KD = 75;
constexpr int NB_INIT = 1, NB_INIT2 = 2, NB_AUX = 3, NB_LEAD = 4, NB_GELU = 5, NB_TURN = 6  , NB_END = 8, NB_INIT3 = 9, NB_WG1 = 10;

#define KV_MAP 0x543
#define KV_LATE 1
#define PF_KV 0
#define PF_G1 0
#define WS_PROMO CU_TENSOR_MAP_L2_PROMOTION_L2_128B
#define RAW_LATE 0
#define PF_RAW 0
#define SIDE_LD 4
#define SIDE_USE 0x554
#define REL_K 0
#define CS_WAIT 1
#define GELU_NB 8
#define H_ORD 0x73625410
#define W2_PF 0
#define H_FLY 8
#define TB2 2
#define SIG_P 3
#define SIG_A 2
#define A_NB0 12
#define RED_GATE 0
#define SUM3 0
#define SIG_W 0
#define XP_KC 4
#define YP_N 4
#define HOLD_KC 11
#define END_KC 13
#define REG_AUX "56"
#define REG_CON "224"
#define LDQ ".nc.L1::no_allocate"
#define LDP ""

__device__ __forceinline__ uint32_t s32(const void* p) { return (uint32_t)__cvta_generic_to_shared(p); }
__device__ __forceinline__ uint32_t clk() { uint32_t t; asm volatile("mov.u32 %0, %%clock;" : "=r"(t)); return t; }
__device__ __forceinline__ bool elect_one() {
  uint32_t p; asm volatile("{\n.reg .pred P;\nelect.sync _|P, 0xffffffff;\nselp.u32 %0, 1, 0, P;\n}" : "=r"(p)); return p;
}
#define ONE(...) do { if (elect_one()) { __VA_ARGS__; } __syncwarp(); } while (0)
__device__ __forceinline__ void mbar_init(uint32_t a, int c) { asm volatile("mbarrier.init.shared::cta.b64 [%0], %1;" ::"r"(a), "r"(c) : "memory"); }
__device__ __forceinline__ void mbar_expect(uint32_t a, int b) { asm volatile("mbarrier.arrive.expect_tx.shared::cta.b64 _, [%0], %1;" ::"r"(a), "r"(b) : "memory"); }
__device__ __forceinline__ void mbar_arrive(uint32_t a) { asm volatile("mbarrier.arrive.shared::cta.b64 _, [%0];" ::"r"(a) : "memory"); }
__device__ __forceinline__ bool spin_guard(uint32_t& n, uint32_t) {
  return ++n > (1u << 20);
}
__device__ __forceinline__ void mbar_wait(uint32_t a, int ph) {
  asm volatile("{\n.reg .pred p;\n.reg .u32 n;\nmov.u32 n, 0;\nW:\n.pragma \"nounroll\";\nmbarrier.try_wait.parity.shared::cta.b64 p, [%0], %1;\n"
               "add.u32 n, n, 1;\nsetp.ge.or.u32 p, n, 0x100000, p;\n@!p bra W;\n}" ::"r"(a), "r"(ph) : "memory");
}
__device__ __forceinline__ bool mbar_test(uint32_t a, int ph) {
  uint32_t ok;
  asm volatile("{\n.reg .pred p;\nmbarrier.test_wait.parity.shared::cta.b64 p, [%1], %2;\nselp.u32 %0, 1, 0, p;\n}" : "=r"(ok) : "r"(a), "r"(ph) : "memory");
  return __all_sync(0xffffffffu, ok);
}
__device__ __forceinline__ void tma2d(uint32_t dst, const CUtensorMap* tm, int c0, int c1, uint32_t bar) {
  asm volatile("cp.async.bulk.tensor.2d.shared::cluster.global.mbarrier::complete_tx::bytes [%0], [%1, {%3, %4}], [%2];"
               ::"r"(dst), "l"(tm), "r"(bar), "r"(c0), "r"(c1) : "memory");
}
__device__ __forceinline__ void tma3d(uint32_t dst, const CUtensorMap* tm, int c0, int c1, int c2, uint32_t bar) {
  asm volatile("cp.async.bulk.tensor.3d.shared::cluster.global.mbarrier::complete_tx::bytes [%0], [%1, {%3, %4, %5}], [%2];"
               ::"r"(dst), "l"(tm), "r"(bar), "r"(c0), "r"(c1), "r"(c2) : "memory");
}
__device__ __forceinline__ void tma2d_st(const CUtensorMap* tm, int c0, int c1, uint32_t src) {
  asm volatile("cp.async.bulk.tensor.2d.global.shared::cta.bulk_group [%0, {%2, %3}], [%1];" ::"l"(tm), "r"(src), "r"(c0), "r"(c1) : "memory");
}
__device__ __forceinline__ void tma3d_st(const CUtensorMap* tm, int c0, int c1, int c2, uint32_t src) {
  asm volatile("cp.async.bulk.tensor.3d.global.shared::cta.bulk_group [%0, {%2, %3, %4}], [%1];" ::"l"(tm), "r"(src), "r"(c0), "r"(c1), "r"(c2) : "memory");
}
__device__ __forceinline__ void bulk_g2s(uint32_t dst, const void* src, int bytes, uint32_t bar) {
  asm volatile("cp.async.bulk.shared::cluster.global.mbarrier::complete_tx::bytes [%0], [%1], %2, [%3];" ::"r"(dst), "l"(src), "r"(bytes), "r"(bar) : "memory");
}
__device__ __forceinline__ void bulk_commit() { asm volatile("cp.async.bulk.commit_group;" ::: "memory"); }
__device__ __forceinline__ void bulk_wait_read() { asm volatile("cp.async.bulk.wait_group.read 0;" ::: "memory"); }
__device__ __forceinline__ void bulk_wait_all() { asm volatile("cp.async.bulk.wait_group 0;" ::: "memory"); }
__device__ __forceinline__ void fence_async_smem() { asm volatile("fence.proxy.async.shared::cta;" ::: "memory"); }
__device__ __forceinline__ void fence_async_all() { asm volatile("fence.proxy.async;" ::: "memory"); }
__device__ __forceinline__ void fence_gpu() { asm volatile("fence.acq_rel.gpu;" ::: "memory"); }
#define bar_sync(id, n) asm volatile("bar.sync %0, %1;" ::"n"(id), "n"(n) : "memory")
#define bar_arrive(id, n) asm volatile("bar.arrive %0, %1;" ::"n"(id), "n"(n) : "memory")
__device__ __forceinline__ void wg_fence() { asm volatile("wgmma.fence.sync.aligned;" ::: "memory"); }
__device__ __forceinline__ void wg_commit() { asm volatile("wgmma.commit_group.sync.aligned;" ::: "memory"); }
template <int N> __device__ __forceinline__ void wg_wait() { asm volatile("wgmma.wait_group.sync.aligned %0;" ::"n"(N) : "memory"); }
__device__ __forceinline__ uint64_t mkdesc(uint32_t addr, uint32_t lbo, uint32_t sbo, int sw) {
  return (uint64_t)((addr & 0x3FFFF) >> 4) | ((uint64_t)(lbo >> 4) << 16) | ((uint64_t)(sbo >> 4) << 32) | ((uint64_t)sw << 62);
}
__device__ __forceinline__ uint32_t ldg32(const void* p) { uint32_t v; asm volatile("ld.global" LDQ ".b32 %0, [%1];" : "=r"(v) : "l"(p)); return v; }
template <int OFF> __device__ __forceinline__ uint32_t ldg32o(const void* p) { uint32_t v; asm volatile("ld.global" LDQ ".b32 %0, [%1+%2];" : "=r"(v) : "l"(p), "n"(OFF)); return v; }
template <int I> __device__ __forceinline__ void kv_loads(const void* kp, const void* vp, uint32_t (&kk)[16], uint32_t (&o)[16]) {
  kk[I] = ldg32o<I * DM * 2>(kp); o[I] = ldg32o<I * DM * 2>(vp);
  if constexpr (I < 15) kv_loads<I + 1>(kp, vp, kk, o);
}
__device__ __forceinline__ uint4 ldg128(const void* p) {
  uint4 v; asm volatile("ld.global" LDQ LDP ".v4.b32 {%0,%1,%2,%3}, [%4];" : "=r"(v.x), "=r"(v.y), "=r"(v.z), "=r"(v.w) : "l"(p)); return v;
}
__device__ __forceinline__ void stg128(void* p, uint32_t x, uint32_t y, uint32_t z, uint32_t w) {
  asm volatile("st.global.v4.b32 [%0], {%1,%2,%3,%4};" ::"l"(p), "r"(x), "r"(y), "r"(z), "r"(w) : "memory");
}
__device__ __forceinline__ uint4 ld_relaxed128(const void* p) {
  uint4 v; asm volatile("ld.relaxed.gpu.global.v4.b32 {%0,%1,%2,%3}, [%4];" : "=r"(v.x), "=r"(v.y), "=r"(v.z), "=r"(v.w) : "l"(p) : "memory"); return v;
}
__device__ __forceinline__ uint2 ld_relaxed64(const void* p) {
  uint2 v; asm volatile("ld.relaxed.gpu.global.v2.b32 {%0,%1}, [%2];" : "=r"(v.x), "=r"(v.y) : "l"(p) : "memory"); return v;
}
__device__ __forceinline__ uint4 ld_relaxed_b128(const void* p) {
  uint4 v; asm volatile("{\n.reg .b128 t;\nld.relaxed.gpu.global.b128 t, [%4];\nmov.b128 {%0,%1,%2,%3}, t;\n}" : "=r"(v.x), "=r"(v.y), "=r"(v.z), "=r"(v.w) : "l"(p) : "memory"); return v;
}
__device__ __forceinline__ void st_relaxed_b128(void* p, uint32_t x, uint32_t y, uint32_t z, uint32_t w) {
  asm volatile("{\n.reg .b128 t;\nmov.b128 t, {%1,%2,%3,%4};\nst.relaxed.gpu.global.b128 [%0], t;\n}" ::"l"(p), "r"(x), "r"(y), "r"(z), "r"(w) : "memory");
}
__device__ __forceinline__ void st_relaxed64(void* p, uint32_t x, uint32_t y) {
  asm volatile("{\n.reg .b64 t;\nmov.b64 t, {%1,%2};\nst.relaxed.gpu.global.b64 [%0], t;\n}" ::"l"(p), "r"(x), "r"(y) : "memory");
}
__device__ __forceinline__ void st_relaxed32(void* p, uint32_t x) { asm volatile("st.relaxed.gpu.global.b32 [%0], %1;" ::"l"(p), "r"(x) : "memory"); }
__device__ __forceinline__ uint32_t ld_relaxed32(const void* p) { uint32_t v; asm volatile("ld.relaxed.gpu.global.b32 %0, [%1];" : "=r"(v) : "l"(p) : "memory"); return v; }
__device__ __forceinline__ void st_relaxed128(void* p, uint32_t x, uint32_t y, uint32_t z, uint32_t w) {
  asm volatile("{\n.reg .b64 t, u;\nmov.b64 t, {%1,%2};\nmov.b64 u, {%3,%4};\nst.relaxed.gpu.global.v2.b64 [%0], {t, u};\n}" ::"l"(p), "r"(x), "r"(y), "r"(z), "r"(w) : "memory");
}
__device__ __forceinline__ void fence_release() { asm volatile("fence.proxy.async.global;\nfence.release.gpu;" ::: "memory"); }
__device__ __forceinline__ void fence_acquire() { asm volatile("fence.acquire.gpu;\nfence.proxy.async.global;" ::: "memory"); }
__device__ __forceinline__ void signal_cnt(int idx) { asm volatile("red.relaxed.gpu.global.add.u32 [%0], 1;" ::"l"(&g_cnt[idx * 32]) : "memory"); }
__device__ __forceinline__ void wait_cnt(int idx, unsigned target) {
  uint32_t n = 0;
#pragma unroll 1
  while (!__all_sync(0xffffffffu, (int)(ld_relaxed32(&g_cnt[idx * 32]) - target) >= 0)) {
    if (spin_guard(n, 0x100 + idx)) break;
  }
  fence_acquire();
}
__device__ __forceinline__ void bulk_s2g(void* dst, uint32_t src, int bytes) {
  asm volatile("cp.async.bulk.global.shared::cta.bulk_group [%0], [%1], %2;" ::"l"(dst), "r"(src), "r"(bytes) : "memory");
}
__device__ __forceinline__ void bulk_add_s2g(void* dst, uint32_t src, int bytes) {
  asm volatile("cp.reduce.async.bulk.global.shared::cta.bulk_group.add.noftz.bf16 [%0], [%1], %2;" ::"l"(dst), "r"(src), "r"(bytes) : "memory");
}
__device__ __forceinline__ void prefetch_l2(const void* p, int bytes) { asm volatile("cp.async.bulk.prefetch.L2.global [%0], %1;" ::"l"(p), "r"(bytes) : "memory"); }
__device__ __forceinline__ void prefetch_tile(const CUtensorMap* tm, int c0, int c1) {
  asm volatile("cp.async.bulk.prefetch.tensor.2d.L2.global.tile [%0, {%1, %2}];" ::"l"(tm), "r"(c0), "r"(c1) : "memory");
}
__device__ __forceinline__ void prefetch_map(const CUtensorMap* tm) { asm volatile("prefetch.tensormap [%0];" ::"l"(tm) : "memory"); }
__device__ __forceinline__ uint32_t pack_bf16(float lo, float hi) {
  uint32_t r; asm("cvt.rn.bf16x2.f32 %0, %1, %2;" : "=r"(r) : "f"(hi), "f"(lo)); return r;
}
__device__ __forceinline__ float bf_lo(uint32_t v) { return __uint_as_float(v << 16); }
__device__ __forceinline__ float bf_hi(uint32_t v) { return __uint_as_float(v & 0xFFFF0000u); }
__device__ __forceinline__ float bf_round(float x) { return __bfloat162float(__float2bfloat16_rn(x)); }
__device__ __forceinline__ uint32_t bmul2(uint32_t a, uint32_t b) { uint32_t r; asm("mul.rn.bf16x2 %0, %1, %2;" : "=r"(r) : "r"(a), "r"(b)); return r; }
__device__ __forceinline__ uint32_t bfma2(uint32_t a, uint32_t b, uint32_t c) { uint32_t r; asm("fma.rn.bf16x2 %0, %1, %2, %3;" : "=r"(r) : "r"(a), "r"(b), "r"(c)); return r; }
__device__ __forceinline__ uint32_t badd2(uint32_t a, uint32_t b) { uint32_t r; asm("add.rn.bf16x2 %0, %1, %2;" : "=r"(r) : "r"(a), "r"(b)); return r; }
__device__ __forceinline__ uint32_t bsub2(uint32_t a, uint32_t b) { uint32_t r; asm("sub.rn.bf16x2 %0, %1, %2;" : "=r"(r) : "r"(a), "r"(b)); return r; }
__device__ __forceinline__ float tanh_fast(float x) { float r; asm("tanh.approx.f32 %0, %1;" : "=f"(r) : "f"(x)); return r; }
__device__ __forceinline__ float rcp_fast(float x) { float r; asm("rcp.approx.ftz.f32 %0, %1;" : "=f"(r) : "f"(x)); return r; }
__device__ __forceinline__ float sqrt_fast(float x) { float r; asm("sqrt.approx.ftz.f32 %0, %1;" : "=f"(r) : "f"(x)); return r; }
__device__ __forceinline__ uint32_t lds32(uint32_t a) { uint32_t v; asm volatile("ld.shared.b32 %0, [%1];" : "=r"(v) : "r"(a)); return v; }
__device__ __forceinline__ uint4 lds128(uint32_t a) { uint4 v; asm volatile("ld.shared.v4.b32 {%0,%1,%2,%3}, [%4];" : "=r"(v.x), "=r"(v.y), "=r"(v.z), "=r"(v.w) : "r"(a)); return v; }
__device__ __forceinline__ float2 lds64f(uint32_t a) { float2 v; asm volatile("ld.shared.v2.f32 {%0,%1}, [%2];" : "=f"(v.x), "=f"(v.y) : "r"(a)); return v; }
__device__ __forceinline__ void sts64f(uint32_t a, float x, float y) { asm volatile("st.shared.v2.f32 [%0], {%1,%2};" ::"r"(a), "f"(x), "f"(y) : "memory"); }
__device__ __forceinline__ void sts32(uint32_t a, uint32_t x) { asm volatile("st.shared.b32 [%0], %1;" ::"r"(a), "r"(x) : "memory"); }
__device__ __forceinline__ void sts128(uint32_t a, uint32_t x, uint32_t y, uint32_t z, uint32_t w) { asm volatile("st.shared.v4.b32 [%0], {%1,%2,%3,%4};" ::"r"(a), "r"(x), "r"(y), "r"(z), "r"(w) : "memory"); }
__device__ __forceinline__ void stsm4(uint32_t a, uint32_t r0, uint32_t r1, uint32_t r2, uint32_t r3) {
  asm volatile("stmatrix.sync.aligned.m8n8.x4.shared.b16 [%0], {%1,%2,%3,%4};" ::"r"(a), "r"(r0), "r"(r1), "r"(r2), "r"(r3) : "memory");
}
__device__ __forceinline__ void stsm4t(uint32_t a, uint32_t r0, uint32_t r1, uint32_t r2, uint32_t r3) {
  asm volatile("stmatrix.sync.aligned.m8n8.x4.trans.shared.b16 [%0], {%1,%2,%3,%4};" ::"r"(a), "r"(r0), "r"(r1), "r"(r2), "r"(r3) : "memory");
}
__device__ __forceinline__ void stsm2(uint32_t a, uint32_t r0, uint32_t r1) {
  asm volatile("stmatrix.sync.aligned.m8n8.x2.shared.b16 [%0], {%1,%2};" ::"r"(a), "r"(r0), "r"(r1) : "memory");
}
__device__ __forceinline__ void ldsm4(uint32_t a, uint32_t& r0, uint32_t& r1, uint32_t& r2, uint32_t& r3) {
  asm volatile("ldmatrix.sync.aligned.m8n8.x4.shared.b16 {%0,%1,%2,%3}, [%4];" : "=r"(r0), "=r"(r1), "=r"(r2), "=r"(r3) : "r"(a) : "memory");
}
__device__ __forceinline__ void ldsm4t(uint32_t a, uint32_t& r0, uint32_t& r1, uint32_t& r2, uint32_t& r3) {
  asm volatile("ldmatrix.sync.aligned.m8n8.x4.trans.shared.b16 {%0,%1,%2,%3}, [%4];" : "=r"(r0), "=r"(r1), "=r"(r2), "=r"(r3) : "r"(a) : "memory");
}
__device__ __forceinline__ uint32_t mapa(uint32_t a, uint32_t rank) { uint32_t r; asm("mapa.shared::cluster.u32 %0, %1, %2;" : "=r"(r) : "r"(a), "r"(rank)); return r; }
__device__ __forceinline__ void mbar_arrive_remote(uint32_t a) { asm volatile("mbarrier.arrive.relaxed.cluster.shared::cluster.b64 _, [%0];" ::"r"(a) : "memory"); }
__device__ __forceinline__ void st_async128(uint32_t a, uint32_t x, uint32_t y, uint32_t z, uint32_t w, uint32_t bar) {
  asm volatile("st.async.weak.shared::cluster.mbarrier::complete_tx::bytes.v4.b32 [%0], {%1,%2,%3,%4}, [%5];" ::"r"(a), "r"(x), "r"(y), "r"(z), "r"(w), "r"(bar) : "memory");
}
#define TS(i)

#define TSKV
__device__ __forceinline__ void wg_ss_216(float (&d)[108], uint64_t da, uint64_t db, int sd) {
  asm volatile("{\n.reg .pred p;\nsetp.ne.b32 p, %110, 0;\n"
    "wgmma.mma_async.sync.aligned.m64n216k16.f32.bf16.bf16 {%0,%1,%2,%3,%4,%5,%6,%7,%8,%9,%10,%11,%12,%13,%14,%15,%16,%17,%18,%19,%20,%21,%22,%23,%24,%25,%26,%27,%28,%29,%30,%31,%32,%33,%34,%35,%36,%37,%38,%39,%40,%41,%42,%43,%44,%45,%46,%47,%48,%49,%50,%51,%52,%53,%54,%55,%56,%57,%58,%59,%60,%61,%62,%63,%64,%65,%66,%67,%68,%69,%70,%71,%72,%73,%74,%75,%76,%77,%78,%79,%80,%81,%82,%83,%84,%85,%86,%87,%88,%89,%90,%91,%92,%93,%94,%95,%96,%97,%98,%99,%100,%101,%102,%103,%104,%105,%106,%107}, %108, %109, p, 1, 1, 0, 1;\n}\n"
    : "+f"(d[0]),"+f"(d[1]),"+f"(d[2]),"+f"(d[3]),"+f"(d[4]),"+f"(d[5]),"+f"(d[6]),"+f"(d[7]),"+f"(d[8]),"+f"(d[9]),"+f"(d[10]),"+f"(d[11]),"+f"(d[12]),"+f"(d[13]),"+f"(d[14]),"+f"(d[15]),"+f"(d[16]),"+f"(d[17]),"+f"(d[18]),"+f"(d[19]),"+f"(d[20]),"+f"(d[21]),"+f"(d[22]),"+f"(d[23]),"+f"(d[24]),"+f"(d[25]),"+f"(d[26]),"+f"(d[27]),"+f"(d[28]),"+f"(d[29]),"+f"(d[30]),"+f"(d[31]),"+f"(d[32]),"+f"(d[33]),"+f"(d[34]),"+f"(d[35]),"+f"(d[36]),"+f"(d[37]),"+f"(d[38]),"+f"(d[39]),"+f"(d[40]),"+f"(d[41]),"+f"(d[42]),"+f"(d[43]),"+f"(d[44]),"+f"(d[45]),"+f"(d[46]),"+f"(d[47]),"+f"(d[48]),"+f"(d[49]),"+f"(d[50]),"+f"(d[51]),"+f"(d[52]),"+f"(d[53]),"+f"(d[54]),"+f"(d[55]),"+f"(d[56]),"+f"(d[57]),"+f"(d[58]),"+f"(d[59]),"+f"(d[60]),"+f"(d[61]),"+f"(d[62]),"+f"(d[63]),"+f"(d[64]),"+f"(d[65]),"+f"(d[66]),"+f"(d[67]),"+f"(d[68]),"+f"(d[69]),"+f"(d[70]),"+f"(d[71]),"+f"(d[72]),"+f"(d[73]),"+f"(d[74]),"+f"(d[75]),"+f"(d[76]),"+f"(d[77]),"+f"(d[78]),"+f"(d[79]),"+f"(d[80]),"+f"(d[81]),"+f"(d[82]),"+f"(d[83]),"+f"(d[84]),"+f"(d[85]),"+f"(d[86]),"+f"(d[87]),"+f"(d[88]),"+f"(d[89]),"+f"(d[90]),"+f"(d[91]),"+f"(d[92]),"+f"(d[93]),"+f"(d[94]),"+f"(d[95]),"+f"(d[96]),"+f"(d[97]),"+f"(d[98]),"+f"(d[99]),"+f"(d[100]),"+f"(d[101]),"+f"(d[102]),"+f"(d[103]),"+f"(d[104]),"+f"(d[105]),"+f"(d[106]),"+f"(d[107]) : "l"(da), "l"(db), "r"(sd));
}
__device__ __forceinline__ void wg_ss_160(float (&d)[80], uint64_t da, uint64_t db, int sd) {
  asm volatile("{\n.reg .pred p;\nsetp.ne.b32 p, %82, 0;\n"
    "wgmma.mma_async.sync.aligned.m64n160k16.f32.bf16.bf16 {%0,%1,%2,%3,%4,%5,%6,%7,%8,%9,%10,%11,%12,%13,%14,%15,%16,%17,%18,%19,%20,%21,%22,%23,%24,%25,%26,%27,%28,%29,%30,%31,%32,%33,%34,%35,%36,%37,%38,%39,%40,%41,%42,%43,%44,%45,%46,%47,%48,%49,%50,%51,%52,%53,%54,%55,%56,%57,%58,%59,%60,%61,%62,%63,%64,%65,%66,%67,%68,%69,%70,%71,%72,%73,%74,%75,%76,%77,%78,%79}, %80, %81, p, 1, 1, 0, 1;\n}\n"
    : "+f"(d[0]),"+f"(d[1]),"+f"(d[2]),"+f"(d[3]),"+f"(d[4]),"+f"(d[5]),"+f"(d[6]),"+f"(d[7]),"+f"(d[8]),"+f"(d[9]),"+f"(d[10]),"+f"(d[11]),"+f"(d[12]),"+f"(d[13]),"+f"(d[14]),"+f"(d[15]),"+f"(d[16]),"+f"(d[17]),"+f"(d[18]),"+f"(d[19]),"+f"(d[20]),"+f"(d[21]),"+f"(d[22]),"+f"(d[23]),"+f"(d[24]),"+f"(d[25]),"+f"(d[26]),"+f"(d[27]),"+f"(d[28]),"+f"(d[29]),"+f"(d[30]),"+f"(d[31]),"+f"(d[32]),"+f"(d[33]),"+f"(d[34]),"+f"(d[35]),"+f"(d[36]),"+f"(d[37]),"+f"(d[38]),"+f"(d[39]),"+f"(d[40]),"+f"(d[41]),"+f"(d[42]),"+f"(d[43]),"+f"(d[44]),"+f"(d[45]),"+f"(d[46]),"+f"(d[47]),"+f"(d[48]),"+f"(d[49]),"+f"(d[50]),"+f"(d[51]),"+f"(d[52]),"+f"(d[53]),"+f"(d[54]),"+f"(d[55]),"+f"(d[56]),"+f"(d[57]),"+f"(d[58]),"+f"(d[59]),"+f"(d[60]),"+f"(d[61]),"+f"(d[62]),"+f"(d[63]),"+f"(d[64]),"+f"(d[65]),"+f"(d[66]),"+f"(d[67]),"+f"(d[68]),"+f"(d[69]),"+f"(d[70]),"+f"(d[71]),"+f"(d[72]),"+f"(d[73]),"+f"(d[74]),"+f"(d[75]),"+f"(d[76]),"+f"(d[77]),"+f"(d[78]),"+f"(d[79]) : "l"(da), "l"(db), "r"(sd));
}
__device__ __forceinline__ void wg_rs_216(float (&d)[108], uint32_t a0, uint32_t a1, uint32_t a2, uint32_t a3, uint64_t db) {
  asm volatile("{\n.reg .pred p;\nsetp.ne.b32 p, 1, 0;\n"
    "wgmma.mma_async.sync.aligned.m64n216k16.f32.bf16.bf16 {%0,%1,%2,%3,%4,%5,%6,%7,%8,%9,%10,%11,%12,%13,%14,%15,%16,%17,%18,%19,%20,%21,%22,%23,%24,%25,%26,%27,%28,%29,%30,%31,%32,%33,%34,%35,%36,%37,%38,%39,%40,%41,%42,%43,%44,%45,%46,%47,%48,%49,%50,%51,%52,%53,%54,%55,%56,%57,%58,%59,%60,%61,%62,%63,%64,%65,%66,%67,%68,%69,%70,%71,%72,%73,%74,%75,%76,%77,%78,%79,%80,%81,%82,%83,%84,%85,%86,%87,%88,%89,%90,%91,%92,%93,%94,%95,%96,%97,%98,%99,%100,%101,%102,%103,%104,%105,%106,%107}, {%108,%109,%110,%111}, %112, p, 1, 1, 1;\n}\n"
    : "+f"(d[0]),"+f"(d[1]),"+f"(d[2]),"+f"(d[3]),"+f"(d[4]),"+f"(d[5]),"+f"(d[6]),"+f"(d[7]),"+f"(d[8]),"+f"(d[9]),"+f"(d[10]),"+f"(d[11]),"+f"(d[12]),"+f"(d[13]),"+f"(d[14]),"+f"(d[15]),"+f"(d[16]),"+f"(d[17]),"+f"(d[18]),"+f"(d[19]),"+f"(d[20]),"+f"(d[21]),"+f"(d[22]),"+f"(d[23]),"+f"(d[24]),"+f"(d[25]),"+f"(d[26]),"+f"(d[27]),"+f"(d[28]),"+f"(d[29]),"+f"(d[30]),"+f"(d[31]),"+f"(d[32]),"+f"(d[33]),"+f"(d[34]),"+f"(d[35]),"+f"(d[36]),"+f"(d[37]),"+f"(d[38]),"+f"(d[39]),"+f"(d[40]),"+f"(d[41]),"+f"(d[42]),"+f"(d[43]),"+f"(d[44]),"+f"(d[45]),"+f"(d[46]),"+f"(d[47]),"+f"(d[48]),"+f"(d[49]),"+f"(d[50]),"+f"(d[51]),"+f"(d[52]),"+f"(d[53]),"+f"(d[54]),"+f"(d[55]),"+f"(d[56]),"+f"(d[57]),"+f"(d[58]),"+f"(d[59]),"+f"(d[60]),"+f"(d[61]),"+f"(d[62]),"+f"(d[63]),"+f"(d[64]),"+f"(d[65]),"+f"(d[66]),"+f"(d[67]),"+f"(d[68]),"+f"(d[69]),"+f"(d[70]),"+f"(d[71]),"+f"(d[72]),"+f"(d[73]),"+f"(d[74]),"+f"(d[75]),"+f"(d[76]),"+f"(d[77]),"+f"(d[78]),"+f"(d[79]),"+f"(d[80]),"+f"(d[81]),"+f"(d[82]),"+f"(d[83]),"+f"(d[84]),"+f"(d[85]),"+f"(d[86]),"+f"(d[87]),"+f"(d[88]),"+f"(d[89]),"+f"(d[90]),"+f"(d[91]),"+f"(d[92]),"+f"(d[93]),"+f"(d[94]),"+f"(d[95]),"+f"(d[96]),"+f"(d[97]),"+f"(d[98]),"+f"(d[99]),"+f"(d[100]),"+f"(d[101]),"+f"(d[102]),"+f"(d[103]),"+f"(d[104]),"+f"(d[105]),"+f"(d[106]),"+f"(d[107]) : "r"(a0), "r"(a1), "r"(a2), "r"(a3), "l"(db));
}
__device__ __forceinline__ void wg_cv_0_0(float (&d)[128], uint32_t a0, uint32_t a1, uint32_t a2, uint32_t a3, uint64_t db) {
  asm volatile("{\n.reg .pred p;\nsetp.ne.b32 p, 0, 0;\n"
    "wgmma.mma_async.sync.aligned.m64n32k16.f32.bf16.bf16 {%0,%1,%2,%3,%4,%5,%6,%7,%8,%9,%10,%11,%12,%13,%14,%15}, {%16,%17,%18,%19}, %20, p, 1, 1, 0;\n}\n"
    : "+f"(d[0]),"+f"(d[1]),"+f"(d[2]),"+f"(d[3]),"+f"(d[4]),"+f"(d[5]),"+f"(d[6]),"+f"(d[7]),"+f"(d[8]),"+f"(d[9]),"+f"(d[10]),"+f"(d[11]),"+f"(d[12]),"+f"(d[13]),"+f"(d[14]),"+f"(d[15]) : "r"(a0), "r"(a1), "r"(a2), "r"(a3), "l"(db));
}
__device__ __forceinline__ void wg_cv_0_1(float (&d)[128], uint32_t a0, uint32_t a1, uint32_t a2, uint32_t a3, uint64_t db) {
  asm volatile("{\n.reg .pred p;\nsetp.ne.b32 p, 1, 0;\n"
    "wgmma.mma_async.sync.aligned.m64n32k16.f32.bf16.bf16 {%0,%1,%2,%3,%4,%5,%6,%7,%8,%9,%10,%11,%12,%13,%14,%15}, {%16,%17,%18,%19}, %20, p, 1, 1, 0;\n}\n"
    : "+f"(d[0]),"+f"(d[1]),"+f"(d[2]),"+f"(d[3]),"+f"(d[4]),"+f"(d[5]),"+f"(d[6]),"+f"(d[7]),"+f"(d[8]),"+f"(d[9]),"+f"(d[10]),"+f"(d[11]),"+f"(d[12]),"+f"(d[13]),"+f"(d[14]),"+f"(d[15]) : "r"(a0), "r"(a1), "r"(a2), "r"(a3), "l"(db));
}
__device__ __forceinline__ void wg_cv_1_0(float (&d)[128], uint32_t a0, uint32_t a1, uint32_t a2, uint32_t a3, uint64_t db) {
  asm volatile("{\n.reg .pred p;\nsetp.ne.b32 p, 0, 0;\n"
    "wgmma.mma_async.sync.aligned.m64n32k16.f32.bf16.bf16 {%0,%1,%2,%3,%4,%5,%6,%7,%8,%9,%10,%11,%12,%13,%14,%15}, {%16,%17,%18,%19}, %20, p, 1, 1, 0;\n}\n"
    : "+f"(d[16]),"+f"(d[17]),"+f"(d[18]),"+f"(d[19]),"+f"(d[20]),"+f"(d[21]),"+f"(d[22]),"+f"(d[23]),"+f"(d[24]),"+f"(d[25]),"+f"(d[26]),"+f"(d[27]),"+f"(d[28]),"+f"(d[29]),"+f"(d[30]),"+f"(d[31]) : "r"(a0), "r"(a1), "r"(a2), "r"(a3), "l"(db));
}
__device__ __forceinline__ void wg_cv_1_1(float (&d)[128], uint32_t a0, uint32_t a1, uint32_t a2, uint32_t a3, uint64_t db) {
  asm volatile("{\n.reg .pred p;\nsetp.ne.b32 p, 1, 0;\n"
    "wgmma.mma_async.sync.aligned.m64n32k16.f32.bf16.bf16 {%0,%1,%2,%3,%4,%5,%6,%7,%8,%9,%10,%11,%12,%13,%14,%15}, {%16,%17,%18,%19}, %20, p, 1, 1, 0;\n}\n"
    : "+f"(d[16]),"+f"(d[17]),"+f"(d[18]),"+f"(d[19]),"+f"(d[20]),"+f"(d[21]),"+f"(d[22]),"+f"(d[23]),"+f"(d[24]),"+f"(d[25]),"+f"(d[26]),"+f"(d[27]),"+f"(d[28]),"+f"(d[29]),"+f"(d[30]),"+f"(d[31]) : "r"(a0), "r"(a1), "r"(a2), "r"(a3), "l"(db));
}
__device__ __forceinline__ void wg_cv_2_0(float (&d)[128], uint32_t a0, uint32_t a1, uint32_t a2, uint32_t a3, uint64_t db) {
  asm volatile("{\n.reg .pred p;\nsetp.ne.b32 p, 0, 0;\n"
    "wgmma.mma_async.sync.aligned.m64n32k16.f32.bf16.bf16 {%0,%1,%2,%3,%4,%5,%6,%7,%8,%9,%10,%11,%12,%13,%14,%15}, {%16,%17,%18,%19}, %20, p, 1, 1, 0;\n}\n"
    : "+f"(d[32]),"+f"(d[33]),"+f"(d[34]),"+f"(d[35]),"+f"(d[36]),"+f"(d[37]),"+f"(d[38]),"+f"(d[39]),"+f"(d[40]),"+f"(d[41]),"+f"(d[42]),"+f"(d[43]),"+f"(d[44]),"+f"(d[45]),"+f"(d[46]),"+f"(d[47]) : "r"(a0), "r"(a1), "r"(a2), "r"(a3), "l"(db));
}
__device__ __forceinline__ void wg_cv_2_1(float (&d)[128], uint32_t a0, uint32_t a1, uint32_t a2, uint32_t a3, uint64_t db) {
  asm volatile("{\n.reg .pred p;\nsetp.ne.b32 p, 1, 0;\n"
    "wgmma.mma_async.sync.aligned.m64n32k16.f32.bf16.bf16 {%0,%1,%2,%3,%4,%5,%6,%7,%8,%9,%10,%11,%12,%13,%14,%15}, {%16,%17,%18,%19}, %20, p, 1, 1, 0;\n}\n"
    : "+f"(d[32]),"+f"(d[33]),"+f"(d[34]),"+f"(d[35]),"+f"(d[36]),"+f"(d[37]),"+f"(d[38]),"+f"(d[39]),"+f"(d[40]),"+f"(d[41]),"+f"(d[42]),"+f"(d[43]),"+f"(d[44]),"+f"(d[45]),"+f"(d[46]),"+f"(d[47]) : "r"(a0), "r"(a1), "r"(a2), "r"(a3), "l"(db));
}
__device__ __forceinline__ void wg_cv_3_0(float (&d)[128], uint32_t a0, uint32_t a1, uint32_t a2, uint32_t a3, uint64_t db) {
  asm volatile("{\n.reg .pred p;\nsetp.ne.b32 p, 0, 0;\n"
    "wgmma.mma_async.sync.aligned.m64n32k16.f32.bf16.bf16 {%0,%1,%2,%3,%4,%5,%6,%7,%8,%9,%10,%11,%12,%13,%14,%15}, {%16,%17,%18,%19}, %20, p, 1, 1, 0;\n}\n"
    : "+f"(d[48]),"+f"(d[49]),"+f"(d[50]),"+f"(d[51]),"+f"(d[52]),"+f"(d[53]),"+f"(d[54]),"+f"(d[55]),"+f"(d[56]),"+f"(d[57]),"+f"(d[58]),"+f"(d[59]),"+f"(d[60]),"+f"(d[61]),"+f"(d[62]),"+f"(d[63]) : "r"(a0), "r"(a1), "r"(a2), "r"(a3), "l"(db));
}
__device__ __forceinline__ void wg_cv_3_1(float (&d)[128], uint32_t a0, uint32_t a1, uint32_t a2, uint32_t a3, uint64_t db) {
  asm volatile("{\n.reg .pred p;\nsetp.ne.b32 p, 1, 0;\n"
    "wgmma.mma_async.sync.aligned.m64n32k16.f32.bf16.bf16 {%0,%1,%2,%3,%4,%5,%6,%7,%8,%9,%10,%11,%12,%13,%14,%15}, {%16,%17,%18,%19}, %20, p, 1, 1, 0;\n}\n"
    : "+f"(d[48]),"+f"(d[49]),"+f"(d[50]),"+f"(d[51]),"+f"(d[52]),"+f"(d[53]),"+f"(d[54]),"+f"(d[55]),"+f"(d[56]),"+f"(d[57]),"+f"(d[58]),"+f"(d[59]),"+f"(d[60]),"+f"(d[61]),"+f"(d[62]),"+f"(d[63]) : "r"(a0), "r"(a1), "r"(a2), "r"(a3), "l"(db));
}
__device__ __forceinline__ void wg_cv_4_0(float (&d)[128], uint32_t a0, uint32_t a1, uint32_t a2, uint32_t a3, uint64_t db) {
  asm volatile("{\n.reg .pred p;\nsetp.ne.b32 p, 0, 0;\n"
    "wgmma.mma_async.sync.aligned.m64n32k16.f32.bf16.bf16 {%0,%1,%2,%3,%4,%5,%6,%7,%8,%9,%10,%11,%12,%13,%14,%15}, {%16,%17,%18,%19}, %20, p, 1, 1, 0;\n}\n"
    : "+f"(d[64]),"+f"(d[65]),"+f"(d[66]),"+f"(d[67]),"+f"(d[68]),"+f"(d[69]),"+f"(d[70]),"+f"(d[71]),"+f"(d[72]),"+f"(d[73]),"+f"(d[74]),"+f"(d[75]),"+f"(d[76]),"+f"(d[77]),"+f"(d[78]),"+f"(d[79]) : "r"(a0), "r"(a1), "r"(a2), "r"(a3), "l"(db));
}
__device__ __forceinline__ void wg_cv_4_1(float (&d)[128], uint32_t a0, uint32_t a1, uint32_t a2, uint32_t a3, uint64_t db) {
  asm volatile("{\n.reg .pred p;\nsetp.ne.b32 p, 1, 0;\n"
    "wgmma.mma_async.sync.aligned.m64n32k16.f32.bf16.bf16 {%0,%1,%2,%3,%4,%5,%6,%7,%8,%9,%10,%11,%12,%13,%14,%15}, {%16,%17,%18,%19}, %20, p, 1, 1, 0;\n}\n"
    : "+f"(d[64]),"+f"(d[65]),"+f"(d[66]),"+f"(d[67]),"+f"(d[68]),"+f"(d[69]),"+f"(d[70]),"+f"(d[71]),"+f"(d[72]),"+f"(d[73]),"+f"(d[74]),"+f"(d[75]),"+f"(d[76]),"+f"(d[77]),"+f"(d[78]),"+f"(d[79]) : "r"(a0), "r"(a1), "r"(a2), "r"(a3), "l"(db));
}
__device__ __forceinline__ void wg_cv_5_0(float (&d)[128], uint32_t a0, uint32_t a1, uint32_t a2, uint32_t a3, uint64_t db) {
  asm volatile("{\n.reg .pred p;\nsetp.ne.b32 p, 0, 0;\n"
    "wgmma.mma_async.sync.aligned.m64n32k16.f32.bf16.bf16 {%0,%1,%2,%3,%4,%5,%6,%7,%8,%9,%10,%11,%12,%13,%14,%15}, {%16,%17,%18,%19}, %20, p, 1, 1, 0;\n}\n"
    : "+f"(d[80]),"+f"(d[81]),"+f"(d[82]),"+f"(d[83]),"+f"(d[84]),"+f"(d[85]),"+f"(d[86]),"+f"(d[87]),"+f"(d[88]),"+f"(d[89]),"+f"(d[90]),"+f"(d[91]),"+f"(d[92]),"+f"(d[93]),"+f"(d[94]),"+f"(d[95]) : "r"(a0), "r"(a1), "r"(a2), "r"(a3), "l"(db));
}
__device__ __forceinline__ void wg_cv_5_1(float (&d)[128], uint32_t a0, uint32_t a1, uint32_t a2, uint32_t a3, uint64_t db) {
  asm volatile("{\n.reg .pred p;\nsetp.ne.b32 p, 1, 0;\n"
    "wgmma.mma_async.sync.aligned.m64n32k16.f32.bf16.bf16 {%0,%1,%2,%3,%4,%5,%6,%7,%8,%9,%10,%11,%12,%13,%14,%15}, {%16,%17,%18,%19}, %20, p, 1, 1, 0;\n}\n"
    : "+f"(d[80]),"+f"(d[81]),"+f"(d[82]),"+f"(d[83]),"+f"(d[84]),"+f"(d[85]),"+f"(d[86]),"+f"(d[87]),"+f"(d[88]),"+f"(d[89]),"+f"(d[90]),"+f"(d[91]),"+f"(d[92]),"+f"(d[93]),"+f"(d[94]),"+f"(d[95]) : "r"(a0), "r"(a1), "r"(a2), "r"(a3), "l"(db));
}
__device__ __forceinline__ void wg_cv_6_0(float (&d)[128], uint32_t a0, uint32_t a1, uint32_t a2, uint32_t a3, uint64_t db) {
  asm volatile("{\n.reg .pred p;\nsetp.ne.b32 p, 0, 0;\n"
    "wgmma.mma_async.sync.aligned.m64n32k16.f32.bf16.bf16 {%0,%1,%2,%3,%4,%5,%6,%7,%8,%9,%10,%11,%12,%13,%14,%15}, {%16,%17,%18,%19}, %20, p, 1, 1, 0;\n}\n"
    : "+f"(d[96]),"+f"(d[97]),"+f"(d[98]),"+f"(d[99]),"+f"(d[100]),"+f"(d[101]),"+f"(d[102]),"+f"(d[103]),"+f"(d[104]),"+f"(d[105]),"+f"(d[106]),"+f"(d[107]),"+f"(d[108]),"+f"(d[109]),"+f"(d[110]),"+f"(d[111]) : "r"(a0), "r"(a1), "r"(a2), "r"(a3), "l"(db));
}
__device__ __forceinline__ void wg_cv_6_1(float (&d)[128], uint32_t a0, uint32_t a1, uint32_t a2, uint32_t a3, uint64_t db) {
  asm volatile("{\n.reg .pred p;\nsetp.ne.b32 p, 1, 0;\n"
    "wgmma.mma_async.sync.aligned.m64n32k16.f32.bf16.bf16 {%0,%1,%2,%3,%4,%5,%6,%7,%8,%9,%10,%11,%12,%13,%14,%15}, {%16,%17,%18,%19}, %20, p, 1, 1, 0;\n}\n"
    : "+f"(d[96]),"+f"(d[97]),"+f"(d[98]),"+f"(d[99]),"+f"(d[100]),"+f"(d[101]),"+f"(d[102]),"+f"(d[103]),"+f"(d[104]),"+f"(d[105]),"+f"(d[106]),"+f"(d[107]),"+f"(d[108]),"+f"(d[109]),"+f"(d[110]),"+f"(d[111]) : "r"(a0), "r"(a1), "r"(a2), "r"(a3), "l"(db));
}
__device__ __forceinline__ void wg_cv_7_0(float (&d)[128], uint32_t a0, uint32_t a1, uint32_t a2, uint32_t a3, uint64_t db) {
  asm volatile("{\n.reg .pred p;\nsetp.ne.b32 p, 0, 0;\n"
    "wgmma.mma_async.sync.aligned.m64n32k16.f32.bf16.bf16 {%0,%1,%2,%3,%4,%5,%6,%7,%8,%9,%10,%11,%12,%13,%14,%15}, {%16,%17,%18,%19}, %20, p, 1, 1, 0;\n}\n"
    : "+f"(d[112]),"+f"(d[113]),"+f"(d[114]),"+f"(d[115]),"+f"(d[116]),"+f"(d[117]),"+f"(d[118]),"+f"(d[119]),"+f"(d[120]),"+f"(d[121]),"+f"(d[122]),"+f"(d[123]),"+f"(d[124]),"+f"(d[125]),"+f"(d[126]),"+f"(d[127]) : "r"(a0), "r"(a1), "r"(a2), "r"(a3), "l"(db));
}
__device__ __forceinline__ void wg_cv_7_1(float (&d)[128], uint32_t a0, uint32_t a1, uint32_t a2, uint32_t a3, uint64_t db) {
  asm volatile("{\n.reg .pred p;\nsetp.ne.b32 p, 1, 0;\n"
    "wgmma.mma_async.sync.aligned.m64n32k16.f32.bf16.bf16 {%0,%1,%2,%3,%4,%5,%6,%7,%8,%9,%10,%11,%12,%13,%14,%15}, {%16,%17,%18,%19}, %20, p, 1, 1, 0;\n}\n"
    : "+f"(d[112]),"+f"(d[113]),"+f"(d[114]),"+f"(d[115]),"+f"(d[116]),"+f"(d[117]),"+f"(d[118]),"+f"(d[119]),"+f"(d[120]),"+f"(d[121]),"+f"(d[122]),"+f"(d[123]),"+f"(d[124]),"+f"(d[125]),"+f"(d[126]),"+f"(d[127]) : "r"(a0), "r"(a1), "r"(a2), "r"(a3), "l"(db));
}
template <class F> __device__ __forceinline__ void conv_chain_1(float (&d)[128], uint32_t (&a)[64], uint64_t db, uint32_t ab, F hand) {
  wg_cv_7_0(d, a[60], a[61], a[62], a[63], db + (uint64_t)(0));
  wg_cv_6_0(d, a[52], a[53], a[54], a[55], db + (uint64_t)(0));
  wg_cv_7_1(d, a[56], a[57], a[58], a[59], db + (uint64_t)(16));
  wg_cv_5_0(d, a[44], a[45], a[46], a[47], db + (uint64_t)(0));
  wg_cv_6_1(d, a[48], a[49], a[50], a[51], db + (uint64_t)(16));
  wg_cv_7_1(d, a[52], a[53], a[54], a[55], db + (uint64_t)(32));
  wg_cv_5_1(d, a[40], a[41], a[42], a[43], db + (uint64_t)(16));
  wg_cv_6_1(d, a[44], a[45], a[46], a[47], db + (uint64_t)(32));
  wg_cv_7_1(d, a[48], a[49], a[50], a[51], db + (uint64_t)(48));
  wg_cv_6_1(d, a[40], a[41], a[42], a[43], db + (uint64_t)(48));
  wg_cv_7_1(d, a[44], a[45], a[46], a[47], db + (uint64_t)(64));
  wg_cv_7_1(d, a[40], a[41], a[42], a[43], db + (uint64_t)(80));
  wg_commit();
  wg_cv_7_1(d, a[36], a[37], a[38], a[39], db + (uint64_t)(96));
  wg_cv_6_1(d, a[36], a[37], a[38], a[39], db + (uint64_t)(64));
  wg_cv_5_1(d, a[36], a[37], a[38], a[39], db + (uint64_t)(32));
  wg_cv_4_0(d, a[36], a[37], a[38], a[39], db + (uint64_t)(0));
  wg_commit(); wg_wait<1>();
  wg_cv_7_1(d, a[32], a[33], a[34], a[35], db + (uint64_t)(112));
  wg_cv_6_1(d, a[32], a[33], a[34], a[35], db + (uint64_t)(80));
  wg_cv_5_1(d, a[32], a[33], a[34], a[35], db + (uint64_t)(48));
  a[60] = lds32(ab + (3840));
  a[61] = lds32(ab + (3968));
  a[62] = lds32(ab + (3824));
  a[63] = lds32(ab + (3952));
  wg_cv_4_1(d, a[32], a[33], a[34], a[35], db + (uint64_t)(16));
  wg_cv_7_1(d, a[28], a[29], a[30], a[31], db + (uint64_t)(128));
  wg_cv_6_1(d, a[28], a[29], a[30], a[31], db + (uint64_t)(96));
  wg_cv_5_1(d, a[28], a[29], a[30], a[31], db + (uint64_t)(64));
  a[56] = lds32(ab + (3584));
  a[57] = lds32(ab + (3712));
  a[58] = lds32(ab + (3568));
  a[59] = lds32(ab + (3696));
  wg_cv_4_1(d, a[28], a[29], a[30], a[31], db + (uint64_t)(32));
  wg_cv_3_0(d, a[28], a[29], a[30], a[31], db + (uint64_t)(0));
  wg_cv_7_1(d, a[24], a[25], a[26], a[27], db + (uint64_t)(144));
  wg_cv_6_1(d, a[24], a[25], a[26], a[27], db + (uint64_t)(112));
  a[52] = lds32(ab + (3328));
  a[53] = lds32(ab + (3456));
  a[54] = lds32(ab + (3312));
  a[55] = lds32(ab + (3440));
  wg_cv_5_1(d, a[24], a[25], a[26], a[27], db + (uint64_t)(80));
  wg_cv_4_1(d, a[24], a[25], a[26], a[27], db + (uint64_t)(48));
  wg_cv_3_1(d, a[24], a[25], a[26], a[27], db + (uint64_t)(16));
  wg_commit();
  wg_cv_7_1(d, a[20], a[21], a[22], a[23], db + (uint64_t)(160));
  wg_cv_6_1(d, a[20], a[21], a[22], a[23], db + (uint64_t)(128));
  wg_cv_5_1(d, a[20], a[21], a[22], a[23], db + (uint64_t)(96));
  wg_cv_4_1(d, a[20], a[21], a[22], a[23], db + (uint64_t)(64));
  wg_commit(); wg_wait<1>();
  a[48] = lds32(ab + (3072));
  a[49] = lds32(ab + (3200));
  a[50] = lds32(ab + (3056));
  a[51] = lds32(ab + (3184));
  wg_cv_3_1(d, a[20], a[21], a[22], a[23], db + (uint64_t)(32));
  wg_cv_2_0(d, a[20], a[21], a[22], a[23], db + (uint64_t)(0));
  wg_cv_7_1(d, a[16], a[17], a[18], a[19], db + (uint64_t)(176));
  wg_cv_6_1(d, a[16], a[17], a[18], a[19], db + (uint64_t)(144));
  a[44] = lds32(ab + (2816));
  a[45] = lds32(ab + (2944));
  a[46] = lds32(ab + (2800));
  a[47] = lds32(ab + (2928));
  wg_cv_5_1(d, a[16], a[17], a[18], a[19], db + (uint64_t)(112));
  wg_cv_4_1(d, a[16], a[17], a[18], a[19], db + (uint64_t)(80));
  wg_cv_3_1(d, a[16], a[17], a[18], a[19], db + (uint64_t)(48));
  wg_cv_2_1(d, a[16], a[17], a[18], a[19], db + (uint64_t)(16));
  a[40] = lds32(ab + (2560));
  a[41] = lds32(ab + (2688));
  a[42] = lds32(ab + (2544));
  a[43] = lds32(ab + (2672));
  wg_cv_7_1(d, a[12], a[13], a[14], a[15], db + (uint64_t)(192));
  wg_cv_6_1(d, a[12], a[13], a[14], a[15], db + (uint64_t)(160));
  wg_cv_5_1(d, a[12], a[13], a[14], a[15], db + (uint64_t)(128));
  wg_cv_4_1(d, a[12], a[13], a[14], a[15], db + (uint64_t)(96));
  a[36] = lds32(ab + (2304));
  a[37] = lds32(ab + (2432));
  a[38] = lds32(ab + (2288));
  a[39] = lds32(ab + (2416));
  wg_cv_3_1(d, a[12], a[13], a[14], a[15], db + (uint64_t)(64));
  wg_cv_2_1(d, a[12], a[13], a[14], a[15], db + (uint64_t)(32));
  wg_cv_1_0(d, a[12], a[13], a[14], a[15], db + (uint64_t)(0));
  wg_cv_7_1(d, a[8], a[9], a[10], a[11], db + (uint64_t)(208));
  a[32] = lds32(ab + (2048));
  a[33] = lds32(ab + (2176));
  a[34] = lds32(ab + (2032));
  a[35] = lds32(ab + (2160));
  wg_cv_6_1(d, a[8], a[9], a[10], a[11], db + (uint64_t)(176));
  wg_cv_5_1(d, a[8], a[9], a[10], a[11], db + (uint64_t)(144));
  wg_cv_4_1(d, a[8], a[9], a[10], a[11], db + (uint64_t)(112));
  wg_cv_3_1(d, a[8], a[9], a[10], a[11], db + (uint64_t)(80));
  a[28] = lds32(ab + (1792));
  a[29] = lds32(ab + (1920));
  a[30] = lds32(ab + (1776));
  a[31] = lds32(ab + (1904));
  wg_cv_2_1(d, a[8], a[9], a[10], a[11], db + (uint64_t)(48));
  wg_cv_1_1(d, a[8], a[9], a[10], a[11], db + (uint64_t)(16));
  wg_commit();
  wg_cv_7_1(d, a[4], a[5], a[6], a[7], db + (uint64_t)(224));
  wg_cv_6_1(d, a[4], a[5], a[6], a[7], db + (uint64_t)(192));
  wg_cv_5_1(d, a[4], a[5], a[6], a[7], db + (uint64_t)(160));
  wg_cv_4_1(d, a[4], a[5], a[6], a[7], db + (uint64_t)(128));
  wg_commit(); wg_wait<1>();
  a[24] = lds32(ab + (1536));
  a[25] = lds32(ab + (1664));
  a[26] = lds32(ab + (1520));
  a[27] = lds32(ab + (1648));
  hand();
  wg_cv_3_1(d, a[4], a[5], a[6], a[7], db + (uint64_t)(96));
  wg_cv_2_1(d, a[4], a[5], a[6], a[7], db + (uint64_t)(64));
  wg_cv_1_1(d, a[4], a[5], a[6], a[7], db + (uint64_t)(32));
  wg_cv_0_0(d, a[4], a[5], a[6], a[7], db + (uint64_t)(0));
  a[20] = lds32(ab + (1280));
  a[21] = lds32(ab + (1408));
  a[22] = lds32(ab + (1264));
  a[23] = lds32(ab + (1392));
  wg_cv_7_1(d, a[0], a[1], a[2], a[3], db + (uint64_t)(240));
  wg_cv_6_1(d, a[0], a[1], a[2], a[3], db + (uint64_t)(208));
  wg_cv_5_1(d, a[0], a[1], a[2], a[3], db + (uint64_t)(176));
  wg_cv_4_1(d, a[0], a[1], a[2], a[3], db + (uint64_t)(144));
  a[16] = lds32(ab + (1024));
  a[17] = lds32(ab + (1152));
  a[18] = lds32(ab + (1008));
  a[19] = lds32(ab + (1136));
  wg_cv_3_1(d, a[0], a[1], a[2], a[3], db + (uint64_t)(112));
  wg_cv_2_1(d, a[0], a[1], a[2], a[3], db + (uint64_t)(80));
  wg_cv_1_1(d, a[0], a[1], a[2], a[3], db + (uint64_t)(48));
  wg_cv_0_1(d, a[0], a[1], a[2], a[3], db + (uint64_t)(16));
  wg_commit();
  a[12] = lds32(ab + (768));
  a[13] = lds32(ab + (896));
  a[14] = lds32(ab + (752));
  a[15] = lds32(ab + (880));
  a[8] = lds32(ab + (512));
  a[9] = lds32(ab + (640));
  a[10] = lds32(ab + (496));
  a[11] = lds32(ab + (624));
}
template <class F> __device__ __forceinline__ void conv_chain_0(float (&d)[128], uint32_t (&a)[64], uint64_t db, uint32_t ab, F hand) {
  wg_cv_7_0(d, a[60], a[61], a[62], a[63], db + (uint64_t)(0));
  wg_cv_6_0(d, a[52], a[53], a[54], a[55], db + (uint64_t)(0));
  wg_cv_7_1(d, a[56], a[57], a[58], a[59], db + (uint64_t)(16));
  wg_cv_5_0(d, a[44], a[45], a[46], a[47], db + (uint64_t)(0));
  wg_cv_6_1(d, a[48], a[49], a[50], a[51], db + (uint64_t)(16));
  wg_cv_7_1(d, a[52], a[53], a[54], a[55], db + (uint64_t)(32));
  wg_cv_5_1(d, a[40], a[41], a[42], a[43], db + (uint64_t)(16));
  wg_cv_6_1(d, a[44], a[45], a[46], a[47], db + (uint64_t)(32));
  wg_cv_7_1(d, a[48], a[49], a[50], a[51], db + (uint64_t)(48));
  wg_cv_6_1(d, a[40], a[41], a[42], a[43], db + (uint64_t)(48));
  wg_cv_7_1(d, a[44], a[45], a[46], a[47], db + (uint64_t)(64));
  wg_cv_7_1(d, a[40], a[41], a[42], a[43], db + (uint64_t)(80));
  wg_commit();
  wg_cv_7_1(d, a[36], a[37], a[38], a[39], db + (uint64_t)(96));
  wg_cv_6_1(d, a[36], a[37], a[38], a[39], db + (uint64_t)(64));
  wg_cv_5_1(d, a[36], a[37], a[38], a[39], db + (uint64_t)(32));
  wg_cv_4_0(d, a[36], a[37], a[38], a[39], db + (uint64_t)(0));
  wg_cv_7_1(d, a[32], a[33], a[34], a[35], db + (uint64_t)(112));
  wg_cv_6_1(d, a[32], a[33], a[34], a[35], db + (uint64_t)(80));
  wg_cv_5_1(d, a[32], a[33], a[34], a[35], db + (uint64_t)(48));
  wg_cv_4_1(d, a[32], a[33], a[34], a[35], db + (uint64_t)(16));
  wg_cv_7_1(d, a[28], a[29], a[30], a[31], db + (uint64_t)(128));
  wg_cv_6_1(d, a[28], a[29], a[30], a[31], db + (uint64_t)(96));
  wg_cv_5_1(d, a[28], a[29], a[30], a[31], db + (uint64_t)(64));
  wg_cv_4_1(d, a[28], a[29], a[30], a[31], db + (uint64_t)(32));
  wg_cv_3_0(d, a[28], a[29], a[30], a[31], db + (uint64_t)(0));
  wg_cv_7_1(d, a[24], a[25], a[26], a[27], db + (uint64_t)(144));
  wg_cv_6_1(d, a[24], a[25], a[26], a[27], db + (uint64_t)(112));
  wg_cv_5_1(d, a[24], a[25], a[26], a[27], db + (uint64_t)(80));
  wg_cv_4_1(d, a[24], a[25], a[26], a[27], db + (uint64_t)(48));
  wg_cv_3_1(d, a[24], a[25], a[26], a[27], db + (uint64_t)(16));
  wg_commit();
  wg_cv_7_1(d, a[20], a[21], a[22], a[23], db + (uint64_t)(160));
  wg_cv_6_1(d, a[20], a[21], a[22], a[23], db + (uint64_t)(128));
  wg_cv_5_1(d, a[20], a[21], a[22], a[23], db + (uint64_t)(96));
  wg_cv_4_1(d, a[20], a[21], a[22], a[23], db + (uint64_t)(64));
  wg_cv_3_1(d, a[20], a[21], a[22], a[23], db + (uint64_t)(32));
  wg_cv_2_0(d, a[20], a[21], a[22], a[23], db + (uint64_t)(0));
  wg_cv_7_1(d, a[16], a[17], a[18], a[19], db + (uint64_t)(176));
  wg_cv_6_1(d, a[16], a[17], a[18], a[19], db + (uint64_t)(144));
  wg_cv_5_1(d, a[16], a[17], a[18], a[19], db + (uint64_t)(112));
  wg_cv_4_1(d, a[16], a[17], a[18], a[19], db + (uint64_t)(80));
  wg_cv_3_1(d, a[16], a[17], a[18], a[19], db + (uint64_t)(48));
  wg_cv_2_1(d, a[16], a[17], a[18], a[19], db + (uint64_t)(16));
  wg_cv_7_1(d, a[12], a[13], a[14], a[15], db + (uint64_t)(192));
  wg_cv_6_1(d, a[12], a[13], a[14], a[15], db + (uint64_t)(160));
  wg_cv_5_1(d, a[12], a[13], a[14], a[15], db + (uint64_t)(128));
  wg_cv_4_1(d, a[12], a[13], a[14], a[15], db + (uint64_t)(96));
  wg_cv_3_1(d, a[12], a[13], a[14], a[15], db + (uint64_t)(64));
  wg_cv_2_1(d, a[12], a[13], a[14], a[15], db + (uint64_t)(32));
  wg_cv_1_0(d, a[12], a[13], a[14], a[15], db + (uint64_t)(0));
  wg_cv_7_1(d, a[8], a[9], a[10], a[11], db + (uint64_t)(208));
  wg_cv_6_1(d, a[8], a[9], a[10], a[11], db + (uint64_t)(176));
  wg_cv_5_1(d, a[8], a[9], a[10], a[11], db + (uint64_t)(144));
  wg_cv_4_1(d, a[8], a[9], a[10], a[11], db + (uint64_t)(112));
  wg_cv_3_1(d, a[8], a[9], a[10], a[11], db + (uint64_t)(80));
  wg_cv_2_1(d, a[8], a[9], a[10], a[11], db + (uint64_t)(48));
  wg_cv_1_1(d, a[8], a[9], a[10], a[11], db + (uint64_t)(16));
  wg_commit();
  wg_cv_7_1(d, a[4], a[5], a[6], a[7], db + (uint64_t)(224));
  wg_cv_6_1(d, a[4], a[5], a[6], a[7], db + (uint64_t)(192));
  wg_cv_5_1(d, a[4], a[5], a[6], a[7], db + (uint64_t)(160));
  wg_cv_4_1(d, a[4], a[5], a[6], a[7], db + (uint64_t)(128));
  hand();
  wg_cv_3_1(d, a[4], a[5], a[6], a[7], db + (uint64_t)(96));
  wg_cv_2_1(d, a[4], a[5], a[6], a[7], db + (uint64_t)(64));
  wg_cv_1_1(d, a[4], a[5], a[6], a[7], db + (uint64_t)(32));
  wg_cv_0_0(d, a[4], a[5], a[6], a[7], db + (uint64_t)(0));
  wg_cv_7_1(d, a[0], a[1], a[2], a[3], db + (uint64_t)(240));
  wg_cv_6_1(d, a[0], a[1], a[2], a[3], db + (uint64_t)(208));
  wg_cv_5_1(d, a[0], a[1], a[2], a[3], db + (uint64_t)(176));
  wg_cv_4_1(d, a[0], a[1], a[2], a[3], db + (uint64_t)(144));
  wg_cv_3_1(d, a[0], a[1], a[2], a[3], db + (uint64_t)(112));
  wg_cv_2_1(d, a[0], a[1], a[2], a[3], db + (uint64_t)(80));
  wg_cv_1_1(d, a[0], a[1], a[2], a[3], db + (uint64_t)(48));
  wg_cv_0_1(d, a[0], a[1], a[2], a[3], db + (uint64_t)(16));
  wg_commit();
}
constexpr int CV_RELOADED = 2;

struct Params {
  const __nv_bfloat16 *q, *k, *v, *shift_k, *ssm_k, *ssm_D, *w1, *b1, *w2, *b2;
  __nv_bfloat16* out;
};
struct Maps { CUtensorMap qa, w1, w1x, k, v, hs, hx, ha, hn, w2, w2x, kvs, qf, y, out; };

__global__ void __cluster_dims__(2, 1, 1) __launch_bounds__(384, 1) h3_kernel(const __grid_constant__ Maps M, const Params P) {
  extern __shared__ __align__(1024) uint8_t smem_raw[];
  constexpr uint32_t sc = 1024;
  const int tid = threadIdx.x, lane = tid & 31;
  const int warp = __shfl_sync(0xffffffffu, tid >> 5, 0);
  const uint32_t sb = __shfl_sync(0xffffffffu, s32(smem_raw), 0);
  const int b = blockIdx.x, pr = b >> 1;
  const int G = pr < 4 ? 0 : (pr < 36 ? (pr - 4) & 7 : 1 + (pr - 36) % 7), gi = pr < 4 ? 4 + pr : (pr < 36 ? (pr - 4) >> 3 : 4 + (pr - 36) / 7);
  const int kh = b & 1, nt = (G & 1) * 2 + (gi & 1), rb = (G >> 1) * 4 + (gi >> 1);
  const int dir = (G ^ (G >> 1)) & 1, ri = (gi & 1) * 2 + kh, ci = (G >> 2) * 4 + (gi >> 1);
  const int j = kh * 4 + nt;
  const uint32_t bar = sb + M_BAR;
  auto BAR = [&](int i) { return bar + 8 * i; };
  auto g1_load = [&](int kc) {
    const uint32_t st = sb + (kc & 3) * G1_STAGE, fb = BAR(B_F1 + (kc & 3));
    const int k0 = dir ? 576 - kc * 64 : kc * 64;
    mbar_expect(fb, G1_TX);
    tma2d(st, &M.qa, k0, rb * 128, fb);
    tma3d(st + 16384, &M.w1, 0, k0, 3 * j, fb);
    tma2d(st + 40960, &M.w1x, 1536 + 24 * j, k0, fb);
  };
  auto kv_load = [&](int r, int hf) {
    const uint32_t st = sb + KVS + (r < 3 ? r : r - 3) * KV_BUF, fb = BAR((hf ? B_KIN1 : B_KIN) + r);
    mbar_expect(fb, KV_BUF / 2);
    tma2d(st + 4096 + hf * 2432, &M.k, 128 * r + 64 * (b & 1), 32 * (b >> 1) + 16 * hf - 3, fb);
    tma2d(st + hf * 2048, &M.v, 128 * r + 64 * (b & 1), 32 * (b >> 1) + 16 * hf, fb);
  };
  auto x_load = [&](int c) {
    mbar_expect(BAR(B_XF + c), 4096);
    bulk_g2s(sb + cv_x(c) + XD, g_kvT + (size_t)(128 * c + b) * SL, 4096, BAR(B_XF + c));
  };
  auto conv_sum = [&](int c, int ck, bool third) {
    const uint32_t ra = sb + cv_p(c) + ck * 16;
    __nv_bfloat16* yp = g_yT + (size_t)(128 * c + b) * SL + ck * 8;
    uint4 p[2][4];
    auto ld = [&](int u) {
#pragma unroll
      for (int w = 0; w < 4; w++) p[u & 1][w] = lds128((u == 0 && ck < 2 * w) ? sb + M_ZERO : ra + u * 512 + w * (4096 - 32));
    };
    auto st = [&](int u) {
      auto sum = [&](uint32_t a0, uint32_t a1, uint32_t a2, uint32_t a3) { return badd2(badd2(badd2(a3, a2), a1), a0); };
      const uint4* r = p[u & 1];
      stg128(yp + u * 256, sum(r[0].x, r[1].x, r[2].x, r[3].x), sum(r[0].y, r[1].y, r[2].y, r[3].y), sum(r[0].z, r[1].z, r[2].z, r[3].z), sum(r[0].w, r[1].w, r[2].w, r[3].w));
    };
    ld(0); ld(1); st(0);
    if (third) ld(2);
    st(1);
    if (third) st(2);
  };
  if (warp == 8) {
    if (lane == 0) {
      TS(0);
#pragma unroll
      for (int s = 0; s < 4; s++) mbar_init(BAR(B_F1 + s), 1);
    }
    __syncwarp();
    bar_arrive(NB_INIT, 384);
    ONE(g1_load(0));
  }
  if ((sb & 0xFFFFFFu) != sc) { if (warp == 8) mbar_wait(BAR(B_F1), 0); return; }

  if (warp >= 8) {
    asm volatile("setmaxnreg.dec.sync.aligned.u32 " REG_AUX ";");
    auto table = [&](int c, int aw) {
      const uint32_t kb = sb + cv_t(c);
      const uint32_t dd = lds32(sb + M_AUX + aw * 32 + c * 4);
      if (lane < 2) sts128(kb + lane * (KT_E - 16), 0u, 0u, 0u, 0u);
      uint4 r[8];
#pragma unroll
      for (int it = 0; it < 8; it++) r[it] = lds128(kb + KT_E + (it * 32 + lane) * 16);
      if (lane == 0) { r[0].x = __byte_perm(badd2(r[0].x, dd), r[0].x, 0x7610); sts32(kb + KT_E, r[0].x); }
#pragma unroll
      for (int it = 0; it < 8; it++) {
        const uint32_t pv = __shfl_sync(0xffffffffu, lane == 31 ? (it ? r[it ? it - 1 : 0].w : 0u) : r[it].w, lane - 1);
        sts128(kb + KT_O + (it * 32 + lane) * 16, __byte_perm(pv, r[it].x, 0x5432), __byte_perm(r[it].x, r[it].y, 0x5432),
               __byte_perm(r[it].y, r[it].z, 0x5432), __byte_perm(r[it].z, r[it].w, 0x5432));
      }
      __syncwarp();
      if (lane == 0) mbar_arrive(BAR(B_KT + c));
    };
    if (warp == 8) {
      ONE(g1_load(1); g1_load(2); g1_load(3));
      bar_sync(NB_INIT2, 128);
#pragma unroll
      for (int kc = 3; kc < 10; kc++) {
        if (kc > 3) mbar_wait(BAR(B_E1 + (kc & 3)), (kc >> 3) & 1);
        ONE(if (kc > 3) g1_load(kc);
            for (int r = 0; r < 3; r++) if (kc == ((KV_MAP >> (4 * r)) & 15)) { kv_load(r, 0); kv_load(r, 1); }
            for (int c = 0; c < 5; c++) if (kc == ((PF_RAW >> (4 * c)) & 15)) prefetch_l2(P.ssm_k + (size_t)(128 * c + b) * SL, 4096));
      }
      ONE(prefetch_map(&M.hs); prefetch_map(&M.hx); prefetch_map(&M.ha); prefetch_map(&M.hn); prefetch_map(&M.w2); prefetch_map(&M.w2x));
      bar_sync(NB_INIT3, 64);
      const unsigned ep = lds32(sb + M_AUX + 20);
#pragma unroll 1
      for (int r = SIG_W; r < SIG_P;) {
        int e = r == 0 ? SIG_A : r + 1;
        mbar_wait(BAR(B_KD + e - 1), 0);
#pragma unroll 1
        while (e < SIG_P && mbar_test(BAR(B_KD + e), 0)) e++;
        if (lane == 0 && r == SIG_W) TS(35);
        fence_release();
        if (lane >= r && lane < e) signal_cnt(CNT_KV + lane * 2 + (b & 1));
        if (lane == 0 && r == SIG_W) TS(33);
        r = e;
      }
      const int hc = kh * 896 + nt * 192, hx = kh * 896 + 768 + nt * 24;
#pragma unroll 1
      for (int n = 0; n < 32; n += 4) {
        const int i = (H_ORD >> n) & 7, hw = i >> 2, blk = i & 3;
        if (n == 4 * W2_PF) ONE(prefetch_l2(P.w2 + (size_t)b * (FF * DM / NCTA), FF * DM / NCTA * 2));
        mbar_wait(BAR(B_HB + i), 0);
        fence_async_smem();
        asm volatile("cp.async.bulk.wait_group %0;" ::"n"(H_FLY - 1) : "memory");
        ONE(tma2d_st(blk < 3 ? &M.hs : &M.hx, blk < 3 ? hc + blk * 64 : hx, rb * 128 + hw * 64, sb + hw * HST + blk * 8192); bulk_commit());
      }
      const int cf = (nt * 160 + (nt & 1) * 32) >> 6, ch = nt * 160 + ((nt & 1) ? 0 : 128);
      auto g2_load_b = [&](int kc) {
        const int s = kc & 3, wr = kc < 2 ? 1536 + kh * 96 + (1 - kc) * 64 : kh * 768 + (kc - 2) * 64;
        const uint32_t fb = BAR(B_F2 + s);
        mbar_expect(fb, kc == 0 ? 8192 + 20480 : 16384 + 20480);
        tma3d(sb + g2_b(s), &M.w2, 0, wr, cf, fb);
        tma2d(sb + g2_b(s) + 16384, &M.w2x, ch, wr, fb);
      };
      auto g2_load_a = [&](int kc) {
        const int s = kc & 3;
        tma2d(sb + g2_a(s), kc == 0 ? &M.hn : &M.ha, kh * 896 + (kc < 2 ? 768 + (1 - kc) * 64 : (kc - 2) * 64), rb * 128, BAR(B_F2 + s));
      };
      bulk_wait_all();
      ONE(g2_load_b(0); g2_load_b(1));
      fence_release();
      ONE(signal_cnt(CNT_H + rb * 2 + kh); TS(37));
      wait_cnt(CNT_H + rb * 2 + kh, 4 * ep);
      ONE(TS(39); g2_load_a(0); g2_load_a(1); prefetch_map(&M.qf); prefetch_map(&M.y); prefetch_map(&M.out));
      mbar_wait(BAR(B_KD + 4), 0);
      ONE(g2_load_b(3));
      mbar_wait(BAR(B_TD + 1), 0);
      ONE(g2_load_b(2); g2_load_a(2));
      mbar_wait(BAR(SUM3 ? B_TD : B_SD + 3), 0);
      ONE(mbar_expect(BAR(B_FINQ), 20480); tma3d(sb + FIN_Q, &M.qf, 0, rb * 128 + kh * 64, nt * 5, BAR(B_FINQ)));
      mbar_wait(BAR(B_RF + 2), 0);
      ONE(g2_load_a(3); TS(38));
#pragma unroll 1
      for (int kc = 4; kc < 14; kc++) {
        mbar_wait(BAR(B_E2 + (kc & 3)), ((kc >> 2) - 1) & 1);
        ONE(g2_load_b(kc); g2_load_a(kc));
      }
      if (lane == 0) g_launch[b * 8] = ep;
#pragma unroll 1
      for (int i = 0; i < 5; i++) {
        int gi = i + (nt & 1); if (gi == 5) gi = 0;
        mbar_wait(BAR(B_OUT + i), 0);
        fence_async_smem();
        ONE(tma2d_st(&M.out, nt * 160 + gi * 32, rb * 128 + kh * 64, sb + FIN_Q + gi * 4096));
      }
      ONE(bulk_commit());
      bulk_wait_read();
    } else {
      const int aw = warp - 9, at = tid - 288;
      if (aw == 0) {
        if (lane == 0) {
#pragma unroll
          for (int s = 0; s < 4; s++) { mbar_init(BAR(B_E1 + s), 8); mbar_init(BAR(B_FR + s), 8); mbar_init(BAR(B_F2 + s), 1); mbar_init(BAR(B_E2 + s), 8); }
          mbar_init(BAR(B_KRAW), 1); mbar_init(BAR(B_KRAW + 1), 1);
          mbar_init(BAR(B_RED), 8); mbar_init(BAR(B_BX), 1);
        }
      } else if (aw == 1) {
        if (lane == 0) {
#pragma unroll
          for (int c = 0; c < 5; c++) { mbar_init(BAR(B_KD + c), 2); mbar_init(BAR(B_KT + c), 1); mbar_init(BAR(B_XF + c), 1); mbar_init(BAR(B_SD + c), 4); }
        }
      } else if (lane == 0) {
#pragma unroll
        for (int i = 0; i < 8; i++) mbar_init(BAR(B_HB + i), 4);
#pragma unroll
        for (int c = 0; c < 3; c++) mbar_init(BAR(B_RF + c), 3);
        for (int r = 0; r < 5; r++) { mbar_init(BAR(B_KIN + r), 1); mbar_init(BAR(B_KIN1 + r), 1); }
        mbar_init(BAR(B_YSLOT), 8); mbar_init(BAR(B_XR), 1);
        for (int i = 0; i < 5; i++) mbar_init(BAR(B_OUT + i), 4);
        mbar_init(BAR(B_XD), 1); mbar_expect(BAR(B_XD), 8192); mbar_init(BAR(B_XD + 1), 1); mbar_expect(BAR(B_XD + 1), 12288);
        asm volatile("fence.mbarrier_init.release.cluster;" ::: "memory");
        mbar_init(BAR(B_TD), 4); mbar_init(BAR(B_TD + 1), 8); mbar_init(BAR(B_FINQ), 1); mbar_init(BAR(B_FINY), 1);
      }
      __syncwarp();
      bar_arrive(NB_INIT, 384);
      if (aw == 1) ONE(prefetch_map(&M.k); prefetch_map(&M.v));
      const uint32_t dv0 = ld_relaxed32(lane < 5 ? static_cast<const void*>(P.ssm_D + 128 * lane + (b & ~1)) : &g_launch[b * 8]);
      const uint32_t b2v = ldg32(reinterpret_cast<const uint32_t*>(P.b2 + nt * 160) + (min(at, 79) + 16 * (nt & 1)) % 80);
      const int l27 = min(lane, 26), col = l27 < 24 ? 192 * j + 8 * l27 : 1536 + 24 * j + 8 * (l27 - 24);
      uint4 sk = ldg128(aw < 2 ? P.shift_k + (64 * (b & 1) + 2 * lane) * 4 : P.b1 + col);
      bar_sync(NB_INIT2, 128);
      if (aw == 0) ONE(prefetch_map(&M.kvs));
      if (lane < 4) sts32(sb + M_ZERO + lane * 4, 0u);
      if (lane < 8) sts32(sb + M_AUX + aw * 32 + lane * 4, lane >= 5 ? dv0 + 1 : ((b & 1) ? dv0 >> 16 : dv0 & 0xFFFFu));
      if (at < 80) sts32(sb + M_B2 + at * 4, bmul2(b2v, 0x3f003f00u));
      __syncwarp();
      if (aw == 0) bar_arrive(NB_INIT3, 64);
      uint32_t kvok;
      if (aw == 2) {
        const unsigned ep = lds32(sb + M_AUX + 64 + 20);
        const uint4 bb = sk;
        const uint32_t ba = sb + M_BX + (l27 >> 2) * 512 + ((l27 & 3) << 4);
        mbar_wait(BAR(B_RED), 0);
        const uint32_t tg = ep & 15u;
        auto tagged = [&](float v) { return (__float_as_uint(v) & ~15u) | tg; };
        float c0 = 0.f, c1 = 0.f, s1 = 0.f, s2 = 0.f;
#pragma unroll
        for (int i = 0; i < 16; i += 2) { c0 += __uint_as_float(lds32(sb + M_RED1 + i * 128 + lane * 4)); c1 += __uint_as_float(lds32(sb + M_RED1 + i * 128 + 128 + lane * 4)); }
        st_relaxed32(&g_cs[(dir * 8 + j) * 256 + ci * 32 + lane], tagged(c0 + c1));
        float2 u[8];
#pragma unroll
        for (int i = 0; i < 8; i++) u[i] = lds64f(sb + M_RED0 + (lane & 15) * 128 + ((i + lane) & 7) * 16 + (lane >> 4) * 8);
        const float c = bf_round(u[0].x * (1.f / 40)), cc = 40.f * c * c;
#pragma unroll
        for (int i = 0; i < 8; i++) { s1 += fmaf(-40.f, c, u[i].x); s2 += fmaf(-2.f * c, u[i].x, u[i].y) + cc; }
        const float dm = s1 * (1.f / 320);
        st_relaxed64(&g_stat[dir * SL + rb * 128 + ri * 32 + lane], tagged(c + dm), tagged(fmaf(-dm, s1, s2)));
        __syncwarp();
        if (lane == 0) TS(30);
        sts128((ba + 128) ^ 16, 0u, 0u, 0u, 0u); sts128((ba + 192) ^ 16, bb.x, bb.y, bb.z, bb.w);
#pragma unroll
        for (int i = 4; i < 8; i++) sts128((ba + i * 64) ^ ((i >> 1) << 4), 0u, 0u, 0u, 0u);
        if (SIG_W) {
          mbar_wait(BAR(B_KD + SIG_W - 1), 0);
          fence_release();
          if (lane < SIG_W) signal_cnt(CNT_KV + lane * 2 + (b & 1));
        }
        mbar_wait(BAR(B_FR), 0);
        auto raw_load = [&]() {
          ONE(mbar_expect(BAR(B_KRAW), 4096); mbar_expect(BAR(B_KRAW + 1), 4 * 4096);
              for (int c = 0; c < 5; c++) bulk_g2s(sb + cv_t(c) + KT_E, P.ssm_k + (size_t)(128 * c + b) * SL, 4096, BAR(B_KRAW + (c >= 1))));
        };
        uint32_t x[32], n = 0;
#pragma unroll 1
        while (true) {
#pragma unroll
          for (int i = 0; i < 8; i++) {
            const uint4 v = ld_relaxed128(i < 4 ? static_cast<const void*>(g_cs + ((i >> 1) * 8 + j) * 256 + l27 * 8 + (i & 1) * 4)
                                                : g_stat + ((i >> 1) & 1) * SL + rb * 128 + lane * 4 + (i & 1) * 2);
            x[4 * i] = v.x; x[4 * i + 1] = v.y; x[4 * i + 2] = v.z; x[4 * i + 3] = v.w;
          }
          kvok = ld_relaxed32(&g_cnt[(CNT_KV + (b >> 6)) * 32]);
          if (!RAW_LATE && n == 0) raw_load();
          uint32_t bad = 0;
#pragma unroll
          for (int i = 0; i < 32; i++) { x[i] ^= tg; bad |= x[i]; }
          if (__all_sync(0xffffffffu, (bad & 15u) == 0) || spin_guard(n, 0x131)) break;
        }
        if (RAW_LATE) raw_load();
        uint32_t st[4];
#pragma unroll
        for (int i = 0; i < 4; i++) {
          const float ma = __uint_as_float(x[16 + 2 * i]), mb = __uint_as_float(x[24 + 2 * i]), dl = ma - mb;
          const float m2 = fmaf(dl * dl, 160.f, __uint_as_float(x[17 + 2 * i]) + __uint_as_float(x[25 + 2 * i]));
          const float vb = bf_round(fmaxf(m2, 0.f) * (1.f / DM));
          st[i] = pack_bf16(0.5f * (ma + mb), sqrt_fast(bf_round(vb + 1e-5f)));
        }
        sts128(sb + M_STAT + lane * 16, st[0], st[1], st[2], st[3]);
        uint32_t hi[4], lo[4];
#pragma unroll
        for (int i = 0; i < 4; i++) {
          const float x0 = __uint_as_float(x[2 * i]) + __uint_as_float(x[8 + 2 * i]), x1 = __uint_as_float(x[2 * i + 1]) + __uint_as_float(x[9 + 2 * i]);
          hi[i] = pack_bf16(x0, x1); lo[i] = pack_bf16(x0 - bf_lo(hi[i]), x1 - bf_hi(hi[i]));
        }
        sts128(ba, hi[0], hi[1], hi[2], hi[3]); sts128(ba + 64, lo[0], lo[1], lo[2], lo[3]);
        fence_async_smem();
        __syncwarp();
        ONE(mbar_arrive(BAR(B_BX)); TS(54));
      }
      if (aw < 2) {
        auto done = [&](int r) {
          bulk_wait_all();
          ONE(mbar_arrive(BAR(B_KD + r)); if (r < 2) kv_load(r + 3, aw); TSKV);
        };
        bool pend = false;
#pragma unroll 1
        for (int r = 0; r < 5; r++) {
          const int c0 = 128 * r + 64 * (b & 1);
          const uint32_t buf = sb + KVS + (r < 3 ? r : r - 3) * KV_BUF, stg = buf + aw * 2048, vb = stg + lane * 4, kb = buf + 4096 + aw * 2432 + lane * 4;
          const uint32_t w0 = __byte_perm(sk.x, sk.z, 0x5410), w1 = __byte_perm(sk.x, sk.z, 0x7632);
          const uint32_t w2 = __byte_perm(sk.y, sk.w, 0x5410), w3 = __byte_perm(sk.y, sk.w, 0x7632);
          if (r < 4) sk = ldg128(P.shift_k + (c0 + 128 + 2 * lane) * 4);
          mbar_wait(BAR((aw ? B_KIN1 : B_KIN) + r), 0);
          if (at == 0 && r == 0) TS(56);
          uint32_t kk[19], o[16];
#pragma unroll
          for (int i = 0; i < 19; i++) { kk[i] = lds32(kb + i * 128); if (i >= 3) o[i - 3] = lds32(vb + (i - 3) * 128); }
#pragma unroll
          for (int i = 0; i < 16; i++) o[i] = bmul2(bfma2(kk[i + 3], w0, bfma2(kk[i + 2], w1, bfma2(kk[i + 1], w2, bmul2(kk[i], w3)))), o[i]);
          __syncwarp();
          const uint32_t a0 = stg + lane * 64 + ((lane & 6) << 3);
          const uint32_t s0 = (lane & 4) ? 0x7632 : 0x5410, s1 = s0 ^ 0x2222;
#pragma unroll
          for (int hh = 0; hh < 2; hh++) {
            const uint32_t* u = o + 8 * hh;
            const uint32_t a = a0 ^ (hh << 4);
            sts128(a, __byte_perm(u[1], u[0], s0), __byte_perm(u[3], u[2], s0), __byte_perm(u[5], u[4], s0), __byte_perm(u[7], u[6], s0));
            sts128(a ^ 32, __byte_perm(u[1], u[0], s1), __byte_perm(u[3], u[2], s1), __byte_perm(u[5], u[4], s1), __byte_perm(u[7], u[6], s1));
          }
          if (pend) done(r - 1);
          fence_async_smem();
          __syncwarp();
          ONE(tma2d_st(&M.kvs, 32 * (b >> 1) + 16 * aw, c0, stg); bulk_commit());
          pend = r < 4 && mbar_test(BAR((aw ? B_KIN1 : B_KIN) + r + 1), 0);
          if (!pend) done(r);
        }
      }
      const unsigned ep = lds32(sb + M_AUX + aw * 32 + 20);
      if (aw == 0) {
        mbar_wait(BAR(B_KD + 4), 0);
        fence_release();
        if (lane >= SIG_P && lane < 5) signal_cnt(CNT_KV + lane * 2 + (b & 1));
        if (lane == 0) TS(34);
      } else {
        auto pad = [&](int c0, int c1) {
          if (lane < 17) for (int c = c0; c < c1; c++) sts128(sb + cv_x(c) + lane * 16, 0u, 0u, 0u, 0u);
          fence_async_smem();
          __syncwarp();
        };
        const unsigned* cp = &g_cnt[(CNT_KV + min(lane, 4) * 2 + (b >> 6)) * 32];
        uint32_t n = 0;
        if (aw == 2) { mbar_wait(BAR(B_FR + 1), 0); pad(0, 4); if (lane) kvok = 64 * ep - 1; }
        const int tb1 = aw == 2 ? TB2 : 5;
#pragma unroll 1
        for (int c = aw == 2 ? 0 : 5, tb = aw == 2 ? 0 : TB2; c < 5 || tb < tb1;) {
          if (c < 5) {
            const uint32_t ok = __ballot_sync(0xffffffffu, (int)(kvok - 64 * ep) >= 0) | (spin_guard(n, 0x140) ? 31u : 0u);
            fence_acquire();
#pragma unroll 1
            for (; c < 5 && (ok >> c & 1); c++) {
              if (c == 4) { mbar_wait(BAR(B_KD + 4), 0); pad(4, 5); }
              ONE(x_load(c); if (c == 0) TS(36); if (c >= 3) TS(28 + c));
            }
          }
          if (c < 5) kvok = ld_relaxed32(cp);
          if (tb < tb1) { mbar_wait(BAR(B_KRAW + (tb > 0)), 0); table(tb, aw); if (tb == 1 && lane == 0) TS(55); tb++; }
        }
      }
      if (RED_GATE) mbar_wait(BAR(RED_GATE == 1 ? B_TD + 1 : B_SD + RED_GATE - 1), 0);
#pragma unroll 1
      for (int c = 0; c < 5; c++) {
        mbar_wait(BAR(B_SD + c), 0);
        if (c == 3 && SUM3) continue;
        conv_sum(c, aw * 96 + lane, aw < 2);
        __syncwarp();
        if (c < 3 && lane == 0) mbar_arrive(BAR(B_RF + c));
        if (at == 0) TS(59 + c);
      }
      bar_sync(NB_AUX, 96);
      if (aw == 0) {
        fence_release();
        ONE(signal_cnt(CNT_Y); TS(3));
        wait_cnt(CNT_Y, 128 * ep);
        ONE(TS(40); mbar_arrive(BAR(B_XR)));
        mbar_wait(BAR(B_YSLOT), 0);
        ONE(mbar_expect(BAR(B_FINY), 20480); tma2d(sb + FIN_Y, &M.y, rb * 128 + kh * 64, nt * 160, BAR(B_FINY)));
      }
    }
  } else {
    asm volatile("setmaxnreg.inc.sync.aligned.u32 " REG_CON ";");
    const int wg = warp >> 2, w = warp & 3, g = lane >> 2, q = lane & 3;
    constexpr bool elect = false;
    uint32_t ca[64];
    const uint32_t ab0 = sb + ((g & 1) ? KT_E : KT_O) + (8 * w + 4 + (g >> 1) - q) * 4;
    auto conv_lda = [&](int c, int k0, int k1) {
      const uint32_t ab = ab0 + cv_t(c);
#pragma unroll
      for (int ks = 15; ks >= 0; ks--) {
        if (ks >= k0 && ks < k1) {
          ca[4 * ks + 0] = lds32(ab + ks * 256);
          ca[4 * ks + 1] = lds32(ab + ks * 256 + 128);
          ca[4 * ks + 2] = lds32(ab + ks * 256 - 16);
          ca[4 * ks + 3] = lds32(ab + ks * 256 + 112);
        }
      }
    };
    {
      float d[108];
      auto g1_release = [&](int kc) { if (lane == 0) mbar_arrive(BAR(kc < 6 ? B_E1 + (kc & 3) : B_FR + kc - 6)); };
      auto g1_wait = [&](int kc) { mbar_wait(BAR(B_F1 + (kc & 3)), (kc >> 2) & 1); };
      auto g1_issue = [&](int kc) {
        const int s = kc & 3;
        if (kc == 0) { mbar_wait(BAR(B_F1), 0); if (wg == 1) bar_sync(NB_LEAD, 256); }
        if (tid == 0) TS(8 + kc);
        const uint32_t st = sc + s * G1_STAGE;
        const uint64_t da = mkdesc(st + wg * 8192, 16, 1024, 1), db = mkdesc(st + 16384, 8192, 1024, 1);
        wg_fence();
#pragma unroll
        for (int k = 0; k < 4; k++) {
          wg_ss_216(d, da + k * 2, db + k * 128, (kc | k) != 0);
          if (k == REL_K || k == 3) wg_commit();
          if (k == REL_K && kc > 0) { wg_wait<1>(); g1_release(kc - 1); }
        }
        if (kc == 0 && wg == 0) bar_arrive(NB_LEAD, 256);
      };
      const int t7 = tid & 127, wr = ((t7 >> 3) & 1) * 4 + (t7 >> 4) * 8, wc = 4 * min(ci, 6) + ((t7 >> 1) & 3);
      const uint32_t sa0 = sb + (wg ? 16384 + (wc >> 3) * 8192 + wr * 128 + (((wc ^ wr) & 7) << 4) + (t7 & 1) * 8 : ri * 4096 + t7 * 16);
      float t1 = 0.f, t2 = 0.f, t3 = 0.f, t4 = 0.f;
      auto piece = [&](int i) {
        if (wg == 0) {
          const uint4 x = lds128(sa0 + (i & 3) * G1_STAGE), y = lds128(sa0 + (i & 3) * G1_STAGE + 2048);
          const uint32_t xx[4] = {x.x, x.y, x.z, x.w}, yy[4] = {y.x, y.y, y.z, y.w};
#pragma unroll
          for (int e = 0; e < 4; e++) {
            const float u = bf_lo(xx[e]), v = bf_hi(xx[e]), r = bf_lo(yy[e]), z = bf_hi(yy[e]);
            t1 += u; t2 = fmaf(u, u, t2); t3 += r; t4 = fmaf(r, r, t4);
            t1 += v; t2 = fmaf(v, v, t2); t3 += z; t4 = fmaf(z, z, t4);
          }
        } else {
          float2 xx[4];
#pragma unroll
          for (int e = 0; e < 4; e++) xx[e] = lds64f((sa0 ^ (e * 144)) + (i & 3) * G1_STAGE);
#pragma unroll
          for (int e = 0; e < 4; e++) {
            const uint32_t u = __float_as_uint(xx[e].x), v = __float_as_uint(xx[e].y);
            t1 += bf_lo(u); t2 += bf_hi(u); t3 += bf_lo(v); t4 += bf_hi(v);
          }
        }
      };
      bar_sync(NB_INIT, 384);
#pragma unroll
      for (int kc = 0; kc < 10; kc++) {
        g1_issue(kc);
        if (kc < 5) { g1_wait(kc); piece(kc); }
        if (kc == 4) {
          sts128(sb + (wg ? M_RED1 : M_RED0) + t7 * 16, __float_as_uint(t1), __float_as_uint(t2), __float_as_uint(t3), __float_as_uint(t4));
          __syncwarp();
          if (lane == 0) mbar_arrive(BAR(B_RED));
        }
        if (kc < 9) g1_wait(kc + 1);
      }
      uint2 s0, s1;
      {
        mbar_wait(BAR(B_BX), 0);
        s0.x = lds32(sb + M_STAT + (wg * 64 + w * 16 + g) * 4); s1.x = lds32(sb + M_STAT + (wg * 64 + w * 16 + g + 8) * 4);
        if (tid == 0) TS(46);
        const uint32_t f0 = q == 0 ? ((s0.x & 0xFFFFu) * 0x10001u) ^ 0x80008000u : (q == 1 ? s0.x ^ 0x8000u : 0u);
        const uint32_t f1 = q == 0 ? ((s1.x & 0xFFFFu) * 0x10001u) ^ 0x80008000u : (q == 1 ? s1.x ^ 0x8000u : 0u);
        wg_fence();
        wg_rs_216(d, f0, f1, 0u, 0u, mkdesc(sc + M_BX, 512, 0, 2));
        wg_commit();
      }
      wg_wait<1>();
      if (lane == 0) mbar_arrive(BAR(B_FR + 3));
      const float r0 = 0.25f * rcp_fast(bf_hi(s0.x)), r1 = 0.25f * rcp_fast(bf_hi(s1.x));
      if (wg == 0) mbar_wait(BAR(B_FR + 2), 0);
      wg_wait<0>();
      if (elect) TS(1 + 47 * wg);
      if (wg == 1) bar_sync(NB_GELU, 256);
      const int mi = lane >> 3, row = w * 16 + (mi & 1) * 8 + (lane & 7);
      const uint32_t hs = sb + wg * HST;
      constexpr float C1 = 4.f * 0.7978845608028654f, C2 = 64.f * 0.7978845608028654f * 0.044715f;
      auto gelu2 = [&](float hx) { const float u = hx * fmaf(hx * hx, C2, C1); return fmaf(hx, tanh_fast(u), hx); };
#pragma unroll
      for (int nb = 0; nb < 28; nb += 2) {
        uint32_t p[4];
#pragma unroll
        for (int e = 0; e < 2; e++) {
          if (nb + e < 27) {
            const float* dd = d + 4 * (nb + e);
            p[2 * e] = pack_bf16(gelu2(dd[0] * r0), gelu2(dd[1] * r0));
            p[2 * e + 1] = pack_bf16(gelu2(dd[2] * r1), gelu2(dd[3] * r1));
          }
        }
        const int nbm = nb + (mi >> 1);
        if (nb < 24) stsm4(hs + (nb >> 3) * 8192 + row * 128 + (((nbm & 7) ^ (row & 7)) << 4), p[0], p[1], p[2], p[3]);
        else if (nb == 24) stsm4(hs + 24576 + row * 48 + (mi >> 1) * 16, p[0], p[1], p[2], p[3]);
        else stsm2(hs + 24576 + row * 48 + 32, p[0], p[1]);
        if ((nb & 7) == 6 || nb == 26) {
          __syncwarp();
          if (lane == 0) mbar_arrive(BAR(B_HB + wg * 4 + (nb >> 3)));
        }
        if (nb == GELU_NB && wg == 0) bar_arrive(NB_GELU, 256);
        if (nb == A_NB0) mbar_wait(BAR(B_KT + wg), 0);
        if (nb >= A_NB0 && A_NB0 < 28) conv_lda(wg, 16 - ((nb - A_NB0) / 2 + 1) * 16 / (A_NB0 < 28 ? (28 - A_NB0) / 2 : 1), 16 - (nb - A_NB0) / 2 * 16 / (A_NB0 < 28 ? (28 - A_NB0) / 2 : 1));
      }
      if (A_NB0 >= 28) { mbar_wait(BAR(B_KT + wg), 0); conv_lda(wg, 0, 16); }
      if (elect) TS(2 + 47 * wg);
    }
#pragma unroll 1
    for (int c = wg; c < 5; c += 2) {
      float d[128];
      mbar_wait(BAR(B_XF + c), 0);
      if (c < 3) mbar_wait(BAR(B_KT + c + 2), 0);
      const uint64_t db = mkdesc(sc + cv_x(c), 16, 128, 0);
      if (c > 0) { if (wg) bar_sync(NB_TURN + 1, 256); else bar_sync(NB_TURN, 256); }
      wg_fence();
      auto hand = [&]() { if (wg) bar_arrive(NB_TURN, 256); else bar_arrive(NB_TURN + 1, 256); };
      if (c < 3) conv_chain_1(d, ca, db, ab0 + cv_t(c + 2), hand); else conv_chain_0(d, ca, db, 0, hand);
      mbar_wait(BAR(c >= 3 ? B_RF + c - 3 : B_FR + 3), 0);
      wg_wait<0>();
      if (elect) TS(41 + c);
      const uint32_t wa = sb + cv_p(c) + w * 4096 + lane * 16;
#pragma unroll
      for (int n4 = 0; n4 < 32; n4 += 4) {
        uint32_t p[4];
#pragma unroll
        for (int e = 0; e < 4; e++) {
          const int nb = n4 + e;
          float x = d[4 * nb], y = d[4 * nb + 1];
          if (nb > 0) { x += d[4 * nb - 2]; y += d[4 * nb - 1]; }
          p[e] = pack_bf16(x, y);
        }
        stsm4t(wa + n4 * 128, p[0], p[1], p[2], p[3]);
      }
      if (c == 3 && SUM3) break;
      __syncwarp();
      if (lane == 0) mbar_arrive(BAR(B_SD + c));
      if (c < 3) {
        conv_lda(c + 2, 0, CV_RELOADED);
        if (c > 0) {
          fence_async_smem();
          __syncwarp();
          if (lane == 0) mbar_arrive(BAR(B_TD + 1));
        }
      }
    }
    if (elect) TS(51 + wg);
    {
      float d[80];
      const uint32_t aoff = (wg ^ kh) * 8192;
      auto g2_release = [&](int kc) { if (lane == 0) mbar_arrive(BAR(kc == 10 ? B_YSLOT : B_E2 + (kc & 3))); };
      auto g2_mma = [&](int kc, int first, bool rel) {
        const int s = kc & 3;
        mbar_wait(BAR(B_F2 + s), (kc >> 2) & 1);
        const uint64_t da = mkdesc(sc + g2_a(s) + aoff, 16, 1024, 1), db = mkdesc(sc + g2_b(s), 8192, 1024, 1);
        wg_fence();
#pragma unroll
        for (int k = 0; k < (kc ? 4 : 2); k++) {
          wg_ss_160(d, da + k * 2, db + k * 128, k ? 1 : first);
          if ((k == REL_K && rel) || k == (kc ? 3 : 1)) wg_commit();
          if (k == REL_K && rel) { wg_wait<1>(); g2_release(kc - 1); }
        }
      };
      if (wg == 1) {
        if (SUM3) {
          bar_sync(NB_WG1, 128);
          if (lane == 0) mbar_arrive(BAR(B_TD));
          conv_sum(3, w * 64 + lane, false);
          __syncwarp();
          if (lane == 0) mbar_arrive(BAR(B_SD + 3));
          if (elect) TS(62);
        }
#pragma unroll
        for (int nb = 0; nb < 20; nb++) {
          const uint32_t v = lds32(sb + M_B2 + nb * 16 + q * 4);
          d[4 * nb] = d[4 * nb + 2] = bf_lo(v); d[4 * nb + 1] = d[4 * nb + 3] = bf_hi(v);
        }
        bar_sync(NB_TURN + 1, 256);
        g2_mma(0, 1, false);
#pragma unroll
        for (int kc = 1; kc < 14; kc++) {
          g2_mma(kc, 1, kc < 12);
          if (kc == END_KC) bar_arrive(NB_END, 256);
        }
        mbar_wait(BAR(B_XR), 0);
        wg_wait<0>();
        if (elect) TS(53);
        const uint32_t ra = mapa(sb, kh ^ 1), rbar = ra + M_BAR + 8 * B_XD, dst = ra + (tid & 127) * 16;
#pragma unroll
        for (int i = 0; i < 10; i++) {
          const float* dd = d + 8 * i;
          st_async128(dst + (i < 5 ? P0 + i * 2048 : P1 + (i - 5) * 2048), pack_bf16(dd[0], dd[1]), pack_bf16(dd[2], dd[3]), pack_bf16(dd[4], dd[5]), pack_bf16(dd[6], dd[7]), rbar + 8 * (i >= 4));
        }
        if (elect) TS(7);
      } else {
        const int mi = lane >> 3, row = (mi & 1) * 8 + (lane & 7);
        const uint32_t qa = sb + FIN_Q + (w * 16 + row) * 64;
        auto q_addr = [&](int np) {
          int gi = (np >> 1) + (nt & 1); if (gi == 5) gi = 0;
          return qa + gi * 4096 + ((((np & 1) * 2 + (mi >> 1)) ^ ((row >> 1) & 3)) << 4);
        };
        uint32_t sv[40];
        uint32_t m0, m1; float rs0, rs1;
        g2_mma(0, 0, false);
#pragma unroll
        for (int kc = 1; kc < 10; kc++) {
          if (tid == 0) TS(17 + kc);
          g2_mma(kc, 1, true);
          if (kc == XP_KC - 1) {
            const uint32_t s0 = lds32(sb + M_STAT + (kh * 64 + w * 16 + g) * 4), s1 = lds32(sb + M_STAT + (kh * 64 + w * 16 + g + 8) * 4);
            m0 = (s0 & 0xFFFFu) * 0x10001u; m1 = (s1 & 0xFFFFu) * 0x10001u;
            rs0 = rcp_fast(bf_hi(s0)); rs1 = rcp_fast(bf_hi(s1));
          }
          if (kc >= XP_KC && XP_KC < 10) {
            mbar_wait(BAR(B_FINQ), 0);
#pragma unroll
            for (int np = 10 * (kc - XP_KC) / (XP_KC < 10 ? 10 - XP_KC : 1); np < 10 * (kc + 1 - XP_KC) / (XP_KC < 10 ? 10 - XP_KC : 1); np++) {
              uint32_t xq[4];
              ldsm4(q_addr(np), xq[0], xq[1], xq[2], xq[3]);
#pragma unroll
              for (int e = 0; e < 4; e++) {
                const uint32_t dm = bsub2(xq[e], (e & 1) ? m1 : m0);
                const float rs = (e & 1) ? rs1 : rs0;
                sv[4 * np + e] = pack_bf16(bf_lo(dm) * rs, bf_hi(dm) * rs);
              }
            }
          }
        }
        auto y_prep = [&](int n0, int n1) {
          if (n1 > n0) mbar_wait(BAR(B_FINY), 0);
#pragma unroll
          for (int np = n0; np < n1; np++) {
            int cb = 2 * np + 4 * (nt & 1); if (cb >= 20) cb -= 20;
            cb += mi >> 1;
            const uint32_t ya = sb + FIN_Y + cb * 1024 + (lane & 7) * 128 + (((2 * w + (mi & 1)) ^ (lane & 7)) << 4);
            uint32_t y[4];
            ldsm4t(ya, y[0], y[1], y[2], y[3]);
#pragma unroll
            for (int e = 0; e < 4; e++) sv[4 * np + e] = bmul2(sv[4 * np + e], y[e]);
          }
        };
        if (tid == 0) TS(27);
#pragma unroll
        for (int kc = 10; kc < 14; kc++) {
          g2_mma(kc, 1, kc == 10 || (kc == 11 && HOLD_KC > 10));
          if (kc == HOLD_KC) {
            if (kc == 10) { wg_wait<0>(); g2_release(10); }
            if (tid == 0) TS(28);
            bar_sync(NB_END, 256);
          }
          if (kc == 12) y_prep(0, YP_N);
        }
        if (tid == 0) TS(29);
        y_prep(YP_N, 10);
        if (tid == 0) TS(47);
        mbar_wait(BAR(B_XD), 0);
        if (tid == 0) TS(5);
        uint4 v0 = lds128(sb + tid * 16 + P0), v1 = lds128(sb + tid * 16 + P0 + 2048);
        wg_wait<0>();
        if (tid == 0) TS(4);
#pragma unroll
        for (int np = 0; np < 10; np++) {
          const uint32_t pw[4] = {v0.x, v0.y, v0.z, v0.w};
          v0 = v1;
          if (np < 8) {
            if (np == 2) mbar_wait(BAR(B_XD + 1), 0);
            v1 = lds128(sb + tid * 16 + (np + 2 < 5 ? P0 + (np + 2) * 2048 : P1 + (np - 3) * 2048));
          }
          uint32_t o[4];
          ldsm4(q_addr(np), o[0], o[1], o[2], o[3]);
#pragma unroll
          for (int e = 0; e < 4; e++) {
            const float h0 = d[8 * np + 2 * e] + bf_lo(pw[e]), h1 = d[8 * np + 2 * e + 1] + bf_hi(pw[e]);
            o[e] = bfma2(sv[4 * np + e], pack_bf16(fmaf(h0, tanh_fast(h0), h0), fmaf(h1, tanh_fast(h1), h1)), o[e]);
          }
          stsm4(q_addr(np), o[0], o[1], o[2], o[3]);
          if (np & 1) {
            if (np == 9 && tid == 0) TS(50);
            __syncwarp();
            if (lane == 0) mbar_arrive(BAR(B_OUT + (np >> 1)));
          }
        }
      }
    }
  }
}

typedef CUresult (*EncFn)(CUtensorMap*, CUtensorMapDataType, cuuint32_t, void*, const cuuint64_t*, const cuuint64_t*, const cuuint32_t*, const cuuint32_t*,
                          CUtensorMapInterleave, CUtensorMapSwizzle, CUtensorMapL2promotion, CUtensorMapFloatOOBfill);

static void make_map(EncFn enc, CUtensorMap* tm, const void* ptr, int cols, int rows, int bc, int br, int grp, CUtensorMapSwizzle sw,
                     CUtensorMapL2promotion promo = CU_TENSOR_MAP_L2_PROMOTION_NONE) {
  cuuint64_t gd[3] = {(cuuint64_t)(grp ? bc : cols), (cuuint64_t)rows, (cuuint64_t)(cols / bc)};
  cuuint64_t gs[2] = {(cuuint64_t)cols * 2, (cuuint64_t)bc * 2};
  cuuint32_t bd[3] = {(cuuint32_t)bc, (cuuint32_t)br, (cuuint32_t)grp};
  cuuint32_t es[3] = {1, 1, 1};
  CUresult r = enc(tm, CU_TENSOR_MAP_DATA_TYPE_BFLOAT16, grp ? 3 : 2, const_cast<void*>(ptr), gd, gs, bd, es, CU_TENSOR_MAP_INTERLEAVE_NONE, sw,
                   promo, CU_TENSOR_MAP_FLOAT_OOB_FILL_NONE);
  (void)r;
}

}

extern "C" void kernel_launch(void* const* d_in, const int* in_sizes, int n_in, void* d_out, int out_size) {
  using namespace h3;
  (void)in_sizes; (void)n_in; (void)out_size;
  static EncFn enc = nullptr;
  static void *p_h = nullptr, *p_yT = nullptr, *p_kvT = nullptr;
  if (!enc) {
    void* fn = nullptr; cudaDriverEntryPointQueryResult qr;
    cudaGetDriverEntryPoint("cuTensorMapEncodeTiled", &fn, cudaEnableDefault, &qr);
    enc = (EncFn)fn;
    cudaGetSymbolAddress(&p_h, g_h);
    cudaGetSymbolAddress(&p_yT, g_yT);
    cudaGetSymbolAddress(&p_kvT, g_kvT);
    cudaFuncSetAttribute(h3_kernel, cudaFuncAttributeMaxDynamicSharedMemorySize, SMEM_BYTES);
  }
  Params P;
  P.q = (const __nv_bfloat16*)d_in[0]; P.k = (const __nv_bfloat16*)d_in[1]; P.v = (const __nv_bfloat16*)d_in[2];
  P.shift_k = (const __nv_bfloat16*)d_in[3]; P.ssm_k = (const __nv_bfloat16*)d_in[4]; P.ssm_D = (const __nv_bfloat16*)d_in[5];
  P.out = (__nv_bfloat16*)d_out;
  P.w1 = (const __nv_bfloat16*)d_in[7]; P.b1 = (const __nv_bfloat16*)d_in[8]; P.w2 = (const __nv_bfloat16*)d_in[9]; P.b2 = (const __nv_bfloat16*)d_in[10];
  const CUtensorMapSwizzle S128 = CU_TENSOR_MAP_SWIZZLE_128B, S64 = CU_TENSOR_MAP_SWIZZLE_64B, S0 = CU_TENSOR_MAP_SWIZZLE_NONE;
  Maps M;
  make_map(enc, &M.qa, P.q, DM, SL, 64, 128, 0, S128);
  make_map(enc, &M.w1, P.w1, FF, DM, 64, 64, 3, S128);
  make_map(enc, &M.w1x, P.w1, FF, DM, 24, 64, 0, S128, WS_PROMO);
  make_map(enc, &M.k, P.k, DM, SL, 64, 19, 0, S0);
  make_map(enc, &M.v, P.v, DM, SL, 64, 16, 0, S0);
  make_map(enc, &M.hs, p_h, HP, SL, 64, 64, 0, S128);
  make_map(enc, &M.hx, p_h, HP, SL, 24, 64, 0, S0);
  make_map(enc, &M.ha, p_h, HP, SL, 64, 128, 0, S128);
  make_map(enc, &M.hn, p_h, HP, SL, 32, 128, 0, S128);
  make_map(enc, &M.w2, P.w2, DM, FF, 64, 64, 2, S128);
  make_map(enc, &M.w2x, P.w2, DM, FF, 32, 64, 0, S128);
  make_map(enc, &M.kvs, p_kvT, SL, DM, 16, 64, 0, CU_TENSOR_MAP_SWIZZLE_32B);
  make_map(enc, &M.qf, P.q, DM, SL, 32, 64, 5, S64);
  make_map(enc, &M.y, p_yT, SL, DM, 64, 160, 0, S128);
  make_map(enc, &M.out, d_out, DM, SL, 32, 64, 0, S64);
  h3_kernel<<<NCTA, 384, SMEM_BYTES>>>(M, P);
}
```

```cpp
#include <cuda_runtime.h>
#include <cuda_bf16.h>
#include <cuda.h>
#include <stdint.h>

namespace h3 {

constexpr int SL = 2048, DM = 640, FF = 1728, HP = 1792;
constexpr int NCTA = 128;

__device__ __align__(1024) __nv_bfloat16 g_h[SL * HP];
__device__ __align__(1024) __nv_bfloat16 g_kvT[DM * SL];
__device__ __align__(1024) __nv_bfloat16 g_yT[DM * SL];
__device__ __align__(1024) uint2 g_stat[2 * SL];
__device__ __align__(1024) uint32_t g_cs[2 * 8 * 256];
__device__ __align__(1024) unsigned g_cnt[64 * 32];
__device__ __align__(1024) unsigned g_launch[NCTA * 8];
constexpr int CNT_Y = 0, CNT_H = 16;

constexpr int G1_STAGE = 49152, G1_TX = 16384 + 24576 + 3072;
constexpr int HST = 49152;
constexpr int P0 = 81920, P1 = 140288, P2 = 156672;
constexpr int XCH = 4368, XD = 272, X0 = 173056, X4 = 221184;
constexpr int KVS = 196608, KV_BUF = 8960;
constexpr int KT_CH = 8240, KT_O = 16, KT_E = 4144, KT0 = 98304;
constexpr int FIN_Q = X0, FIN_Y = 98304;
constexpr int MISC = 226816;
constexpr int M_BX = MISC;
constexpr int M_RED0 = M_BX + 2048, M_RED1 = M_BX;
constexpr int M_SK = KVS + 3 * KV_BUF;
constexpr int M_STAT = M_BX + 3584;
constexpr int M_B2 = M_STAT + 512;
constexpr int M_AUX = M_B2 + 320;
constexpr int M_ZERO = M_AUX + 96;
constexpr int M_BAR = M_ZERO + 16;
constexpr int M_TS = M_BAR + 80 * 8;
constexpr int SMEM_BYTES = M_TS + 256;
__host__ __device__ constexpr int cv_x(int c) { return c == 4 ? X4 : X0 + c * XCH; }
__host__ __device__ constexpr int cv_p(int c) { return c == 2 ? P2 : ((c == 0 || c == 3) ? P0 : P1); }
__host__ __device__ constexpr int cv_t(int c) { return KT0 + c * KT_CH; }
__host__ __device__ constexpr int g2_a(int s) { return s == 0 ? 0 : (s == 1 ? 40960 : (s == 2 ? 98304 : P2)); }
__host__ __device__ constexpr int g2_b(int s) { return s == 0 ? 16384 : (s == 1 ? 57344 : (s == 2 ? 114688 : KVS)); }
static_assert(M_SK + 2560 <= MISC && X4 + XCH <= MISC && KVS + 24576 <= X4 && X0 + 4 * XCH <= KVS && FIN_Q + 20480 <= KVS, "smem");
static_assert(KT0 + 5 * KT_CH <= P1 && P1 + 16384 <= P2 && P2 + 16384 <= X0 && SMEM_BYTES <= 232448 && MISC % 512 == 0 && M_BAR % 8 == 0, "smem");
constexpr int B_F1 = 0, B_E1 = 4, B_FR = 8, B_F2 = 12, B_E2 = 16, B_KRAW = 20, B_KT = 22, B_XF = 27, B_HB = 32, B_SD = 40, B_RF = 45,
              B_TD = 48, B_FINQ = 50, B_FINY = 51, B_RED = 52, B_BX = 53, B_KIN = 54, B_XR = 59, B_OUT = 61, B_SK = 66, B_YSLOT = 67, B_XD = 68, B_KIN1 = 70, B_XL = 75, B_KD = 60;
constexpr int NB_INIT = 1, NB_INIT2 = 2, NB_AUX = 3, NB_LEAD = 4, NB_GELU = 5, NB_TURN = 6  , NB_END = 8, NB_INIT3 = 9, NB_WG1 = 10;

#define KV_MAP 0x543
#define KV_LATE 1
#define PF_KV 0
#define PF_G1 0
#define WS_PROMO CU_TENSOR_MAP_L2_PROMOTION_L2_128B
#define RAW_LATE 0
#define PF_RAW 0
#define SIDE_LD 4
#define SIDE_USE 0x554
#define REL_K 0
#define CS_WAIT 1
#define GELU_NB 8
#define H_ORD 0x73625410
#define W2_PF 7
#define H_FLY 8
#define TB2 2
#define X_A 2
#define A_NB0 20
#define RED_GATE 0
#define SUM3 0
#define XP_KC 4
#define YP_N 4
#define HOLD_KC 11
#define END_KC 13
#define REG_AUX "56"
#define REG_CON "224"
#define LDQ ".nc.L1::no_allocate"
#define LDP ""

__device__ __forceinline__ uint32_t s32(const void* p) { return (uint32_t)__cvta_generic_to_shared(p); }
__device__ __forceinline__ uint32_t clk() { uint32_t t; asm volatile("mov.u32 %0, %%clock;" : "=r"(t)); return t; }
__device__ __forceinline__ bool elect_one() {
  uint32_t p; asm volatile("{\n.reg .pred P;\nelect.sync _|P, 0xffffffff;\nselp.u32 %0, 1, 0, P;\n}" : "=r"(p)); return p;
}
#define ONE(...) do { if (elect_one()) { __VA_ARGS__; } __syncwarp(); } while (0)
__device__ __forceinline__ void mbar_init(uint32_t a, int c) { asm volatile("mbarrier.init.shared::cta.b64 [%0], %1;" ::"r"(a), "r"(c) : "memory"); }
__device__ __forceinline__ void mbar_expect(uint32_t a, int b) { asm volatile("mbarrier.arrive.expect_tx.shared::cta.b64 _, [%0], %1;" ::"r"(a), "r"(b) : "memory"); }
__device__ __forceinline__ void mbar_arrive(uint32_t a) { asm volatile("mbarrier.arrive.shared::cta.b64 _, [%0];" ::"r"(a) : "memory"); }
__device__ __forceinline__ bool spin_guard(uint32_t& n, uint32_t) {
  return ++n > (1u << 20);
}
__device__ __forceinline__ void mbar_wait(uint32_t a, int ph) {
  asm volatile("{\n.reg .pred p;\n.reg .u32 n;\nmov.u32 n, 0;\nW:\n.pragma \"nounroll\";\nmbarrier.try_wait.parity.shared::cta.b64 p, [%0], %1;\n"
               "add.u32 n, n, 1;\nsetp.ge.or.u32 p, n, 0x100000, p;\n@!p bra W;\n}" ::"r"(a), "r"(ph) : "memory");
}
__device__ __forceinline__ bool mbar_test(uint32_t a, int ph) {
  uint32_t ok;
  asm volatile("{\n.reg .pred p;\nmbarrier.test_wait.parity.shared::cta.b64 p, [%1], %2;\nselp.u32 %0, 1, 0, p;\n}" : "=r"(ok) : "r"(a), "r"(ph) : "memory");
  return __all_sync(0xffffffffu, ok);
}
__device__ __forceinline__ void tma2d(uint32_t dst, const CUtensorMap* tm, int c0, int c1, uint32_t bar) {
  asm volatile("cp.async.bulk.tensor.2d.shared::cluster.global.mbarrier::complete_tx::bytes [%0], [%1, {%3, %4}], [%2];"
               ::"r"(dst), "l"(tm), "r"(bar), "r"(c0), "r"(c1) : "memory");
}
__device__ __forceinline__ void tma3d(uint32_t dst, const CUtensorMap* tm, int c0, int c1, int c2, uint32_t bar) {
  asm volatile("cp.async.bulk.tensor.3d.shared::cluster.global.mbarrier::complete_tx::bytes [%0], [%1, {%3, %4, %5}], [%2];"
               ::"r"(dst), "l"(tm), "r"(bar), "r"(c0), "r"(c1), "r"(c2) : "memory");
}
__device__ __forceinline__ void tma2d_st(const CUtensorMap* tm, int c0, int c1, uint32_t src) {
  asm volatile("cp.async.bulk.tensor.2d.global.shared::cta.bulk_group [%0, {%2, %3}], [%1];" ::"l"(tm), "r"(src), "r"(c0), "r"(c1) : "memory");
}
__device__ __forceinline__ void tma3d_st(const CUtensorMap* tm, int c0, int c1, int c2, uint32_t src) {
  asm volatile("cp.async.bulk.tensor.3d.global.shared::cta.bulk_group [%0, {%2, %3, %4}], [%1];" ::"l"(tm), "r"(src), "r"(c0), "r"(c1), "r"(c2) : "memory");
}
__device__ __forceinline__ void bulk_g2s(uint32_t dst, const void* src, int bytes, uint32_t bar) {
  asm volatile("cp.async.bulk.shared::cluster.global.mbarrier::complete_tx::bytes [%0], [%1], %2, [%3];" ::"r"(dst), "l"(src), "r"(bytes), "r"(bar) : "memory");
}
__device__ __forceinline__ void bulk_commit() { asm volatile("cp.async.bulk.commit_group;" ::: "memory"); }
__device__ __forceinline__ void bulk_wait_read() { asm volatile("cp.async.bulk.wait_group.read 0;" ::: "memory"); }
__device__ __forceinline__ void bulk_wait_all() { asm volatile("cp.async.bulk.wait_group 0;" ::: "memory"); }
__device__ __forceinline__ void fence_async_smem() { asm volatile("fence.proxy.async.shared::cta;" ::: "memory"); }
__device__ __forceinline__ void fence_async_all() { asm volatile("fence.proxy.async;" ::: "memory"); }
__device__ __forceinline__ void fence_gpu() { asm volatile("fence.acq_rel.gpu;" ::: "memory"); }
#define bar_sync(id, n) asm volatile("bar.sync %0, %1;" ::"n"(id), "n"(n) : "memory")
#define bar_arrive(id, n) asm volatile("bar.arrive %0, %1;" ::"n"(id), "n"(n) : "memory")
__device__ __forceinline__ void wg_fence() { asm volatile("wgmma.fence.sync.aligned;" ::: "memory"); }
__device__ __forceinline__ void wg_commit() { asm volatile("wgmma.commit_group.sync.aligned;" ::: "memory"); }
template <int N> __device__ __forceinline__ void wg_wait() { asm volatile("wgmma.wait_group.sync.aligned %0;" ::"n"(N) : "memory"); }
__device__ __forceinline__ uint64_t mkdesc(uint32_t addr, uint32_t lbo, uint32_t sbo, int sw) {
  return (uint64_t)((addr & 0x3FFFF) >> 4) | ((uint64_t)(lbo >> 4) << 16) | ((uint64_t)(sbo >> 4) << 32) | ((uint64_t)sw << 62);
}
__device__ __forceinline__ uint32_t ldg32(const void* p) { uint32_t v; asm volatile("ld.global" LDQ ".b32 %0, [%1];" : "=r"(v) : "l"(p)); return v; }
template <int OFF> __device__ __forceinline__ uint32_t ldg32o(const void* p) { uint32_t v; asm volatile("ld.global" LDQ ".b32 %0, [%1+%2];" : "=r"(v) : "l"(p), "n"(OFF)); return v; }
template <int I> __device__ __forceinline__ void kv_loads(const void* kp, const void* vp, uint32_t (&kk)[16], uint32_t (&o)[16]) {
  kk[I] = ldg32o<I * DM * 2>(kp); o[I] = ldg32o<I * DM * 2>(vp);
  if constexpr (I < 15) kv_loads<I + 1>(kp, vp, kk, o);
}
__device__ __forceinline__ uint4 ldg128(const void* p) {
  uint4 v; asm volatile("ld.global" LDQ LDP ".v4.b32 {%0,%1,%2,%3}, [%4];" : "=r"(v.x), "=r"(v.y), "=r"(v.z), "=r"(v.w) : "l"(p)); return v;
}
__device__ __forceinline__ void stg128(void* p, uint32_t x, uint32_t y, uint32_t z, uint32_t w) {
  asm volatile("st.global.v4.b32 [%0], {%1,%2,%3,%4};" ::"l"(p), "r"(x), "r"(y), "r"(z), "r"(w) : "memory");
}
__device__ __forceinline__ uint4 ld_relaxed128(const void* p) {
  uint4 v; asm volatile("ld.relaxed.gpu.global.v4.b32 {%0,%1,%2,%3}, [%4];" : "=r"(v.x), "=r"(v.y), "=r"(v.z), "=r"(v.w) : "l"(p) : "memory"); return v;
}
__device__ __forceinline__ uint2 ld_relaxed64(const void* p) {
  uint2 v; asm volatile("ld.relaxed.gpu.global.v2.b32 {%0,%1}, [%2];" : "=r"(v.x), "=r"(v.y) : "l"(p) : "memory"); return v;
}
__device__ __forceinline__ uint4 ld_relaxed_b128(const void* p) {
  uint4 v; asm volatile("{\n.reg .b128 t;\nld.relaxed.gpu.global.b128 t, [%4];\nmov.b128 {%0,%1,%2,%3}, t;\n}" : "=r"(v.x), "=r"(v.y), "=r"(v.z), "=r"(v.w) : "l"(p) : "memory"); return v;
}
__device__ __forceinline__ void st_relaxed_b128(void* p, uint32_t x, uint32_t y, uint32_t z, uint32_t w) {
  asm volatile("{\n.reg .b128 t;\nmov.b128 t, {%1,%2,%3,%4};\nst.relaxed.gpu.global.b128 [%0], t;\n}" ::"l"(p), "r"(x), "r"(y), "r"(z), "r"(w) : "memory");
}
__device__ __forceinline__ void st_relaxed64(void* p, uint32_t x, uint32_t y) {
  asm volatile("{\n.reg .b64 t;\nmov.b64 t, {%1,%2};\nst.relaxed.gpu.global.b64 [%0], t;\n}" ::"l"(p), "r"(x), "r"(y) : "memory");
}
__device__ __forceinline__ void st_relaxed32(void* p, uint32_t x) { asm volatile("st.relaxed.gpu.global.b32 [%0], %1;" ::"l"(p), "r"(x) : "memory"); }
__device__ __forceinline__ uint32_t ld_relaxed32(const void* p) { uint32_t v; asm volatile("ld.relaxed.gpu.global.b32 %0, [%1];" : "=r"(v) : "l"(p) : "memory"); return v; }
__device__ __forceinline__ void st_relaxed128(void* p, uint32_t x, uint32_t y, uint32_t z, uint32_t w) {
  asm volatile("{\n.reg .b64 t, u;\nmov.b64 t, {%1,%2};\nmov.b64 u, {%3,%4};\nst.relaxed.gpu.global.v2.b64 [%0], {t, u};\n}" ::"l"(p), "r"(x), "r"(y), "r"(z), "r"(w) : "memory");
}
__device__ __forceinline__ void fence_release() { asm volatile("fence.proxy.async.global;\nfence.release.gpu;" ::: "memory"); }
__device__ __forceinline__ void fence_acquire() { asm volatile("fence.acquire.gpu;\nfence.proxy.async.global;" ::: "memory"); }
__device__ __forceinline__ void signal_cnt(int idx) { asm volatile("red.relaxed.gpu.global.add.u32 [%0], 1;" ::"l"(&g_cnt[idx * 32]) : "memory"); }
__device__ __forceinline__ void wait_cnt(int idx, unsigned target) {
  uint32_t n = 0;
#pragma unroll 1
  while (!__all_sync(0xffffffffu, (int)(ld_relaxed32(&g_cnt[idx * 32]) - target) >= 0)) {
    if (spin_guard(n, 0x100 + idx)) break;
  }
  fence_acquire();
}
__device__ __forceinline__ void bulk_s2g(void* dst, uint32_t src, int bytes) {
  asm volatile("cp.async.bulk.global.shared::cta.bulk_group [%0], [%1], %2;" ::"l"(dst), "r"(src), "r"(bytes) : "memory");
}
__device__ __forceinline__ void bulk_add_s2g(void* dst, uint32_t src, int bytes) {
  asm volatile("cp.reduce.async.bulk.global.shared::cta.bulk_group.add.noftz.bf16 [%0], [%1], %2;" ::"l"(dst), "r"(src), "r"(bytes) : "memory");
}
__device__ __forceinline__ void prefetch_l2(const void* p, int bytes) { asm volatile("cp.async.bulk.prefetch.L2.global [%0], %1;" ::"l"(p), "r"(bytes) : "memory"); }
__device__ __forceinline__ void prefetch_tile(const CUtensorMap* tm, int c0, int c1) {
  asm volatile("cp.async.bulk.prefetch.tensor.2d.L2.global.tile [%0, {%1, %2}];" ::"l"(tm), "r"(c0), "r"(c1) : "memory");
}
__device__ __forceinline__ void prefetch_map(const CUtensorMap* tm) { asm volatile("prefetch.tensormap [%0];" ::"l"(tm) : "memory"); }
__device__ __forceinline__ uint32_t pack_bf16(float lo, float hi) {
  uint32_t r; asm("cvt.rn.bf16x2.f32 %0, %1, %2;" : "=r"(r) : "f"(hi), "f"(lo)); return r;
}
__device__ __forceinline__ float bf_lo(uint32_t v) { return __uint_as_float(v << 16); }
__device__ __forceinline__ float bf_hi(uint32_t v) { return __uint_as_float(v & 0xFFFF0000u); }
__device__ __forceinline__ float bf_round(float x) { return __bfloat162float(__float2bfloat16_rn(x)); }
__device__ __forceinline__ uint32_t bmul2(uint32_t a, uint32_t b) { uint32_t r; asm("mul.rn.bf16x2 %0, %1, %2;" : "=r"(r) : "r"(a), "r"(b)); return r; }
__device__ __forceinline__ uint32_t bfma2(uint32_t a, uint32_t b, uint32_t c) { uint32_t r; asm("fma.rn.bf16x2 %0, %1, %2, %3;" : "=r"(r) : "r"(a), "r"(b), "r"(c)); return r; }
__device__ __forceinline__ uint32_t badd2(uint32_t a, uint32_t b) { uint32_t r; asm("add.rn.bf16x2 %0, %1, %2;" : "=r"(r) : "r"(a), "r"(b)); return r; }
__device__ __forceinline__ uint32_t bsub2(uint32_t a, uint32_t b) { uint32_t r; asm("sub.rn.bf16x2 %0, %1, %2;" : "=r"(r) : "r"(a), "r"(b)); return r; }
__device__ __forceinline__ float tanh_fast(float x) { float r; asm("tanh.approx.f32 %0, %1;" : "=f"(r) : "f"(x)); return r; }
__device__ __forceinline__ float rcp_fast(float x) { float r; asm("rcp.approx.ftz.f32 %0, %1;" : "=f"(r) : "f"(x)); return r; }
__device__ __forceinline__ float sqrt_fast(float x) { float r; asm("sqrt.approx.ftz.f32 %0, %1;" : "=f"(r) : "f"(x)); return r; }
__device__ __forceinline__ uint32_t lds32(uint32_t a) { uint32_t v; asm volatile("ld.shared.b32 %0, [%1];" : "=r"(v) : "r"(a)); return v; }
__device__ __forceinline__ uint4 lds128(uint32_t a) { uint4 v; asm volatile("ld.shared.v4.b32 {%0,%1,%2,%3}, [%4];" : "=r"(v.x), "=r"(v.y), "=r"(v.z), "=r"(v.w) : "r"(a)); return v; }
__device__ __forceinline__ float2 lds64f(uint32_t a) { float2 v; asm volatile("ld.shared.v2.f32 {%0,%1}, [%2];" : "=f"(v.x), "=f"(v.y) : "r"(a)); return v; }
__device__ __forceinline__ void sts64f(uint32_t a, float x, float y) { asm volatile("st.shared.v2.f32 [%0], {%1,%2};" ::"r"(a), "f"(x), "f"(y) : "memory"); }
__device__ __forceinline__ void sts32(uint32_t a, uint32_t x) { asm volatile("st.shared.b32 [%0], %1;" ::"r"(a), "r"(x) : "memory"); }
__device__ __forceinline__ void sts128(uint32_t a, uint32_t x, uint32_t y, uint32_t z, uint32_t w) { asm volatile("st.shared.v4.b32 [%0], {%1,%2,%3,%4};" ::"r"(a), "r"(x), "r"(y), "r"(z), "r"(w) : "memory"); }
__device__ __forceinline__ void stsm4(uint32_t a, uint32_t r0, uint32_t r1, uint32_t r2, uint32_t r3) {
  asm volatile("stmatrix.sync.aligned.m8n8.x4.shared.b16 [%0], {%1,%2,%3,%4};" ::"r"(a), "r"(r0), "r"(r1), "r"(r2), "r"(r3) : "memory");
}
__device__ __forceinline__ void stsm4t(uint32_t a, uint32_t r0, uint32_t r1, uint32_t r2, uint32_t r3) {
  asm volatile("stmatrix.sync.aligned.m8n8.x4.trans.shared.b16 [%0], {%1,%2,%3,%4};" ::"r"(a), "r"(r0), "r"(r1), "r"(r2), "r"(r3) : "memory");
}
__device__ __forceinline__ void stsm2(uint32_t a, uint32_t r0, uint32_t r1) {
  asm volatile("stmatrix.sync.aligned.m8n8.x2.shared.b16 [%0], {%1,%2};" ::"r"(a), "r"(r0), "r"(r1) : "memory");
}
__device__ __forceinline__ void ldsm4(uint32_t a, uint32_t& r0, uint32_t& r1, uint32_t& r2, uint32_t& r3) {
  asm volatile("ldmatrix.sync.aligned.m8n8.x4.shared.b16 {%0,%1,%2,%3}, [%4];" : "=r"(r0), "=r"(r1), "=r"(r2), "=r"(r3) : "r"(a) : "memory");
}
__device__ __forceinline__ void ldsm4t(uint32_t a, uint32_t& r0, uint32_t& r1, uint32_t& r2, uint32_t& r3) {
  asm volatile("ldmatrix.sync.aligned.m8n8.x4.trans.shared.b16 {%0,%1,%2,%3}, [%4];" : "=r"(r0), "=r"(r1), "=r"(r2), "=r"(r3) : "r"(a) : "memory");
}
__device__ __forceinline__ uint32_t mapa(uint32_t a, uint32_t rank) { uint32_t r; asm("mapa.shared::cluster.u32 %0, %1, %2;" : "=r"(r) : "r"(a), "r"(rank)); return r; }
__device__ __forceinline__ void mbar_arrive_remote(uint32_t a) { asm volatile("mbarrier.arrive.relaxed.cluster.shared::cluster.b64 _, [%0];" ::"r"(a) : "memory"); }
__device__ __forceinline__ void st_async128(uint32_t a, uint32_t x, uint32_t y, uint32_t z, uint32_t w, uint32_t bar) {
  asm volatile("st.async.weak.shared::cluster.mbarrier::complete_tx::bytes.v4.b32 [%0], {%1,%2,%3,%4}, [%5];" ::"r"(a), "r"(x), "r"(y), "r"(z), "r"(w), "r"(bar) : "memory");
}
#define TS(i)

#define TSKV
__device__ __forceinline__ void wg_ss_216(float (&d)[108], uint64_t da, uint64_t db, int sd) {
  asm volatile("{\n.reg .pred p;\nsetp.ne.b32 p, %110, 0;\n"
    "wgmma.mma_async.sync.aligned.m64n216k16.f32.bf16.bf16 {%0,%1,%2,%3,%4,%5,%6,%7,%8,%9,%10,%11,%12,%13,%14,%15,%16,%17,%18,%19,%20,%21,%22,%23,%24,%25,%26,%27,%28,%29,%30,%31,%32,%33,%34,%35,%36,%37,%38,%39,%40,%41,%42,%43,%44,%45,%46,%47,%48,%49,%50,%51,%52,%53,%54,%55,%56,%57,%58,%59,%60,%61,%62,%63,%64,%65,%66,%67,%68,%69,%70,%71,%72,%73,%74,%75,%76,%77,%78,%79,%80,%81,%82,%83,%84,%85,%86,%87,%88,%89,%90,%91,%92,%93,%94,%95,%96,%97,%98,%99,%100,%101,%102,%103,%104,%105,%106,%107}, %108, %109, p, 1, 1, 0, 1;\n}\n"
    : "+f"(d[0]),"+f"(d[1]),"+f"(d[2]),"+f"(d[3]),"+f"(d[4]),"+f"(d[5]),"+f"(d[6]),"+f"(d[7]),"+f"(d[8]),"+f"(d[9]),"+f"(d[10]),"+f"(d[11]),"+f"(d[12]),"+f"(d[13]),"+f"(d[14]),"+f"(d[15]),"+f"(d[16]),"+f"(d[17]),"+f"(d[18]),"+f"(d[19]),"+f"(d[20]),"+f"(d[21]),"+f"(d[22]),"+f"(d[23]),"+f"(d[24]),"+f"(d[25]),"+f"(d[26]),"+f"(d[27]),"+f"(d[28]),"+f"(d[29]),"+f"(d[30]),"+f"(d[31]),"+f"(d[32]),"+f"(d[33]),"+f"(d[34]),"+f"(d[35]),"+f"(d[36]),"+f"(d[37]),"+f"(d[38]),"+f"(d[39]),"+f"(d[40]),"+f"(d[41]),"+f"(d[42]),"+f"(d[43]),"+f"(d[44]),"+f"(d[45]),"+f"(d[46]),"+f"(d[47]),"+f"(d[48]),"+f"(d[49]),"+f"(d[50]),"+f"(d[51]),"+f"(d[52]),"+f"(d[53]),"+f"(d[54]),"+f"(d[55]),"+f"(d[56]),"+f"(d[57]),"+f"(d[58]),"+f"(d[59]),"+f"(d[60]),"+f"(d[61]),"+f"(d[62]),"+f"(d[63]),"+f"(d[64]),"+f"(d[65]),"+f"(d[66]),"+f"(d[67]),"+f"(d[68]),"+f"(d[69]),"+f"(d[70]),"+f"(d[71]),"+f"(d[72]),"+f"(d[73]),"+f"(d[74]),"+f"(d[75]),"+f"(d[76]),"+f"(d[77]),"+f"(d[78]),"+f"(d[79]),"+f"(d[80]),"+f"(d[81]),"+f"(d[82]),"+f"(d[83]),"+f"(d[84]),"+f"(d[85]),"+f"(d[86]),"+f"(d[87]),"+f"(d[88]),"+f"(d[89]),"+f"(d[90]),"+f"(d[91]),"+f"(d[92]),"+f"(d[93]),"+f"(d[94]),"+f"(d[95]),"+f"(d[96]),"+f"(d[97]),"+f"(d[98]),"+f"(d[99]),"+f"(d[100]),"+f"(d[101]),"+f"(d[102]),"+f"(d[103]),"+f"(d[104]),"+f"(d[105]),"+f"(d[106]),"+f"(d[107]) : "l"(da), "l"(db), "r"(sd));
}
__device__ __forceinline__ void wg_ss_160(float (&d)[80], uint64_t da, uint64_t db, int sd) {
  asm volatile("{\n.reg .pred p;\nsetp.ne.b32 p, %82, 0;\n"
    "wgmma.mma_async.sync.aligned.m64n160k16.f32.bf16.bf16 {%0,%1,%2,%3,%4,%5,%6,%7,%8,%9,%10,%11,%12,%13,%14,%15,%16,%17,%18,%19,%20,%21,%22,%23,%24,%25,%26,%27,%28,%29,%30,%31,%32,%33,%34,%35,%36,%37,%38,%39,%40,%41,%42,%43,%44,%45,%46,%47,%48,%49,%50,%51,%52,%53,%54,%55,%56,%57,%58,%59,%60,%61,%62,%63,%64,%65,%66,%67,%68,%69,%70,%71,%72,%73,%74,%75,%76,%77,%78,%79}, %80, %81, p, 1, 1, 0, 1;\n}\n"
    : "+f"(d[0]),"+f"(d[1]),"+f"(d[2]),"+f"(d[3]),"+f"(d[4]),"+f"(d[5]),"+f"(d[6]),"+f"(d[7]),"+f"(d[8]),"+f"(d[9]),"+f"(d[10]),"+f"(d[11]),"+f"(d[12]),"+f"(d[13]),"+f"(d[14]),"+f"(d[15]),"+f"(d[16]),"+f"(d[17]),"+f"(d[18]),"+f"(d[19]),"+f"(d[20]),"+f"(d[21]),"+f"(d[22]),"+f"(d[23]),"+f"(d[24]),"+f"(d[25]),"+f"(d[26]),"+f"(d[27]),"+f"(d[28]),"+f"(d[29]),"+f"(d[30]),"+f"(d[31]),"+f"(d[32]),"+f"(d[33]),"+f"(d[34]),"+f"(d[35]),"+f"(d[36]),"+f"(d[37]),"+f"(d[38]),"+f"(d[39]),"+f"(d[40]),"+f"(d[41]),"+f"(d[42]),"+f"(d[43]),"+f"(d[44]),"+f"(d[45]),"+f"(d[46]),"+f"(d[47]),"+f"(d[48]),"+f"(d[49]),"+f"(d[50]),"+f"(d[51]),"+f"(d[52]),"+f"(d[53]),"+f"(d[54]),"+f"(d[55]),"+f"(d[56]),"+f"(d[57]),"+f"(d[58]),"+f"(d[59]),"+f"(d[60]),"+f"(d[61]),"+f"(d[62]),"+f"(d[63]),"+f"(d[64]),"+f"(d[65]),"+f"(d[66]),"+f"(d[67]),"+f"(d[68]),"+f"(d[69]),"+f"(d[70]),"+f"(d[71]),"+f"(d[72]),"+f"(d[73]),"+f"(d[74]),"+f"(d[75]),"+f"(d[76]),"+f"(d[77]),"+f"(d[78]),"+f"(d[79]) : "l"(da), "l"(db), "r"(sd));
}
__device__ __forceinline__ void wg_rs_216(float (&d)[108], uint32_t a0, uint32_t a1, uint32_t a2, uint32_t a3, uint64_t db) {
  asm volatile("{\n.reg .pred p;\nsetp.ne.b32 p, 1, 0;\n"
    "wgmma.mma_async.sync.aligned.m64n216k16.f32.bf16.bf16 {%0,%1,%2,%3,%4,%5,%6,%7,%8,%9,%10,%11,%12,%13,%14,%15,%16,%17,%18,%19,%20,%21,%22,%23,%24,%25,%26,%27,%28,%29,%30,%31,%32,%33,%34,%35,%36,%37,%38,%39,%40,%41,%42,%43,%44,%45,%46,%47,%48,%49,%50,%51,%52,%53,%54,%55,%56,%57,%58,%59,%60,%61,%62,%63,%64,%65,%66,%67,%68,%69,%70,%71,%72,%73,%74,%75,%76,%77,%78,%79,%80,%81,%82,%83,%84,%85,%86,%87,%88,%89,%90,%91,%92,%93,%94,%95,%96,%97,%98,%99,%100,%101,%102,%103,%104,%105,%106,%107}, {%108,%109,%110,%111}, %112, p, 1, 1, 1;\n}\n"
    : "+f"(d[0]),"+f"(d[1]),"+f"(d[2]),"+f"(d[3]),"+f"(d[4]),"+f"(d[5]),"+f"(d[6]),"+f"(d[7]),"+f"(d[8]),"+f"(d[9]),"+f"(d[10]),"+f"(d[11]),"+f"(d[12]),"+f"(d[13]),"+f"(d[14]),"+f"(d[15]),"+f"(d[16]),"+f"(d[17]),"+f"(d[18]),"+f"(d[19]),"+f"(d[20]),"+f"(d[21]),"+f"(d[22]),"+f"(d[23]),"+f"(d[24]),"+f"(d[25]),"+f"(d[26]),"+f"(d[27]),"+f"(d[28]),"+f"(d[29]),"+f"(d[30]),"+f"(d[31]),"+f"(d[32]),"+f"(d[33]),"+f"(d[34]),"+f"(d[35]),"+f"(d[36]),"+f"(d[37]),"+f"(d[38]),"+f"(d[39]),"+f"(d[40]),"+f"(d[41]),"+f"(d[42]),"+f"(d[43]),"+f"(d[44]),"+f"(d[45]),"+f"(d[46]),"+f"(d[47]),"+f"(d[48]),"+f"(d[49]),"+f"(d[50]),"+f"(d[51]),"+f"(d[52]),"+f"(d[53]),"+f"(d[54]),"+f"(d[55]),"+f"(d[56]),"+f"(d[57]),"+f"(d[58]),"+f"(d[59]),"+f"(d[60]),"+f"(d[61]),"+f"(d[62]),"+f"(d[63]),"+f"(d[64]),"+f"(d[65]),"+f"(d[66]),"+f"(d[67]),"+f"(d[68]),"+f"(d[69]),"+f"(d[70]),"+f"(d[71]),"+f"(d[72]),"+f"(d[73]),"+f"(d[74]),"+f"(d[75]),"+f"(d[76]),"+f"(d[77]),"+f"(d[78]),"+f"(d[79]),"+f"(d[80]),"+f"(d[81]),"+f"(d[82]),"+f"(d[83]),"+f"(d[84]),"+f"(d[85]),"+f"(d[86]),"+f"(d[87]),"+f"(d[88]),"+f"(d[89]),"+f"(d[90]),"+f"(d[91]),"+f"(d[92]),"+f"(d[93]),"+f"(d[94]),"+f"(d[95]),"+f"(d[96]),"+f"(d[97]),"+f"(d[98]),"+f"(d[99]),"+f"(d[100]),"+f"(d[101]),"+f"(d[102]),"+f"(d[103]),"+f"(d[104]),"+f"(d[105]),"+f"(d[106]),"+f"(d[107]) : "r"(a0), "r"(a1), "r"(a2), "r"(a3), "l"(db));
}
__device__ __forceinline__ void wg_cv_0_0(float (&d)[128], uint32_t a0, uint32_t a1, uint32_t a2, uint32_t a3, uint64_t db) {
  asm volatile("{\n.reg .pred p;\nsetp.ne.b32 p, 0, 0;\n"
    "wgmma.mma_async.sync.aligned.m64n32k16.f32.bf16.bf16 {%0,%1,%2,%3,%4,%5,%6,%7,%8,%9,%10,%11,%12,%13,%14,%15}, {%16,%17,%18,%19}, %20, p, 1, 1, 0;\n}\n"
    : "+f"(d[0]),"+f"(d[1]),"+f"(d[2]),"+f"(d[3]),"+f"(d[4]),"+f"(d[5]),"+f"(d[6]),"+f"(d[7]),"+f"(d[8]),"+f"(d[9]),"+f"(d[10]),"+f"(d[11]),"+f"(d[12]),"+f"(d[13]),"+f"(d[14]),"+f"(d[15]) : "r"(a0), "r"(a1), "r"(a2), "r"(a3), "l"(db));
}
__device__ __forceinline__ void wg_cv_0_1(float (&d)[128], uint32_t a0, uint32_t a1, uint32_t a2, uint32_t a3, uint64_t db) {
  asm volatile("{\n.reg .pred p;\nsetp.ne.b32 p, 1, 0;\n"
    "wgmma.mma_async.sync.aligned.m64n32k16.f32.bf16.bf16 {%0,%1,%2,%3,%4,%5,%6,%7,%8,%9,%10,%11,%12,%13,%14,%15}, {%16,%17,%18,%19}, %20, p, 1, 1, 0;\n}\n"
    : "+f"(d[0]),"+f"(d[1]),"+f"(d[2]),"+f"(d[3]),"+f"(d[4]),"+f"(d[5]),"+f"(d[6]),"+f"(d[7]),"+f"(d[8]),"+f"(d[9]),"+f"(d[10]),"+f"(d[11]),"+f"(d[12]),"+f"(d[13]),"+f"(d[14]),"+f"(d[15]) : "r"(a0), "r"(a1), "r"(a2), "r"(a3), "l"(db));
}
__device__ __forceinline__ void wg_cv_1_0(float (&d)[128], uint32_t a0, uint32_t a1, uint32_t a2, uint32_t a3, uint64_t db) {
  asm volatile("{\n.reg .pred p;\nsetp.ne.b32 p, 0, 0;\n"
    "wgmma.mma_async.sync.aligned.m64n32k16.f32.bf16.bf16 {%0,%1,%2,%3,%4,%5,%6,%7,%8,%9,%10,%11,%12,%13,%14,%15}, {%16,%17,%18,%19}, %20, p, 1, 1, 0;\n}\n"
    : "+f"(d[16]),"+f"(d[17]),"+f"(d[18]),"+f"(d[19]),"+f"(d[20]),"+f"(d[21]),"+f"(d[22]),"+f"(d[23]),"+f"(d[24]),"+f"(d[25]),"+f"(d[26]),"+f"(d[27]),"+f"(d[28]),"+f"(d[29]),"+f"(d[30]),"+f"(d[31]) : "r"(a0), "r"(a1), "r"(a2), "r"(a3), "l"(db));
}
__device__ __forceinline__ void wg_cv_1_1(float (&d)[128], uint32_t a0, uint32_t a1, uint32_t a2, uint32_t a3, uint64_t db) {
  asm volatile("{\n.reg .pred p;\nsetp.ne.b32 p, 1, 0;\n"
    "wgmma.mma_async.sync.aligned.m64n32k16.f32.bf16.bf16 {%0,%1,%2,%3,%4,%5,%6,%7,%8,%9,%10,%11,%12,%13,%14,%15}, {%16,%17,%18,%19}, %20, p, 1, 1, 0;\n}\n"
    : "+f"(d[16]),"+f"(d[17]),"+f"(d[18]),"+f"(d[19]),"+f"(d[20]),"+f"(d[21]),"+f"(d[22]),"+f"(d[23]),"+f"(d[24]),"+f"(d[25]),"+f"(d[26]),"+f"(d[27]),"+f"(d[28]),"+f"(d[29]),"+f"(d[30]),"+f"(d[31]) : "r"(a0), "r"(a1), "r"(a2), "r"(a3), "l"(db));
}
__device__ __forceinline__ void wg_cv_2_0(float (&d)[128], uint32_t a0, uint32_t a1, uint32_t a2, uint32_t a3, uint64_t db) {
  asm volatile("{\n.reg .pred p;\nsetp.ne.b32 p, 0, 0;\n"
    "wgmma.mma_async.sync.aligned.m64n32k16.f32.bf16.bf16 {%0,%1,%2,%3,%4,%5,%6,%7,%8,%9,%10,%11,%12,%13,%14,%15}, {%16,%17,%18,%19}, %20, p, 1, 1, 0;\n}\n"
    : "+f"(d[32]),"+f"(d[33]),"+f"(d[34]),"+f"(d[35]),"+f"(d[36]),"+f"(d[37]),"+f"(d[38]),"+f"(d[39]),"+f"(d[40]),"+f"(d[41]),"+f"(d[42]),"+f"(d[43]),"+f"(d[44]),"+f"(d[45]),"+f"(d[46]),"+f"(d[47]) : "r"(a0), "r"(a1), "r"(a2), "r"(a3), "l"(db));
}
__device__ __forceinline__ void wg_cv_2_1(float (&d)[128], uint32_t a0, uint32_t a1, uint32_t a2, uint32_t a3, uint64_t db) {
  asm volatile("{\n.reg .pred p;\nsetp.ne.b32 p, 1, 0;\n"
    "wgmma.mma_async.sync.aligned.m64n32k16.f32.bf16.bf16 {%0,%1,%2,%3,%4,%5,%6,%7,%8,%9,%10,%11,%12,%13,%14,%15}, {%16,%17,%18,%19}, %20, p, 1, 1, 0;\n}\n"
    : "+f"(d[32]),"+f"(d[33]),"+f"(d[34]),"+f"(d[35]),"+f"(d[36]),"+f"(d[37]),"+f"(d[38]),"+f"(d[39]),"+f"(d[40]),"+f"(d[41]),"+f"(d[42]),"+f"(d[43]),"+f"(d[44]),"+f"(d[45]),"+f"(d[46]),"+f"(d[47]) : "r"(a0), "r"(a1), "r"(a2), "r"(a3), "l"(db));
}
__device__ __forceinline__ void wg_cv_3_0(float (&d)[128], uint32_t a0, uint32_t a1, uint32_t a2, uint32_t a3, uint64_t db) {
  asm volatile("{\n.reg .pred p;\nsetp.ne.b32 p, 0, 0;\n"
    "wgmma.mma_async.sync.aligned.m64n32k16.f32.bf16.bf16 {%0,%1,%2,%3,%4,%5,%6,%7,%8,%9,%10,%11,%12,%13,%14,%15}, {%16,%17,%18,%19}, %20, p, 1, 1, 0;\n}\n"
    : "+f"(d[48]),"+f"(d[49]),"+f"(d[50]),"+f"(d[51]),"+f"(d[52]),"+f"(d[53]),"+f"(d[54]),"+f"(d[55]),"+f"(d[56]),"+f"(d[57]),"+f"(d[58]),"+f"(d[59]),"+f"(d[60]),"+f"(d[61]),"+f"(d[62]),"+f"(d[63]) : "r"(a0), "r"(a1), "r"(a2), "r"(a3), "l"(db));
}
__device__ __forceinline__ void wg_cv_3_1(float (&d)[128], uint32_t a0, uint32_t a1, uint32_t a2, uint32_t a3, uint64_t db) {
  asm volatile("{\n.reg .pred p;\nsetp.ne.b32 p, 1, 0;\n"
    "wgmma.mma_async.sync.aligned.m64n32k16.f32.bf16.bf16 {%0,%1,%2,%3,%4,%5,%6,%7,%8,%9,%10,%11,%12,%13,%14,%15}, {%16,%17,%18,%19}, %20, p, 1, 1, 0;\n}\n"
    : "+f"(d[48]),"+f"(d[49]),"+f"(d[50]),"+f"(d[51]),"+f"(d[52]),"+f"(d[53]),"+f"(d[54]),"+f"(d[55]),"+f"(d[56]),"+f"(d[57]),"+f"(d[58]),"+f"(d[59]),"+f"(d[60]),"+f"(d[61]),"+f"(d[62]),"+f"(d[63]) : "r"(a0), "r"(a1), "r"(a2), "r"(a3), "l"(db));
}
__device__ __forceinline__ void wg_cv_4_0(float (&d)[128], uint32_t a0, uint32_t a1, uint32_t a2, uint32_t a3, uint64_t db) {
  asm volatile("{\n.reg .pred p;\nsetp.ne.b32 p, 0, 0;\n"
    "wgmma.mma_async.sync.aligned.m64n32k16.f32.bf16.bf16 {%0,%1,%2,%3,%4,%5,%6,%7,%8,%9,%10,%11,%12,%13,%14,%15}, {%16,%17,%18,%19}, %20, p, 1, 1, 0;\n}\n"
    : "+f"(d[64]),"+f"(d[65]),"+f"(d[66]),"+f"(d[67]),"+f"(d[68]),"+f"(d[69]),"+f"(d[70]),"+f"(d[71]),"+f"(d[72]),"+f"(d[73]),"+f"(d[74]),"+f"(d[75]),"+f"(d[76]),"+f"(d[77]),"+f"(d[78]),"+f"(d[79]) : "r"(a0), "r"(a1), "r"(a2), "r"(a3), "l"(db));
}
__device__ __forceinline__ void wg_cv_4_1(float (&d)[128], uint32_t a0, uint32_t a1, uint32_t a2, uint32_t a3, uint64_t db) {
  asm volatile("{\n.reg .pred p;\nsetp.ne.b32 p, 1, 0;\n"
    "wgmma.mma_async.sync.aligned.m64n32k16.f32.bf16.bf16 {%0,%1,%2,%3,%4,%5,%6,%7,%8,%9,%10,%11,%12,%13,%14,%15}, {%16,%17,%18,%19}, %20, p, 1, 1, 0;\n}\n"
    : "+f"(d[64]),"+f"(d[65]),"+f"(d[66]),"+f"(d[67]),"+f"(d[68]),"+f"(d[69]),"+f"(d[70]),"+f"(d[71]),"+f"(d[72]),"+f"(d[73]),"+f"(d[74]),"+f"(d[75]),"+f"(d[76]),"+f"(d[77]),"+f"(d[78]),"+f"(d[79]) : "r"(a0), "r"(a1), "r"(a2), "r"(a3), "l"(db));
}
__device__ __forceinline__ void wg_cv_5_0(float (&d)[128], uint32_t a0, uint32_t a1, uint32_t a2, uint32_t a3, uint64_t db) {
  asm volatile("{\n.reg .pred p;\nsetp.ne.b32 p, 0, 0;\n"
    "wgmma.mma_async.sync.aligned.m64n32k16.f32.bf16.bf16 {%0,%1,%2,%3,%4,%5,%6,%7,%8,%9,%10,%11,%12,%13,%14,%15}, {%16,%17,%18,%19}, %20, p, 1, 1, 0;\n}\n"
    : "+f"(d[80]),"+f"(d[81]),"+f"(d[82]),"+f"(d[83]),"+f"(d[84]),"+f"(d[85]),"+f"(d[86]),"+f"(d[87]),"+f"(d[88]),"+f"(d[89]),"+f"(d[90]),"+f"(d[91]),"+f"(d[92]),"+f"(d[93]),"+f"(d[94]),"+f"(d[95]) : "r"(a0), "r"(a1), "r"(a2), "r"(a3), "l"(db));
}
__device__ __forceinline__ void wg_cv_5_1(float (&d)[128], uint32_t a0, uint32_t a1, uint32_t a2, uint32_t a3, uint64_t db) {
  asm volatile("{\n.reg .pred p;\nsetp.ne.b32 p, 1, 0;\n"
    "wgmma.mma_async.sync.aligned.m64n32k16.f32.bf16.bf16 {%0,%1,%2,%3,%4,%5,%6,%7,%8,%9,%10,%11,%12,%13,%14,%15}, {%16,%17,%18,%19}, %20, p, 1, 1, 0;\n}\n"
    : "+f"(d[80]),"+f"(d[81]),"+f"(d[82]),"+f"(d[83]),"+f"(d[84]),"+f"(d[85]),"+f"(d[86]),"+f"(d[87]),"+f"(d[88]),"+f"(d[89]),"+f"(d[90]),"+f"(d[91]),"+f"(d[92]),"+f"(d[93]),"+f"(d[94]),"+f"(d[95]) : "r"(a0), "r"(a1), "r"(a2), "r"(a3), "l"(db));
}
__device__ __forceinline__ void wg_cv_6_0(float (&d)[128], uint32_t a0, uint32_t a1, uint32_t a2, uint32_t a3, uint64_t db) {
  asm volatile("{\n.reg .pred p;\nsetp.ne.b32 p, 0, 0;\n"
    "wgmma.mma_async.sync.aligned.m64n32k16.f32.bf16.bf16 {%0,%1,%2,%3,%4,%5,%6,%7,%8,%9,%10,%11,%12,%13,%14,%15}, {%16,%17,%18,%19}, %20, p, 1, 1, 0;\n}\n"
    : "+f"(d[96]),"+f"(d[97]),"+f"(d[98]),"+f"(d[99]),"+f"(d[100]),"+f"(d[101]),"+f"(d[102]),"+f"(d[103]),"+f"(d[104]),"+f"(d[105]),"+f"(d[106]),"+f"(d[107]),"+f"(d[108]),"+f"(d[109]),"+f"(d[110]),"+f"(d[111]) : "r"(a0), "r"(a1), "r"(a2), "r"(a3), "l"(db));
}
__device__ __forceinline__ void wg_cv_6_1(float (&d)[128], uint32_t a0, uint32_t a1, uint32_t a2, uint32_t a3, uint64_t db) {
  asm volatile("{\n.reg .pred p;\nsetp.ne.b32 p, 1, 0;\n"
    "wgmma.mma_async.sync.aligned.m64n32k16.f32.bf16.bf16 {%0,%1,%2,%3,%4,%5,%6,%7,%8,%9,%10,%11,%12,%13,%14,%15}, {%16,%17,%18,%19}, %20, p, 1, 1, 0;\n}\n"
    : "+f"(d[96]),"+f"(d[97]),"+f"(d[98]),"+f"(d[99]),"+f"(d[100]),"+f"(d[101]),"+f"(d[102]),"+f"(d[103]),"+f"(d[104]),"+f"(d[105]),"+f"(d[106]),"+f"(d[107]),"+f"(d[108]),"+f"(d[109]),"+f"(d[110]),"+f"(d[111]) : "r"(a0), "r"(a1), "r"(a2), "r"(a3), "l"(db));
}
__device__ __forceinline__ void wg_cv_7_0(float (&d)[128], uint32_t a0, uint32_t a1, uint32_t a2, uint32_t a3, uint64_t db) {
  asm volatile("{\n.reg .pred p;\nsetp.ne.b32 p, 0, 0;\n"
    "wgmma.mma_async.sync.aligned.m64n32k16.f32.bf16.bf16 {%0,%1,%2,%3,%4,%5,%6,%7,%8,%9,%10,%11,%12,%13,%14,%15}, {%16,%17,%18,%19}, %20, p, 1, 1, 0;\n}\n"
    : "+f"(d[112]),"+f"(d[113]),"+f"(d[114]),"+f"(d[115]),"+f"(d[116]),"+f"(d[117]),"+f"(d[118]),"+f"(d[119]),"+f"(d[120]),"+f"(d[121]),"+f"(d[122]),"+f"(d[123]),"+f"(d[124]),"+f"(d[125]),"+f"(d[126]),"+f"(d[127]) : "r"(a0), "r"(a1), "r"(a2), "r"(a3), "l"(db));
}
__device__ __forceinline__ void wg_cv_7_1(float (&d)[128], uint32_t a0, uint32_t a1, uint32_t a2, uint32_t a3, uint64_t db) {
  asm volatile("{\n.reg .pred p;\nsetp.ne.b32 p, 1, 0;\n"
    "wgmma.mma_async.sync.aligned.m64n32k16.f32.bf16.bf16 {%0,%1,%2,%3,%4,%5,%6,%7,%8,%9,%10,%11,%12,%13,%14,%15}, {%16,%17,%18,%19}, %20, p, 1, 1, 0;\n}\n"
    : "+f"(d[112]),"+f"(d[113]),"+f"(d[114]),"+f"(d[115]),"+f"(d[116]),"+f"(d[117]),"+f"(d[118]),"+f"(d[119]),"+f"(d[120]),"+f"(d[121]),"+f"(d[122]),"+f"(d[123]),"+f"(d[124]),"+f"(d[125]),"+f"(d[126]),"+f"(d[127]) : "r"(a0), "r"(a1), "r"(a2), "r"(a3), "l"(db));
}
template <class F> __device__ __forceinline__ void conv_chain_1(float (&d)[128], uint32_t (&a)[64], uint64_t db, uint32_t ab, F hand) {
  wg_cv_7_0(d, a[60], a[61], a[62], a[63], db + (uint64_t)(0));
  wg_cv_6_0(d, a[52], a[53], a[54], a[55], db + (uint64_t)(0));
  wg_cv_7_1(d, a[56], a[57], a[58], a[59], db + (uint64_t)(16));
  wg_cv_5_0(d, a[44], a[45], a[46], a[47], db + (uint64_t)(0));
  wg_cv_6_1(d, a[48], a[49], a[50], a[51], db + (uint64_t)(16));
  wg_cv_7_1(d, a[52], a[53], a[54], a[55], db + (uint64_t)(32));
  wg_cv_5_1(d, a[40], a[41], a[42], a[43], db + (uint64_t)(16));
  wg_cv_6_1(d, a[44], a[45], a[46], a[47], db + (uint64_t)(32));
  wg_cv_7_1(d, a[48], a[49], a[50], a[51], db + (uint64_t)(48));
  wg_cv_6_1(d, a[40], a[41], a[42], a[43], db + (uint64_t)(48));
  wg_cv_7_1(d, a[44], a[45], a[46], a[47], db + (uint64_t)(64));
  wg_cv_7_1(d, a[40], a[41], a[42], a[43], db + (uint64_t)(80));
  wg_commit();
  wg_cv_7_1(d, a[36], a[37], a[38], a[39], db + (uint64_t)(96));
  wg_cv_6_1(d, a[36], a[37], a[38], a[39], db + (uint64_t)(64));
  wg_cv_5_1(d, a[36], a[37], a[38], a[39], db + (uint64_t)(32));
  wg_cv_4_0(d, a[36], a[37], a[38], a[39], db + (uint64_t)(0));
  wg_commit(); wg_wait<1>();
  wg_cv_7_1(d, a[32], a[33], a[34], a[35], db + (uint64_t)(112));
  wg_cv_6_1(d, a[32], a[33], a[34], a[35], db + (uint64_t)(80));
  wg_cv_5_1(d, a[32], a[33], a[34], a[35], db + (uint64_t)(48));
  a[60] = lds32(ab + (3840));
  a[61] = lds32(ab + (3968));
  a[62] = lds32(ab + (3824));
  a[63] = lds32(ab + (3952));
  wg_cv_4_1(d, a[32], a[33], a[34], a[35], db + (uint64_t)(16));
  wg_cv_7_1(d, a[28], a[29], a[30], a[31], db + (uint64_t)(128));
  wg_cv_6_1(d, a[28], a[29], a[30], a[31], db + (uint64_t)(96));
  wg_cv_5_1(d, a[28], a[29], a[30], a[31], db + (uint64_t)(64));
  a[56] = lds32(ab + (3584));
  a[57] = lds32(ab + (3712));
  a[58] = lds32(ab + (3568));
  a[59] = lds32(ab + (3696));
  wg_cv_4_1(d, a[28], a[29], a[30], a[31], db + (uint64_t)(32));
  wg_cv_3_0(d, a[28], a[29], a[30], a[31], db + (uint64_t)(0));
  wg_cv_7_1(d, a[24], a[25], a[26], a[27], db + (uint64_t)(144));
  wg_cv_6_1(d, a[24], a[25], a[26], a[27], db + (uint64_t)(112));
  a[52] = lds32(ab + (3328));
  a[53] = lds32(ab + (3456));
  a[54] = lds32(ab + (3312));
  a[55] = lds32(ab + (3440));
  wg_cv_5_1(d, a[24], a[25], a[26], a[27], db + (uint64_t)(80));
  wg_cv_4_1(d, a[24], a[25], a[26], a[27], db + (uint64_t)(48));
  wg_cv_3_1(d, a[24], a[25], a[26], a[27], db + (uint64_t)(16));
  wg_commit();
  wg_cv_7_1(d, a[20], a[21], a[22], a[23], db + (uint64_t)(160));
  wg_cv_6_1(d, a[20], a[21], a[22], a[23], db + (uint64_t)(128));
  wg_cv_5_1(d, a[20], a[21], a[22], a[23], db + (uint64_t)(96));
  wg_cv_4_1(d, a[20], a[21], a[22], a[23], db + (uint64_t)(64));
  wg_commit(); wg_wait<1>();
  a[48] = lds32(ab + (3072));
  a[49] = lds32(ab + (3200));
  a[50] = lds32(ab + (3056));
  a[51] = lds32(ab + (3184));
  wg_cv_3_1(d, a[20], a[21], a[22], a[23], db + (uint64_t)(32));
  wg_cv_2_0(d, a[20], a[21], a[22], a[23], db + (uint64_t)(0));
  wg_cv_7_1(d, a[16], a[17], a[18], a[19], db + (uint64_t)(176));
  wg_cv_6_1(d, a[16], a[17], a[18], a[19], db + (uint64_t)(144));
  a[44] = lds32(ab + (2816));
  a[45] = lds32(ab + (2944));
  a[46] = lds32(ab + (2800));
  a[47] = lds32(ab + (2928));
  wg_cv_5_1(d, a[16], a[17], a[18], a[19], db + (uint64_t)(112));
  wg_cv_4_1(d, a[16], a[17], a[18], a[19], db + (uint64_t)(80));
  wg_cv_3_1(d, a[16], a[17], a[18], a[19], db + (uint64_t)(48));
  wg_cv_2_1(d, a[16], a[17], a[18], a[19], db + (uint64_t)(16));
  a[40] = lds32(ab + (2560));
  a[41] = lds32(ab + (2688));
  a[42] = lds32(ab + (2544));
  a[43] = lds32(ab + (2672));
  wg_cv_7_1(d, a[12], a[13], a[14], a[15], db + (uint64_t)(192));
  wg_cv_6_1(d, a[12], a[13], a[14], a[15], db + (uint64_t)(160));
  wg_cv_5_1(d, a[12], a[13], a[14], a[15], db + (uint64_t)(128));
  wg_cv_4_1(d, a[12], a[13], a[14], a[15], db + (uint64_t)(96));
  a[36] = lds32(ab + (2304));
  a[37] = lds32(ab + (2432));
  a[38] = lds32(ab + (2288));
  a[39] = lds32(ab + (2416));
  wg_cv_3_1(d, a[12], a[13], a[14], a[15], db + (uint64_t)(64));
  wg_cv_2_1(d, a[12], a[13], a[14], a[15], db + (uint64_t)(32));
  wg_cv_1_0(d, a[12], a[13], a[14], a[15], db + (uint64_t)(0));
  wg_cv_7_1(d, a[8], a[9], a[10], a[11], db + (uint64_t)(208));
  a[32] = lds32(ab + (2048));
  a[33] = lds32(ab + (2176));
  a[34] = lds32(ab + (2032));
  a[35] = lds32(ab + (2160));
  wg_cv_6_1(d, a[8], a[9], a[10], a[11], db + (uint64_t)(176));
  wg_cv_5_1(d, a[8], a[9], a[10], a[11], db + (uint64_t)(144));
  wg_cv_4_1(d, a[8], a[9], a[10], a[11], db + (uint64_t)(112));
  wg_cv_3_1(d, a[8], a[9], a[10], a[11], db + (uint64_t)(80));
  a[28] = lds32(ab + (1792));
  a[29] = lds32(ab + (1920));
  a[30] = lds32(ab + (1776));
  a[31] = lds32(ab + (1904));
  wg_cv_2_1(d, a[8], a[9], a[10], a[11], db + (uint64_t)(48));
  wg_cv_1_1(d, a[8], a[9], a[10], a[11], db + (uint64_t)(16));
  wg_commit();
  wg_cv_7_1(d, a[4], a[5], a[6], a[7], db + (uint64_t)(224));
  wg_cv_6_1(d, a[4], a[5], a[6], a[7], db + (uint64_t)(192));
  wg_cv_5_1(d, a[4], a[5], a[6], a[7], db + (uint64_t)(160));
  wg_cv_4_1(d, a[4], a[5], a[6], a[7], db + (uint64_t)(128));
  wg_commit(); wg_wait<1>();
  a[24] = lds32(ab + (1536));
  a[25] = lds32(ab + (1664));
  a[26] = lds32(ab + (1520));
  a[27] = lds32(ab + (1648));
  hand();
  wg_cv_3_1(d, a[4], a[5], a[6], a[7], db + (uint64_t)(96));
  wg_cv_2_1(d, a[4], a[5], a[6], a[7], db + (uint64_t)(64));
  wg_cv_1_1(d, a[4], a[5], a[6], a[7], db + (uint64_t)(32));
  wg_cv_0_0(d, a[4], a[5], a[6], a[7], db + (uint64_t)(0));
  a[20] = lds32(ab + (1280));
  a[21] = lds32(ab + (1408));
  a[22] = lds32(ab + (1264));
  a[23] = lds32(ab + (1392));
  wg_cv_7_1(d, a[0], a[1], a[2], a[3], db + (uint64_t)(240));
  wg_cv_6_1(d, a[0], a[1], a[2], a[3], db + (uint64_t)(208));
  wg_cv_5_1(d, a[0], a[1], a[2], a[3], db + (uint64_t)(176));
  wg_cv_4_1(d, a[0], a[1], a[2], a[3], db + (uint64_t)(144));
  a[16] = lds32(ab + (1024));
  a[17] = lds32(ab + (1152));
  a[18] = lds32(ab + (1008));
  a[19] = lds32(ab + (1136));
  wg_cv_3_1(d, a[0], a[1], a[2], a[3], db + (uint64_t)(112));
  wg_cv_2_1(d, a[0], a[1], a[2], a[3], db + (uint64_t)(80));
  wg_cv_1_1(d, a[0], a[1], a[2], a[3], db + (uint64_t)(48));
  wg_cv_0_1(d, a[0], a[1], a[2], a[3], db + (uint64_t)(16));
  wg_commit();
  a[12] = lds32(ab + (768));
  a[13] = lds32(ab + (896));
  a[14] = lds32(ab + (752));
  a[15] = lds32(ab + (880));
  a[8] = lds32(ab + (512));
  a[9] = lds32(ab + (640));
  a[10] = lds32(ab + (496));
  a[11] = lds32(ab + (624));
}
template <class F> __device__ __forceinline__ void conv_chain_0(float (&d)[128], uint32_t (&a)[64], uint64_t db, uint32_t ab, F hand) {
  wg_cv_7_0(d, a[60], a[61], a[62], a[63], db + (uint64_t)(0));
  wg_cv_6_0(d, a[52], a[53], a[54], a[55], db + (uint64_t)(0));
  wg_cv_7_1(d, a[56], a[57], a[58], a[59], db + (uint64_t)(16));
  wg_cv_5_0(d, a[44], a[45], a[46], a[47], db + (uint64_t)(0));
  wg_cv_6_1(d, a[48], a[49], a[50], a[51], db + (uint64_t)(16));
  wg_cv_7_1(d, a[52], a[53], a[54], a[55], db + (uint64_t)(32));
  wg_cv_5_1(d, a[40], a[41], a[42], a[43], db + (uint64_t)(16));
  wg_cv_6_1(d, a[44], a[45], a[46], a[47], db + (uint64_t)(32));
  wg_cv_7_1(d, a[48], a[49], a[50], a[51], db + (uint64_t)(48));
  wg_cv_6_1(d, a[40], a[41], a[42], a[43], db + (uint64_t)(48));
  wg_cv_7_1(d, a[44], a[45], a[46], a[47], db + (uint64_t)(64));
  wg_cv_7_1(d, a[40], a[41], a[42], a[43], db + (uint64_t)(80));
  wg_commit();
  wg_cv_7_1(d, a[36], a[37], a[38], a[39], db + (uint64_t)(96));
  wg_cv_6_1(d, a[36], a[37], a[38], a[39], db + (uint64_t)(64));
  wg_cv_5_1(d, a[36], a[37], a[38], a[39], db + (uint64_t)(32));
  wg_cv_4_0(d, a[36], a[37], a[38], a[39], db + (uint64_t)(0));
  wg_cv_7_1(d, a[32], a[33], a[34], a[35], db + (uint64_t)(112));
  wg_cv_6_1(d, a[32], a[33], a[34], a[35], db + (uint64_t)(80));
  wg_cv_5_1(d, a[32], a[33], a[34], a[35], db + (uint64_t)(48));
  wg_cv_4_1(d, a[32], a[33], a[34], a[35], db + (uint64_t)(16));
  wg_cv_7_1(d, a[28], a[29], a[30], a[31], db + (uint64_t)(128));
  wg_cv_6_1(d, a[28], a[29], a[30], a[31], db + (uint64_t)(96));
  wg_cv_5_1(d, a[28], a[29], a[30], a[31], db + (uint64_t)(64));
  wg_cv_4_1(d, a[28], a[29], a[30], a[31], db + (uint64_t)(32));
  wg_cv_3_0(d, a[28], a[29], a[30], a[31], db + (uint64_t)(0));
  wg_cv_7_1(d, a[24], a[25], a[26], a[27], db + (uint64_t)(144));
  wg_cv_6_1(d, a[24], a[25], a[26], a[27], db + (uint64_t)(112));
  wg_cv_5_1(d, a[24], a[25], a[26], a[27], db + (uint64_t)(80));
  wg_cv_4_1(d, a[24], a[25], a[26], a[27], db + (uint64_t)(48));
  wg_cv_3_1(d, a[24], a[25], a[26], a[27], db + (uint64_t)(16));
  wg_commit();
  wg_cv_7_1(d, a[20], a[21], a[22], a[23], db + (uint64_t)(160));
  wg_cv_6_1(d, a[20], a[21], a[22], a[23], db + (uint64_t)(128));
  wg_cv_5_1(d, a[20], a[21], a[22], a[23], db + (uint64_t)(96));
  wg_cv_4_1(d, a[20], a[21], a[22], a[23], db + (uint64_t)(64));
  wg_cv_3_1(d, a[20], a[21], a[22], a[23], db + (uint64_t)(32));
  wg_cv_2_0(d, a[20], a[21], a[22], a[23], db + (uint64_t)(0));
  wg_cv_7_1(d, a[16], a[17], a[18], a[19], db + (uint64_t)(176));
  wg_cv_6_1(d, a[16], a[17], a[18], a[19], db + (uint64_t)(144));
  wg_cv_5_1(d, a[16], a[17], a[18], a[19], db + (uint64_t)(112));
  wg_cv_4_1(d, a[16], a[17], a[18], a[19], db + (uint64_t)(80));
  wg_cv_3_1(d, a[16], a[17], a[18], a[19], db + (uint64_t)(48));
  wg_cv_2_1(d, a[16], a[17], a[18], a[19], db + (uint64_t)(16));
  wg_cv_7_1(d, a[12], a[13], a[14], a[15], db + (uint64_t)(192));
  wg_cv_6_1(d, a[12], a[13], a[14], a[15], db + (uint64_t)(160));
  wg_cv_5_1(d, a[12], a[13], a[14], a[15], db + (uint64_t)(128));
  wg_cv_4_1(d, a[12], a[13], a[14], a[15], db + (uint64_t)(96));
  wg_cv_3_1(d, a[12], a[13], a[14], a[15], db + (uint64_t)(64));
  wg_cv_2_1(d, a[12], a[13], a[14], a[15], db + (uint64_t)(32));
  wg_cv_1_0(d, a[12], a[13], a[14], a[15], db + (uint64_t)(0));
  wg_cv_7_1(d, a[8], a[9], a[10], a[11], db + (uint64_t)(208));
  wg_cv_6_1(d, a[8], a[9], a[10], a[11], db + (uint64_t)(176));
  wg_cv_5_1(d, a[8], a[9], a[10], a[11], db + (uint64_t)(144));
  wg_cv_4_1(d, a[8], a[9], a[10], a[11], db + (uint64_t)(112));
  wg_cv_3_1(d, a[8], a[9], a[10], a[11], db + (uint64_t)(80));
  wg_cv_2_1(d, a[8], a[9], a[10], a[11], db + (uint64_t)(48));
  wg_cv_1_1(d, a[8], a[9], a[10], a[11], db + (uint64_t)(16));
  wg_commit();
  wg_cv_7_1(d, a[4], a[5], a[6], a[7], db + (uint64_t)(224));
  wg_cv_6_1(d, a[4], a[5], a[6], a[7], db + (uint64_t)(192));
  wg_cv_5_1(d, a[4], a[5], a[6], a[7], db + (uint64_t)(160));
  wg_cv_4_1(d, a[4], a[5], a[6], a[7], db + (uint64_t)(128));
  hand();
  wg_cv_3_1(d, a[4], a[5], a[6], a[7], db + (uint64_t)(96));
  wg_cv_2_1(d, a[4], a[5], a[6], a[7], db + (uint64_t)(64));
  wg_cv_1_1(d, a[4], a[5], a[6], a[7], db + (uint64_t)(32));
  wg_cv_0_0(d, a[4], a[5], a[6], a[7], db + (uint64_t)(0));
  wg_cv_7_1(d, a[0], a[1], a[2], a[3], db + (uint64_t)(240));
  wg_cv_6_1(d, a[0], a[1], a[2], a[3], db + (uint64_t)(208));
  wg_cv_5_1(d, a[0], a[1], a[2], a[3], db + (uint64_t)(176));
  wg_cv_4_1(d, a[0], a[1], a[2], a[3], db + (uint64_t)(144));
  wg_cv_3_1(d, a[0], a[1], a[2], a[3], db + (uint64_t)(112));
  wg_cv_2_1(d, a[0], a[1], a[2], a[3], db + (uint64_t)(80));
  wg_cv_1_1(d, a[0], a[1], a[2], a[3], db + (uint64_t)(48));
  wg_cv_0_1(d, a[0], a[1], a[2], a[3], db + (uint64_t)(16));
  wg_commit();
}
constexpr int CV_RELOADED = 2;

struct Params {
  const __nv_bfloat16 *q, *k, *v, *shift_k, *ssm_k, *ssm_D, *w1, *b1, *w2, *b2;
  __nv_bfloat16* out;
};
struct Maps { CUtensorMap qa, w1, w1x, k, v, hs, hx, ha, hn, w2, w2x, kvs, qf, y, out; };

__global__ void __cluster_dims__(2, 1, 1) __launch_bounds__(384, 1) h3_kernel(const __grid_constant__ Maps M, const Params P) {
  extern __shared__ __align__(1024) uint8_t smem_raw[];
  constexpr uint32_t sc = 1024;
  const int tid = threadIdx.x, lane = tid & 31;
  const int warp = __shfl_sync(0xffffffffu, tid >> 5, 0);
  const uint32_t sb = __shfl_sync(0xffffffffu, s32(smem_raw), 0);
  const int b = blockIdx.x, pr = b >> 1;
  const int G = pr < 4 ? 0 : (pr < 36 ? (pr - 4) & 7 : 1 + (pr - 36) % 7), gi = pr < 4 ? 4 + pr : (pr < 36 ? (pr - 4) >> 3 : 4 + (pr - 36) / 7);
  const int kh = b & 1, nt = (G & 1) * 2 + (gi & 1), rb = (G >> 1) * 4 + (gi >> 1);
  const int dir = (G ^ (G >> 1)) & 1, ri = (gi & 1) * 2 + kh, ci = (G >> 2) * 4 + (gi >> 1);
  const int j = kh * 4 + nt;
  const uint32_t bar = sb + M_BAR;
  auto BAR = [&](int i) { return bar + 8 * i; };
  auto g1_load = [&](int kc) {
    const uint32_t st = sb + (kc & 3) * G1_STAGE, fb = BAR(B_F1 + (kc & 3));
    const int k0 = dir ? 576 - kc * 64 : kc * 64;
    mbar_expect(fb, G1_TX);
    tma2d(st, &M.qa, k0, rb * 128, fb);
    tma3d(st + 16384, &M.w1, 0, k0, 3 * j, fb);
    tma2d(st + 40960, &M.w1x, 1536 + 24 * j, k0, fb);
  };
  auto kv_load = [&](int r, int hf) {
    const uint32_t st = sb + KVS + (r < 3 ? r : r - 3) * KV_BUF, fb = BAR((hf ? B_KIN1 : B_KIN) + r);
    mbar_expect(fb, KV_BUF / 2);
    tma2d(st + 4096 + hf * 2432, &M.k, 128 * r + 64 * (b & 1), 32 * (b >> 1) + 16 * hf - 3, fb);
    tma2d(st + hf * 2048, &M.v, 128 * r + 64 * (b & 1), 32 * (b >> 1) + 16 * hf, fb);
  };
  auto conv_sum = [&](int c, int ck, bool third) {
    const uint32_t ra = sb + cv_p(c) + ck * 16;
    __nv_bfloat16* yp = g_yT + (size_t)(128 * c + b) * SL + ck * 8;
    uint4 p[2][4];
    auto ld = [&](int u) {
#pragma unroll
      for (int w = 0; w < 4; w++) p[u & 1][w] = lds128((u == 0 && ck < 2 * w) ? sb + M_ZERO : ra + u * 512 + w * (4096 - 32));
    };
    auto st = [&](int u) {
      auto sum = [&](uint32_t a0, uint32_t a1, uint32_t a2, uint32_t a3) { return badd2(badd2(badd2(a3, a2), a1), a0); };
      const uint4* r = p[u & 1];
      stg128(yp + u * 256, sum(r[0].x, r[1].x, r[2].x, r[3].x), sum(r[0].y, r[1].y, r[2].y, r[3].y), sum(r[0].z, r[1].z, r[2].z, r[3].z), sum(r[0].w, r[1].w, r[2].w, r[3].w));
    };
    ld(0); ld(1); st(0);
    if (third) ld(2);
    st(1);
    if (third) st(2);
  };
  if (warp == 8) {
    if (lane == 0) {
      TS(0);
#pragma unroll
      for (int s = 0; s < 4; s++) mbar_init(BAR(B_F1 + s), 1);
    }
    __syncwarp();
    bar_arrive(NB_INIT, 384);
    ONE(g1_load(0));
  }
  if ((sb & 0xFFFFFFu) != sc) { if (warp == 8) mbar_wait(BAR(B_F1), 0); return; }

  if (warp >= 8) {
    asm volatile("setmaxnreg.dec.sync.aligned.u32 " REG_AUX ";");
    auto table = [&](int c, int aw) {
      const uint32_t kb = sb + cv_t(c);
      const uint32_t dd = lds32(sb + M_AUX + aw * 32 + c * 4);
      if (lane < 2) sts128(kb + lane * (KT_E - 16), 0u, 0u, 0u, 0u);
      uint4 r[8];
#pragma unroll
      for (int it = 0; it < 8; it++) r[it] = lds128(kb + KT_E + (it * 32 + lane) * 16);
      if (lane == 0) { r[0].x = __byte_perm(badd2(r[0].x, dd), r[0].x, 0x7610); sts32(kb + KT_E, r[0].x); }
#pragma unroll
      for (int it = 0; it < 8; it++) {
        const uint32_t pv = __shfl_sync(0xffffffffu, lane == 31 ? (it ? r[it ? it - 1 : 0].w : 0u) : r[it].w, lane - 1);
        sts128(kb + KT_O + (it * 32 + lane) * 16, __byte_perm(pv, r[it].x, 0x5432), __byte_perm(r[it].x, r[it].y, 0x5432),
               __byte_perm(r[it].y, r[it].z, 0x5432), __byte_perm(r[it].z, r[it].w, 0x5432));
      }
      __syncwarp();
      if (lane == 0) mbar_arrive(BAR(B_KT + c));
    };
    if (warp == 8) {
      ONE(g1_load(1); g1_load(2); g1_load(3));
      bar_sync(NB_INIT2, 128);
#pragma unroll
      for (int kc = 3; kc < 10; kc++) {
        if (kc > 3) mbar_wait(BAR(B_E1 + (kc & 3)), (kc >> 3) & 1);
        ONE(if (kc > 3) g1_load(kc);
            for (int r = 0; r < 3; r++) if (kc == ((KV_MAP >> (4 * r)) & 15)) { kv_load(r, 0); kv_load(r, 1); }
            for (int c = 0; c < 5; c++) if (kc == ((PF_RAW >> (4 * c)) & 15)) prefetch_l2(P.ssm_k + (size_t)(128 * c + b) * SL, 4096));
      }
      ONE(prefetch_map(&M.hs); prefetch_map(&M.hx); prefetch_map(&M.ha); prefetch_map(&M.hn); prefetch_map(&M.w2); prefetch_map(&M.w2x));
      bar_sync(NB_INIT3, 64);
      const unsigned ep = lds32(sb + M_AUX + 20);
      const int hc = kh * 896 + nt * 192, hx = kh * 896 + 768 + nt * 24;
#pragma unroll 1
      for (int n = 0; n < 32; n += 4) {
        const int i = (H_ORD >> n) & 7, hw = i >> 2, blk = i & 3;
        if (n == 4 * W2_PF) ONE(prefetch_l2(P.w2 + (size_t)b * (FF * DM / NCTA), FF * DM / NCTA * 2));
        mbar_wait(BAR(B_HB + i), 0);
        fence_async_smem();
        asm volatile("cp.async.bulk.wait_group %0;" ::"n"(H_FLY - 1) : "memory");
        ONE(tma2d_st(blk < 3 ? &M.hs : &M.hx, blk < 3 ? hc + blk * 64 : hx, rb * 128 + hw * 64, sb + hw * HST + blk * 8192); bulk_commit());
      }
      const int cf = (nt * 160 + (nt & 1) * 32) >> 6, ch = nt * 160 + ((nt & 1) ? 0 : 128);
      auto g2_load_b = [&](int kc) {
        const int s = kc & 3, wr = kc < 2 ? 1536 + kh * 96 + (1 - kc) * 64 : kh * 768 + (kc - 2) * 64;
        const uint32_t fb = BAR(B_F2 + s);
        mbar_expect(fb, kc == 0 ? 8192 + 20480 : 16384 + 20480);
        tma3d(sb + g2_b(s), &M.w2, 0, wr, cf, fb);
        tma2d(sb + g2_b(s) + 16384, &M.w2x, ch, wr, fb);
      };
      auto g2_load_a = [&](int kc) {
        const int s = kc & 3;
        tma2d(sb + g2_a(s), kc == 0 ? &M.hn : &M.ha, kh * 896 + (kc < 2 ? 768 + (1 - kc) * 64 : (kc - 2) * 64), rb * 128, BAR(B_F2 + s));
      };
      bulk_wait_all();
      ONE(g2_load_b(0); g2_load_b(1));
      fence_release();
      ONE(signal_cnt(CNT_H + rb * 2 + kh); TS(37));
      wait_cnt(CNT_H + rb * 2 + kh, 4 * ep);
      ONE(TS(39); g2_load_a(0); g2_load_a(1); prefetch_map(&M.qf); prefetch_map(&M.y); prefetch_map(&M.out));
      mbar_wait(BAR(B_KD), 0);
      ONE(g2_load_b(3));
      mbar_wait(BAR(B_TD + 1), 0);
      ONE(g2_load_b(2); g2_load_a(2));
      mbar_wait(BAR(SUM3 ? B_TD : B_SD + 3), 0);
      ONE(mbar_expect(BAR(B_FINQ), 20480); tma3d(sb + FIN_Q, &M.qf, 0, rb * 128 + kh * 64, nt * 5, BAR(B_FINQ)));
      mbar_wait(BAR(B_RF + 2), 0);
      ONE(g2_load_a(3); TS(38));
#pragma unroll 1
      for (int kc = 4; kc < 14; kc++) {
        mbar_wait(BAR(B_E2 + (kc & 3)), ((kc >> 2) - 1) & 1);
        ONE(g2_load_b(kc); g2_load_a(kc));
      }
      if (lane == 0) g_launch[b * 8] = ep;
#pragma unroll 1
      for (int i = 0; i < 5; i++) {
        int gi = i + (nt & 1); if (gi == 5) gi = 0;
        mbar_wait(BAR(B_OUT + i), 0);
        fence_async_smem();
        ONE(tma2d_st(&M.out, nt * 160 + gi * 32, rb * 128 + kh * 64, sb + FIN_Q + gi * 4096));
      }
      ONE(bulk_commit());
      bulk_wait_read();
    } else {
      const int aw = warp - 9, at = tid - 288;
      if (aw == 0) {
        if (lane == 0) {
#pragma unroll
          for (int s = 0; s < 4; s++) { mbar_init(BAR(B_E1 + s), 8); mbar_init(BAR(B_FR + s), 8); mbar_init(BAR(B_F2 + s), 1); mbar_init(BAR(B_E2 + s), 8); }
          mbar_init(BAR(B_KRAW), 1); mbar_init(BAR(B_KRAW + 1), 1);
          mbar_init(BAR(B_RED), 8); mbar_init(BAR(B_BX), 1);
        }
      } else if (aw == 1) {
        if (lane == 0) {
#pragma unroll
          for (int c = 0; c < 5; c++) { if (c == 0) { mbar_init(BAR(B_SK), 1); mbar_init(BAR(B_KD), 2); } mbar_init(BAR(B_XL + c), 1); mbar_init(BAR(B_KT + c), 1); mbar_init(BAR(B_XF + c), 1); mbar_init(BAR(B_SD + c), 4); }
        }
      } else if (lane == 0) {
#pragma unroll
        for (int i = 0; i < 8; i++) mbar_init(BAR(B_HB + i), 4);
#pragma unroll
        for (int c = 0; c < 3; c++) mbar_init(BAR(B_RF + c), 3);
        for (int r = 0; r < 5; r++) { mbar_init(BAR(B_KIN + r), 1); mbar_init(BAR(B_KIN1 + r), 1); }
        mbar_init(BAR(B_YSLOT), 8); mbar_init(BAR(B_XR), 1);
        for (int i = 0; i < 5; i++) mbar_init(BAR(B_OUT + i), 4);
        mbar_init(BAR(B_XD), 1); mbar_expect(BAR(B_XD), 8192); mbar_init(BAR(B_XD + 1), 1); mbar_expect(BAR(B_XD + 1), 12288);
        asm volatile("fence.mbarrier_init.release.cluster;" ::: "memory");
        mbar_init(BAR(B_TD), 4); mbar_init(BAR(B_TD + 1), 8); mbar_init(BAR(B_FINQ), 1); mbar_init(BAR(B_FINY), 1);
      }
      __syncwarp();
      bar_arrive(NB_INIT, 384);
      if (aw == 1) ONE(prefetch_map(&M.k); prefetch_map(&M.v); mbar_expect(BAR(B_SK), 2560);
                       for (int r = 0; r < 5; r++) bulk_g2s(sb + M_SK + r * 512, P.shift_k + (128 * r + 64 * (b & 1)) * 4, 512, BAR(B_SK)));
      const uint32_t dv0 = ld_relaxed32(lane < 5 ? static_cast<const void*>(P.ssm_D + 128 * lane + (b & ~1)) : &g_launch[b * 8]);
      const uint32_t b2v = ldg32(reinterpret_cast<const uint32_t*>(P.b2 + nt * 160) + (min(at, 79) + 16 * (nt & 1)) % 80);
      const int l27 = min(lane, 26), col = l27 < 24 ? 192 * j + 8 * l27 : 1536 + 24 * j + 8 * (l27 - 24);
      uint4 bb;
      if (aw == 2) bb = ldg128(P.b1 + col);
      bar_sync(NB_INIT2, 128);
      if (aw == 0) ONE(prefetch_map(&M.kvs));
      if (lane < 4) sts32(sb + M_ZERO + lane * 4, 0u);
      if (lane < 8) sts32(sb + M_AUX + aw * 32 + lane * 4, lane >= 5 ? dv0 + 1 : ((b & 1) ? dv0 >> 16 : dv0 & 0xFFFFu));
      if (at < 80) sts32(sb + M_B2 + at * 4, bmul2(b2v, 0x3f003f00u));
      __syncwarp();
      if (aw == 0) bar_arrive(NB_INIT3, 64);
      if (aw == 2) {
        const unsigned ep = lds32(sb + M_AUX + 64 + 20);
        const uint32_t ba = sb + M_BX + (l27 >> 2) * 512 + ((l27 & 3) << 4);
        mbar_wait(BAR(B_RED), 0);
        const uint32_t tg = ep & 15u;
        auto tagged = [&](float v) { return (__float_as_uint(v) & ~15u) | tg; };
        float c0 = 0.f, c1 = 0.f, s1 = 0.f, s2 = 0.f;
#pragma unroll
        for (int i = 0; i < 16; i += 2) { c0 += __uint_as_float(lds32(sb + M_RED1 + i * 128 + lane * 4)); c1 += __uint_as_float(lds32(sb + M_RED1 + i * 128 + 128 + lane * 4)); }
        st_relaxed32(&g_cs[(dir * 8 + j) * 256 + ci * 32 + lane], tagged(c0 + c1));
        float2 u[8];
#pragma unroll
        for (int i = 0; i < 8; i++) u[i] = lds64f(sb + M_RED0 + (lane & 15) * 128 + ((i + lane) & 7) * 16 + (lane >> 4) * 8);
        const float c = bf_round(u[0].x * (1.f / 40)), cc = 40.f * c * c;
#pragma unroll
        for (int i = 0; i < 8; i++) { s1 += fmaf(-40.f, c, u[i].x); s2 += fmaf(-2.f * c, u[i].x, u[i].y) + cc; }
        const float dm = s1 * (1.f / 320);
        st_relaxed64(&g_stat[dir * SL + rb * 128 + ri * 32 + lane], tagged(c + dm), tagged(fmaf(-dm, s1, s2)));
        __syncwarp();
        if (lane == 0) TS(30);
        sts128((ba + 128) ^ 16, 0u, 0u, 0u, 0u); sts128((ba + 192) ^ 16, bb.x, bb.y, bb.z, bb.w);
#pragma unroll
        for (int i = 4; i < 8; i++) sts128((ba + i * 64) ^ ((i >> 1) << 4), 0u, 0u, 0u, 0u);
        mbar_wait(BAR(B_FR), 0);
        auto raw_load = [&]() {
          ONE(mbar_expect(BAR(B_KRAW), 4096); mbar_expect(BAR(B_KRAW + 1), 4 * 4096);
              for (int c = 0; c < 5; c++) bulk_g2s(sb + cv_t(c) + KT_E, P.ssm_k + (size_t)(128 * c + b) * SL, 4096, BAR(B_KRAW + (c >= 1))));
        };
        uint32_t x[32], n = 0;
#pragma unroll 1
        while (true) {
#pragma unroll
          for (int i = 0; i < 8; i++) {
            const uint4 v = ld_relaxed128(i < 4 ? static_cast<const void*>(g_cs + ((i >> 1) * 8 + j) * 256 + l27 * 8 + (i & 1) * 4)
                                                : g_stat + ((i >> 1) & 1) * SL + rb * 128 + lane * 4 + (i & 1) * 2);
            x[4 * i] = v.x; x[4 * i + 1] = v.y; x[4 * i + 2] = v.z; x[4 * i + 3] = v.w;
          }
          if (!RAW_LATE && n == 0) raw_load();
          uint32_t bad = 0;
#pragma unroll
          for (int i = 0; i < 32; i++) { x[i] ^= tg; bad |= x[i]; }
          if (__all_sync(0xffffffffu, (bad & 15u) == 0) || spin_guard(n, 0x131)) break;
        }
        if (RAW_LATE) raw_load();
        uint32_t st[4];
#pragma unroll
        for (int i = 0; i < 4; i++) {
          const float ma = __uint_as_float(x[16 + 2 * i]), mb = __uint_as_float(x[24 + 2 * i]), dl = ma - mb;
          const float m2 = fmaf(dl * dl, 160.f, __uint_as_float(x[17 + 2 * i]) + __uint_as_float(x[25 + 2 * i]));
          const float vb = bf_round(fmaxf(m2, 0.f) * (1.f / DM));
          st[i] = pack_bf16(0.5f * (ma + mb), sqrt_fast(bf_round(vb + 1e-5f)));
        }
        sts128(sb + M_STAT + lane * 16, st[0], st[1], st[2], st[3]);
        uint32_t hi[4], lo[4];
#pragma unroll
        for (int i = 0; i < 4; i++) {
          const float x0 = __uint_as_float(x[2 * i]) + __uint_as_float(x[8 + 2 * i]), x1 = __uint_as_float(x[2 * i + 1]) + __uint_as_float(x[9 + 2 * i]);
          hi[i] = pack_bf16(x0, x1); lo[i] = pack_bf16(x0 - bf_lo(hi[i]), x1 - bf_hi(hi[i]));
        }
        sts128(ba, hi[0], hi[1], hi[2], hi[3]); sts128(ba + 64, lo[0], lo[1], lo[2], lo[3]);
        fence_async_smem();
        __syncwarp();
        ONE(mbar_arrive(BAR(B_BX)); TS(54));
      }
      if (aw < 2) {
        auto done = [&](int r) {
          bulk_wait_read();
          ONE(kv_load(r + 3, aw); TSKV);
        };
        const uint32_t par = lds32(sb + M_AUX + aw * 32 + 20) & 1u;
        bool pend = false;
        mbar_wait(BAR(B_SK), 0);
#pragma unroll 1
        for (int r = 0; r < 5; r++) {
          const int c0 = 128 * r + 64 * (b & 1);
          const uint32_t buf = sb + KVS + (r < 3 ? r : r - 3) * KV_BUF, stg = buf + aw * 2048, vb = stg + lane * 4, kb = buf + 4096 + aw * 2432 + lane * 4;
          const uint4 sk = lds128(sb + M_SK + r * 512 + lane * 16);
          const uint32_t w0 = __byte_perm(sk.x, sk.z, 0x5410), w1 = __byte_perm(sk.x, sk.z, 0x7632);
          const uint32_t w2 = __byte_perm(sk.y, sk.w, 0x5410), w3 = __byte_perm(sk.y, sk.w, 0x7632);
          mbar_wait(BAR((aw ? B_KIN1 : B_KIN) + r), 0);
          if (at == 0 && r == 0) TS(56);
          uint32_t kk[19], o[16];
#pragma unroll
          for (int i = 0; i < 19; i++) { kk[i] = lds32(kb + i * 128); if (i >= 3) o[i - 3] = lds32(vb + (i - 3) * 128); }
#pragma unroll
          for (int i = 0; i < 16; i++) o[i] = bmul2(bfma2(kk[i + 3], w0, bfma2(kk[i + 2], w1, bfma2(kk[i + 1], w2, bmul2(kk[i], w3)))), o[i]);
          __syncwarp();
          const uint32_t a0 = stg + lane * 64 + ((lane & 6) << 3);
          const uint32_t s0 = (lane & 4) ? 0x7632 : 0x5410, s1 = s0 ^ 0x2222;
#pragma unroll
          for (int hh = 0; hh < 2; hh++) {
            const uint32_t* u = o + 8 * hh;
            const uint32_t a = a0 ^ (hh << 4);
            auto nz = [&](uint32_t x) { return hh ? x : (x & ~1u) | par; };
            sts128(a, nz(__byte_perm(u[1], u[0], s0)), __byte_perm(u[3], u[2], s0), __byte_perm(u[5], u[4], s0), __byte_perm(u[7], u[6], s0));
            sts128(a ^ 32, nz(__byte_perm(u[1], u[0], s1)), __byte_perm(u[3], u[2], s1), __byte_perm(u[5], u[4], s1), __byte_perm(u[7], u[6], s1));
          }
          if (pend) done(r - 1);
          fence_async_smem();
          __syncwarp();
          ONE(tma2d_st(&M.kvs, 32 * (b >> 1) + 16 * aw, c0, stg); bulk_commit());
          pend = r < 2 && mbar_test(BAR((aw ? B_KIN1 : B_KIN) + r + 1), 0);
          if (!pend && r < 2) done(r);
        }
      }
      const unsigned ep = lds32(sb + M_AUX + aw * 32 + 20);
      auto x_load = [&](int c) { mbar_expect(BAR(B_XL + c), 4096); bulk_g2s(sb + cv_x(c) + XD, g_kvT + (size_t)(128 * c + b) * SL, 4096, BAR(B_XL + c)); };
      auto x_pad = [&](int c0, int c1) {
        if (lane < 17) for (int c = c0; c < c1; c++) sts128(sb + cv_x(c) + lane * 16, 0u, 0u, 0u, 0u);
        fence_async_smem();
        __syncwarp();
      };
      if (aw == 2) {
        mbar_wait(BAR(B_FR + 1), 0);
        ONE(for (int c = 0; c < X_A; c++) x_load(c));
        x_pad(0, 4);
      }
#pragma unroll 1
      for (int c = 2 - aw; c < 5; c += 2) {
        mbar_wait(BAR(B_KRAW + (c > 0)), 0);
        if (lane == 0 && c == 2) TS(35);
        table(c, aw);
        if (lane == 0 && c == 2) TS(55);
        if (c == 0) break;
        if (c < 3) { bulk_wait_read(); ONE(mbar_arrive(BAR(B_KD)); if (aw == 0) TS(34)); }
      }
      if (aw == 2) {
#pragma unroll 1
        for (int c = 0, n = 0; c < 5;) {
          mbar_wait(BAR(B_XL + c), n & 1);
          const uint32_t a = sb + cv_x(c) + XD + lane * 32;
          const uint32_t v = ((lds32(a) ^ ep) | (lds32(a + 1024) ^ ep) | (lds32(a + 2048) ^ ep) | (lds32(a + 3072) ^ ep)) & 1u;
          int nx = c;
          if (__all_sync(0xffffffffu, v == 0) || n > 100000) {
            ONE(mbar_arrive(BAR(B_XF + c)); if (c == 0) TS(36); if (c >= 3) TS(28 + c));
            nx = c + X_A; c++; n = 0;
            if (nx == 4) { mbar_wait(BAR(B_KD), 0); x_pad(4, 5); }
          } else {
            n++;
            if (lane == 0) TS(33);
          }
          if (nx < 5) ONE(x_load(nx));
        }
      }
      if (RED_GATE) mbar_wait(BAR(RED_GATE == 1 ? B_TD + 1 : B_SD + RED_GATE - 1), 0);
#pragma unroll 1
      for (int c = 0; c < 5; c++) {
        mbar_wait(BAR(B_SD + c), 0);
        if (c == 3 && SUM3) continue;
        conv_sum(c, aw * 96 + lane, aw < 2);
        __syncwarp();
        if (c < 3 && lane == 0) mbar_arrive(BAR(B_RF + c));
        if (at == 0) TS(59 + c);
      }
      bar_sync(NB_AUX, 96);
      if (aw == 0) {
        fence_release();
        ONE(signal_cnt(CNT_Y); TS(3));
        wait_cnt(CNT_Y, 128 * ep);
        ONE(TS(40); mbar_arrive(BAR(B_XR)));
        mbar_wait(BAR(B_YSLOT), 0);
        ONE(mbar_expect(BAR(B_FINY), 20480); tma2d(sb + FIN_Y, &M.y, rb * 128 + kh * 64, nt * 160, BAR(B_FINY)));
      }
    }
  } else {
    asm volatile("setmaxnreg.inc.sync.aligned.u32 " REG_CON ";");
    const int wg = warp >> 2, w = warp & 3, g = lane >> 2, q = lane & 3;
    constexpr bool elect = false;
    uint32_t ca[64];
    const uint32_t ab0 = sb + ((g & 1) ? KT_E : KT_O) + (8 * w + 4 + (g >> 1) - q) * 4;
    auto conv_lda = [&](int c, int k0, int k1) {
      const uint32_t ab = ab0 + cv_t(c);
#pragma unroll
      for (int ks = 15; ks >= 0; ks--) {
        if (ks >= k0 && ks < k1) {
          ca[4 * ks + 0] = lds32(ab + ks * 256);
          ca[4 * ks + 1] = lds32(ab + ks * 256 + 128);
          ca[4 * ks + 2] = lds32(ab + ks * 256 - 16);
          ca[4 * ks + 3] = lds32(ab + ks * 256 + 112);
        }
      }
    };
    {
      float d[108];
      auto g1_release = [&](int kc) { if (lane == 0) mbar_arrive(BAR(kc < 6 ? B_E1 + (kc & 3) : B_FR + kc - 6)); };
      auto g1_wait = [&](int kc) { mbar_wait(BAR(B_F1 + (kc & 3)), (kc >> 2) & 1); };
      auto g1_issue = [&](int kc) {
        const int s = kc & 3;
        if (kc == 0) { mbar_wait(BAR(B_F1), 0); if (wg == 1) bar_sync(NB_LEAD, 256); }
        if (tid == 0) TS(8 + kc);
        const uint32_t st = sc + s * G1_STAGE;
        const uint64_t da = mkdesc(st + wg * 8192, 16, 1024, 1), db = mkdesc(st + 16384, 8192, 1024, 1);
        wg_fence();
#pragma unroll
        for (int k = 0; k < 4; k++) {
          wg_ss_216(d, da + k * 2, db + k * 128, (kc | k) != 0);
          if (k == REL_K || k == 3) wg_commit();
          if (k == REL_K && kc > 0) { wg_wait<1>(); g1_release(kc - 1); }
        }
        if (kc == 0 && wg == 0) bar_arrive(NB_LEAD, 256);
      };
      const int t7 = tid & 127, wr = ((t7 >> 3) & 1) * 4 + (t7 >> 4) * 8, wc = 4 * min(ci, 6) + ((t7 >> 1) & 3);
      const uint32_t sa0 = sb + (wg ? 16384 + (wc >> 3) * 8192 + wr * 128 + (((wc ^ wr) & 7) << 4) + (t7 & 1) * 8 : ri * 4096 + t7 * 16);
      float t1 = 0.f, t2 = 0.f, t3 = 0.f, t4 = 0.f;
      auto piece = [&](int i) {
        if (wg == 0) {
          const uint4 x = lds128(sa0 + (i & 3) * G1_STAGE), y = lds128(sa0 + (i & 3) * G1_STAGE + 2048);
          const uint32_t xx[4] = {x.x, x.y, x.z, x.w}, yy[4] = {y.x, y.y, y.z, y.w};
#pragma unroll
          for (int e = 0; e < 4; e++) {
            const float u = bf_lo(xx[e]), v = bf_hi(xx[e]), r = bf_lo(yy[e]), z = bf_hi(yy[e]);
            t1 += u; t2 = fmaf(u, u, t2); t3 += r; t4 = fmaf(r, r, t4);
            t1 += v; t2 = fmaf(v, v, t2); t3 += z; t4 = fmaf(z, z, t4);
          }
        } else {
          float2 xx[4];
#pragma unroll
          for (int e = 0; e < 4; e++) xx[e] = lds64f((sa0 ^ (e * 144)) + (i & 3) * G1_STAGE);
#pragma unroll
          for (int e = 0; e < 4; e++) {
            const uint32_t u = __float_as_uint(xx[e].x), v = __float_as_uint(xx[e].y);
            t1 += bf_lo(u); t2 += bf_hi(u); t3 += bf_lo(v); t4 += bf_hi(v);
          }
        }
      };
      bar_sync(NB_INIT, 384);
#pragma unroll
      for (int kc = 0; kc < 10; kc++) {
        g1_issue(kc);
        if (kc < 5) { g1_wait(kc); piece(kc); }
        if (kc == 4) {
          sts128(sb + (wg ? M_RED1 : M_RED0) + t7 * 16, __float_as_uint(t1), __float_as_uint(t2), __float_as_uint(t3), __float_as_uint(t4));
          __syncwarp();
          if (lane == 0) mbar_arrive(BAR(B_RED));
        }
        if (kc < 9) g1_wait(kc + 1);
      }
      uint2 s0, s1;
      {
        mbar_wait(BAR(B_BX), 0);
        s0.x = lds32(sb + M_STAT + (wg * 64 + w * 16 + g) * 4); s1.x = lds32(sb + M_STAT + (wg * 64 + w * 16 + g + 8) * 4);
        if (tid == 0) TS(46);
        const uint32_t f0 = q == 0 ? ((s0.x & 0xFFFFu) * 0x10001u) ^ 0x80008000u : (q == 1 ? s0.x ^ 0x8000u : 0u);
        const uint32_t f1 = q == 0 ? ((s1.x & 0xFFFFu) * 0x10001u) ^ 0x80008000u : (q == 1 ? s1.x ^ 0x8000u : 0u);
        wg_fence();
        wg_rs_216(d, f0, f1, 0u, 0u, mkdesc(sc + M_BX, 512, 0, 2));
        wg_commit();
      }
      wg_wait<1>();
      if (lane == 0) mbar_arrive(BAR(B_FR + 3));
      const float r0 = 0.25f * rcp_fast(bf_hi(s0.x)), r1 = 0.25f * rcp_fast(bf_hi(s1.x));
      if (wg == 0) mbar_wait(BAR(B_FR + 2), 0);
      wg_wait<0>();
      if (elect) TS(1 + 47 * wg);
      if (wg == 1) bar_sync(NB_GELU, 256);
      const int mi = lane >> 3, row = w * 16 + (mi & 1) * 8 + (lane & 7);
      const uint32_t hs = sb + wg * HST;
      constexpr float C1 = 4.f * 0.7978845608028654f, C2 = 64.f * 0.7978845608028654f * 0.044715f;
      auto gelu2 = [&](float hx) { const float u = hx * fmaf(hx * hx, C2, C1); return fmaf(hx, tanh_fast(u), hx); };
#pragma unroll
      for (int nb = 0; nb < 28; nb += 2) {
        uint32_t p[4];
#pragma unroll
        for (int e = 0; e < 2; e++) {
          if (nb + e < 27) {
            const float* dd = d + 4 * (nb + e);
            p[2 * e] = pack_bf16(gelu2(dd[0] * r0), gelu2(dd[1] * r0));
            p[2 * e + 1] = pack_bf16(gelu2(dd[2] * r1), gelu2(dd[3] * r1));
          }
        }
        const int nbm = nb + (mi >> 1);
        if (nb < 24) stsm4(hs + (nb >> 3) * 8192 + row * 128 + (((nbm & 7) ^ (row & 7)) << 4), p[0], p[1], p[2], p[3]);
        else if (nb == 24) stsm4(hs + 24576 + row * 48 + (mi >> 1) * 16, p[0], p[1], p[2], p[3]);
        else stsm2(hs + 24576 + row * 48 + 32, p[0], p[1]);
        if ((nb & 7) == 6 || nb == 26) {
          __syncwarp();
          if (lane == 0) mbar_arrive(BAR(B_HB + wg * 4 + (nb >> 3)));
        }
        if (nb == GELU_NB && wg == 0) bar_arrive(NB_GELU, 256);
        if (nb == A_NB0) mbar_wait(BAR(B_KT + wg), 0);
        if (nb >= A_NB0 && A_NB0 < 28) conv_lda(wg, 16 - ((nb - A_NB0) / 2 + 1) * 16 / (A_NB0 < 28 ? (28 - A_NB0) / 2 : 1), 16 - (nb - A_NB0) / 2 * 16 / (A_NB0 < 28 ? (28 - A_NB0) / 2 : 1));
      }
      if (A_NB0 >= 28) { mbar_wait(BAR(B_KT + wg), 0); conv_lda(wg, 0, 16); }
      if (elect) TS(2 + 47 * wg);
    }
#pragma unroll 1
    for (int c = wg; c < 5; c += 2) {
      float d[128];
      mbar_wait(BAR(B_XF + c), 0);
      if (c < 3) mbar_wait(BAR(B_KT + c + 2), 0);
      const uint64_t db = mkdesc(sc + cv_x(c), 16, 128, 0);
      if (c > 0) { if (wg) bar_sync(NB_TURN + 1, 256); else bar_sync(NB_TURN, 256); }
      wg_fence();
      auto hand = [&]() { if (wg) bar_arrive(NB_TURN, 256); else bar_arrive(NB_TURN + 1, 256); };
      if (c < 3) conv_chain_1(d, ca, db, ab0 + cv_t(c + 2), hand); else conv_chain_0(d, ca, db, 0, hand);
      mbar_wait(BAR(c >= 3 ? B_RF + c - 3 : B_FR + 3), 0);
      wg_wait<0>();
      if (elect) TS(41 + c);
      const uint32_t wa = sb + cv_p(c) + w * 4096 + lane * 16;
#pragma unroll
      for (int n4 = 0; n4 < 32; n4 += 4) {
        uint32_t p[4];
#pragma unroll
        for (int e = 0; e < 4; e++) {
          const int nb = n4 + e;
          float x = d[4 * nb], y = d[4 * nb + 1];
          if (nb > 0) { x += d[4 * nb - 2]; y += d[4 * nb - 1]; }
          p[e] = pack_bf16(x, y);
        }
        stsm4t(wa + n4 * 128, p[0], p[1], p[2], p[3]);
      }
      if (c == 3 && SUM3) break;
      __syncwarp();
      if (lane == 0) mbar_arrive(BAR(B_SD + c));
      if (c < 3) {
        conv_lda(c + 2, 0, CV_RELOADED);
        if (c > 0) {
          fence_async_smem();
          __syncwarp();
          if (lane == 0) mbar_arrive(BAR(B_TD + 1));
        }
      }
    }
    if (elect) TS(51 + wg);
    {
      float d[80];
      const uint32_t aoff = (wg ^ kh) * 8192;
      auto g2_release = [&](int kc) { if (lane == 0) mbar_arrive(BAR(kc == 10 ? B_YSLOT : B_E2 + (kc & 3))); };
      auto g2_mma = [&](int kc, int first, bool rel) {
        const int s = kc & 3;
        mbar_wait(BAR(B_F2 + s), (kc >> 2) & 1);
        const uint64_t da = mkdesc(sc + g2_a(s) + aoff, 16, 1024, 1), db = mkdesc(sc + g2_b(s), 8192, 1024, 1);
        wg_fence();
#pragma unroll
        for (int k = 0; k < (kc ? 4 : 2); k++) {
          wg_ss_160(d, da + k * 2, db + k * 128, k ? 1 : first);
          if ((k == REL_K && rel) || k == (kc ? 3 : 1)) wg_commit();
          if (k == REL_K && rel) { wg_wait<1>(); g2_release(kc - 1); }
        }
      };
      if (wg == 1) {
        if (SUM3) {
          bar_sync(NB_WG1, 128);
          if (lane == 0) mbar_arrive(BAR(B_TD));
          conv_sum(3, w * 64 + lane, false);
          __syncwarp();
          if (lane == 0) mbar_arrive(BAR(B_SD + 3));
          if (elect) TS(62);
        }
#pragma unroll
        for (int nb = 0; nb < 20; nb++) {
          const uint32_t v = lds32(sb + M_B2 + nb * 16 + q * 4);
          d[4 * nb] = d[4 * nb + 2] = bf_lo(v); d[4 * nb + 1] = d[4 * nb + 3] = bf_hi(v);
        }
        bar_sync(NB_TURN + 1, 256);
        g2_mma(0, 1, false);
#pragma unroll
        for (int kc = 1; kc < 14; kc++) {
          g2_mma(kc, 1, kc < 12);
          if (kc == END_KC) bar_arrive(NB_END, 256);
        }
        mbar_wait(BAR(B_XR), 0);
        wg_wait<0>();
        if (elect) TS(53);
        const uint32_t ra = mapa(sb, kh ^ 1), rbar = ra + M_BAR + 8 * B_XD, dst = ra + (tid & 127) * 16;
#pragma unroll
        for (int i = 0; i < 10; i++) {
          const float* dd = d + 8 * i;
          st_async128(dst + (i < 5 ? P0 + i * 2048 : P1 + (i - 5) * 2048), pack_bf16(dd[0], dd[1]), pack_bf16(dd[2], dd[3]), pack_bf16(dd[4], dd[5]), pack_bf16(dd[6], dd[7]), rbar + 8 * (i >= 4));
        }
        if (elect) TS(7);
      } else {
        const int mi = lane >> 3, row = (mi & 1) * 8 + (lane & 7);
        const uint32_t qa = sb + FIN_Q + (w * 16 + row) * 64;
        auto q_addr = [&](int np) {
          int gi = (np >> 1) + (nt & 1); if (gi == 5) gi = 0;
          return qa + gi * 4096 + ((((np & 1) * 2 + (mi >> 1)) ^ ((row >> 1) & 3)) << 4);
        };
        uint32_t sv[40];
        uint32_t m0, m1; float rs0, rs1;
        g2_mma(0, 0, false);
#pragma unroll
        for (int kc = 1; kc < 10; kc++) {
          if (tid == 0) TS(17 + kc);
          g2_mma(kc, 1, true);
          if (kc == XP_KC - 1) {
            const uint32_t s0 = lds32(sb + M_STAT + (kh * 64 + w * 16 + g) * 4), s1 = lds32(sb + M_STAT + (kh * 64 + w * 16 + g + 8) * 4);
            m0 = (s0 & 0xFFFFu) * 0x10001u; m1 = (s1 & 0xFFFFu) * 0x10001u;
            rs0 = rcp_fast(bf_hi(s0)); rs1 = rcp_fast(bf_hi(s1));
          }
          if (kc >= XP_KC && XP_KC < 10) {
            mbar_wait(BAR(B_FINQ), 0);
#pragma unroll
            for (int np = 10 * (kc - XP_KC) / (XP_KC < 10 ? 10 - XP_KC : 1); np < 10 * (kc + 1 - XP_KC) / (XP_KC < 10 ? 10 - XP_KC : 1); np++) {
              uint32_t xq[4];
              ldsm4(q_addr(np), xq[0], xq[1], xq[2], xq[3]);
#pragma unroll
              for (int e = 0; e < 4; e++) {
                const uint32_t dm = bsub2(xq[e], (e & 1) ? m1 : m0);
                const float rs = (e & 1) ? rs1 : rs0;
                sv[4 * np + e] = pack_bf16(bf_lo(dm) * rs, bf_hi(dm) * rs);
              }
            }
          }
        }
        auto y_prep = [&](int n0, int n1) {
          if (n1 > n0) mbar_wait(BAR(B_FINY), 0);
#pragma unroll
          for (int np = n0; np < n1; np++) {
            int cb = 2 * np + 4 * (nt & 1); if (cb >= 20) cb -= 20;
            cb += mi >> 1;
            const uint32_t ya = sb + FIN_Y + cb * 1024 + (lane & 7) * 128 + (((2 * w + (mi & 1)) ^ (lane & 7)) << 4);
            uint32_t y[4];
            ldsm4t(ya, y[0], y[1], y[2], y[3]);
#pragma unroll
            for (int e = 0; e < 4; e++) sv[4 * np + e] = bmul2(sv[4 * np + e], y[e]);
          }
        };
        if (tid == 0) TS(27);
#pragma unroll
        for (int kc = 10; kc < 14; kc++) {
          g2_mma(kc, 1, kc == 10 || (kc == 11 && HOLD_KC > 10));
          if (kc == HOLD_KC) {
            if (kc == 10) { wg_wait<0>(); g2_release(10); }
            if (tid == 0) TS(28);
            bar_sync(NB_END, 256);
          }
          if (kc == 12) y_prep(0, YP_N);
        }
        if (tid == 0) TS(29);
        y_prep(YP_N, 10);
        if (tid == 0) TS(47);
        mbar_wait(BAR(B_XD), 0);
        if (tid == 0) TS(5);
        uint4 v0 = lds128(sb + tid * 16 + P0), v1 = lds128(sb + tid * 16 + P0 + 2048);
        wg_wait<0>();
        if (tid == 0) TS(4);
#pragma unroll
        for (int np = 0; np < 10; np++) {
          const uint32_t pw[4] = {v0.x, v0.y, v0.z, v0.w};
          v0 = v1;
          if (np < 8) {
            if (np == 2) mbar_wait(BAR(B_XD + 1), 0);
            v1 = lds128(sb + tid * 16 + (np + 2 < 5 ? P0 + (np + 2) * 2048 : P1 + (np - 3) * 2048));
          }
          uint32_t o[4];
          ldsm4(q_addr(np), o[0], o[1], o[2], o[3]);
#pragma unroll
          for (int e = 0; e < 4; e++) {
            const float h0 = d[8 * np + 2 * e] + bf_lo(pw[e]), h1 = d[8 * np + 2 * e + 1] + bf_hi(pw[e]);
            o[e] = bfma2(sv[4 * np + e], pack_bf16(fmaf(h0, tanh_fast(h0), h0), fmaf(h1, tanh_fast(h1), h1)), o[e]);
          }
          stsm4(q_addr(np), o[0], o[1], o[2], o[3]);
          if (np & 1) {
            if (np == 9 && tid == 0) TS(50);
            __syncwarp();
            if (lane == 0) mbar_arrive(BAR(B_OUT + (np >> 1)));
          }
        }
      }
    }
  }
}

typedef CUresult (*EncFn)(CUtensorMap*, CUtensorMapDataType, cuuint32_t, void*, const cuuint64_t*, const cuuint64_t*, const cuuint32_t*, const cuuint32_t*,
                          CUtensorMapInterleave, CUtensorMapSwizzle, CUtensorMapL2promotion, CUtensorMapFloatOOBfill);

static void make_map(EncFn enc, CUtensorMap* tm, const void* ptr, int cols, int rows, int bc, int br, int grp, CUtensorMapSwizzle sw,
                     CUtensorMapL2promotion promo = CU_TENSOR_MAP_L2_PROMOTION_NONE) {
  cuuint64_t gd[3] = {(cuuint64_t)(grp ? bc : cols), (cuuint64_t)rows, (cuuint64_t)(cols / bc)};
  cuuint64_t gs[2] = {(cuuint64_t)cols * 2, (cuuint64_t)bc * 2};
  cuuint32_t bd[3] = {(cuuint32_t)bc, (cuuint32_t)br, (cuuint32_t)grp};
  cuuint32_t es[3] = {1, 1, 1};
  CUresult r = enc(tm, CU_TENSOR_MAP_DATA_TYPE_BFLOAT16, grp ? 3 : 2, const_cast<void*>(ptr), gd, gs, bd, es, CU_TENSOR_MAP_INTERLEAVE_NONE, sw,
                   promo, CU_TENSOR_MAP_FLOAT_OOB_FILL_NONE);
  (void)r;
}

}

extern "C" void kernel_launch(void* const* d_in, const int* in_sizes, int n_in, void* d_out, int out_size) {
  using namespace h3;
  (void)in_sizes; (void)n_in; (void)out_size;
  static EncFn enc = nullptr;
  static void *p_h = nullptr, *p_yT = nullptr, *p_kvT = nullptr;
  if (!enc) {
    void* fn = nullptr; cudaDriverEntryPointQueryResult qr;
    cudaGetDriverEntryPoint("cuTensorMapEncodeTiled", &fn, cudaEnableDefault, &qr);
    enc = (EncFn)fn;
    cudaGetSymbolAddress(&p_h, g_h);
    cudaGetSymbolAddress(&p_yT, g_yT);
    cudaGetSymbolAddress(&p_kvT, g_kvT);
    cudaFuncSetAttribute(h3_kernel, cudaFuncAttributeMaxDynamicSharedMemorySize, SMEM_BYTES);
  }
  Params P;
  P.q = (const __nv_bfloat16*)d_in[0]; P.k = (const __nv_bfloat16*)d_in[1]; P.v = (const __nv_bfloat16*)d_in[2];
  P.shift_k = (const __nv_bfloat16*)d_in[3]; P.ssm_k = (const __nv_bfloat16*)d_in[4]; P.ssm_D = (const __nv_bfloat16*)d_in[5];
  P.out = (__nv_bfloat16*)d_out;
  P.w1 = (const __nv_bfloat16*)d_in[7]; P.b1 = (const __nv_bfloat16*)d_in[8]; P.w2 = (const __nv_bfloat16*)d_in[9]; P.b2 = (const __nv_bfloat16*)d_in[10];
  const CUtensorMapSwizzle S128 = CU_TENSOR_MAP_SWIZZLE_128B, S64 = CU_TENSOR_MAP_SWIZZLE_64B, S0 = CU_TENSOR_MAP_SWIZZLE_NONE;
  Maps M;
  make_map(enc, &M.qa, P.q, DM, SL, 64, 128, 0, S128);
  make_map(enc, &M.w1, P.w1, FF, DM, 64, 64, 3, S128);
  make_map(enc, &M.w1x, P.w1, FF, DM, 24, 64, 0, S128, WS_PROMO);
  make_map(enc, &M.k, P.k, DM, SL, 64, 19, 0, S0);
  make_map(enc, &M.v, P.v, DM, SL, 64, 16, 0, S0);
  make_map(enc, &M.hs, p_h, HP, SL, 64, 64, 0, S128);
  make_map(enc, &M.hx, p_h, HP, SL, 24, 64, 0, S0);
  make_map(enc, &M.ha, p_h, HP, SL, 64, 128, 0, S128);
  make_map(enc, &M.hn, p_h, HP, SL, 32, 128, 0, S128);
  make_map(enc, &M.w2, P.w2, DM, FF, 64, 64, 2, S128);
  make_map(enc, &M.w2x, P.w2, DM, FF, 32, 64, 0, S128);
  make_map(enc, &M.kvs, p_kvT, SL, DM, 16, 64, 0, CU_TENSOR_MAP_SWIZZLE_32B);
  make_map(enc, &M.qf, P.q, DM, SL, 32, 64, 5, S64);
  make_map(enc, &M.y, p_yT, SL, DM, 64, 160, 0, S128);
  make_map(enc, &M.out, d_out, DM, SL, 32, 64, 0, S64);
  h3_kernel<<<NCTA, 384, SMEM_BYTES>>>(M, P);
}
```

```cpp
#include <cuda_runtime.h>
#include <cuda_bf16.h>
#include <cuda.h>
#include <stdint.h>

namespace h3 {

constexpr int SL = 2048, DM = 640, FF = 1728, HP = 1792;
constexpr int NCTA = 128;

__device__ __align__(1024) __nv_bfloat16 g_h[SL * HP];
__device__ __align__(1024) __nv_bfloat16 g_kvT[DM * SL];
__device__ __align__(1024) __nv_bfloat16 g_yT[DM * SL];
__device__ __align__(1024) uint2 g_stat[2 * SL];
__device__ __align__(1024) uint32_t g_cs[2 * 8 * 256];
__device__ __align__(1024) unsigned g_cnt[64 * 32];
__device__ __align__(1024) unsigned g_launch[NCTA * 8];
constexpr int CNT_Y = 0, CNT_H = 16;

constexpr int G1_STAGE = 49152, G1_TX = 16384 + 24576 + 3072;
constexpr int HST = 49152;
constexpr int P0 = 81920, P1 = 140288, P2 = 156672;
constexpr int XCH = 4368, XD = 272, X0 = 173056, X4 = 221184;
constexpr int KVS = 196608, KV_BUF = 8960;
constexpr int KT_CH = 8240, KT_O = 16, KT_E = 4144, KT0 = 98304;
constexpr int FIN_Q = X0, FIN_Y = 98304;
constexpr int MISC = 226816;
constexpr int M_BX = MISC;
constexpr int M_RED0 = M_BX + 2048, M_RED1 = M_BX;
constexpr int M_SK = KVS + 3 * KV_BUF;
constexpr int M_STAT = M_BX + 3584;
constexpr int M_B2 = MISC - 640;
constexpr int M_AUX = M_STAT + 512;
constexpr int M_ZERO = M_AUX + 96;
constexpr int M_BAR = M_ZERO + 16;
constexpr int M_TS = M_BAR + 80 * 8;
constexpr int SMEM_BYTES = M_TS + 256;
__host__ __device__ constexpr int cv_x(int c) { return c == 4 ? X4 : X0 + c * XCH; }
__host__ __device__ constexpr int cv_p(int c) { return c == 2 ? P2 : ((c == 0 || c == 3) ? P0 : P1); }
__host__ __device__ constexpr int cv_t(int c) { return KT0 + c * KT_CH; }
__host__ __device__ constexpr int g2_a(int s) { return s == 0 ? 0 : (s == 1 ? 40960 : (s == 2 ? 98304 : P2)); }
__host__ __device__ constexpr int g2_b(int s) { return s == 0 ? 16384 : (s == 1 ? 57344 : (s == 2 ? 114688 : KVS)); }
static_assert(M_SK + 2560 <= M_B2 && X4 + XCH <= M_B2 && KVS + 24576 <= X4 && X0 + 4 * XCH <= KVS && FIN_Q + 20480 <= KVS, "smem");
static_assert(KT0 + 5 * KT_CH <= P1 && P1 + 16384 <= P2 && P2 + 16384 <= X0 && SMEM_BYTES <= 232448 && MISC % 512 == 0 && M_BAR % 8 == 0, "smem");
constexpr int B_F1 = 0, B_E1 = 4, B_FR = 8, B_F2 = 12, B_E2 = 16, B_KRAW = 20, B_KT = 22, B_XF = 27, B_HB = 32, B_SD = 40, B_RF = 45,
              B_TD = 48, B_FINQ = 50, B_FINY = 51, B_RED = 52, B_BX = 53, B_KIN = 54, B_XR = 59, B_OUT = 61, B_SK = 66, B_YSLOT = 67, B_XD = 68, B_KIN1 = 70, B_XL = 75, B_KD = 60;
constexpr int NB_INIT = 1, NB_INIT2 = 2, NB_AUX = 3, NB_LEAD = 4, NB_GELU = 5, NB_TURN = 6  , NB_END = 8, NB_INIT3 = 9, NB_WG1 = 10;

#define KV_MAP 0x543
#define KV_LATE 1
#define PF_KV 0
#define PF_G1 0
#define WS_PROMO CU_TENSOR_MAP_L2_PROMOTION_L2_128B
#define RAW_LATE 0
#define PF_RAW 0
#define SIDE_LD 4
#define SIDE_USE 0x554
#define REL_K 0
#define CS_WAIT 1
#define GELU_NB 8
#define H_ORD 0x73625410
#define W2_PF 7
#define H_FLY 8
#define TB2 2
#define X_A 2
#define FENCE_KIND 1
#define SCH 1
#define A_NB0 14
#define RED_GATE 2
#define SUM3 0
#define XP_KC 4
#define YP_N 4
#define LEAD_KC 1
#define LEAD_F 0
#define HOLD_KC 11
#define END_KC 13
#define REG_AUX "56"
#define REG_CON "224"
#define LDQ ".nc.L1::no_allocate"
#define LDP ""

__device__ __forceinline__ uint32_t s32(const void* p) { return (uint32_t)__cvta_generic_to_shared(p); }
__device__ __forceinline__ uint32_t clk() { uint32_t t; asm volatile("mov.u32 %0, %%clock;" : "=r"(t)); return t; }
__device__ __forceinline__ bool elect_one() {
  uint32_t p; asm volatile("{\n.reg .pred P;\nelect.sync _|P, 0xffffffff;\nselp.u32 %0, 1, 0, P;\n}" : "=r"(p)); return p;
}
#define ONE(...) do { if (elect_one()) { __VA_ARGS__; } __syncwarp(); } while (0)
__device__ __forceinline__ void mbar_init(uint32_t a, int c) { asm volatile("mbarrier.init.shared::cta.b64 [%0], %1;" ::"r"(a), "r"(c) : "memory"); }
__device__ __forceinline__ void mbar_expect(uint32_t a, int b) { asm volatile("mbarrier.arrive.expect_tx.shared::cta.b64 _, [%0], %1;" ::"r"(a), "r"(b) : "memory"); }
__device__ __forceinline__ void mbar_arrive(uint32_t a) { asm volatile("mbarrier.arrive.shared::cta.b64 _, [%0];" ::"r"(a) : "memory"); }
__device__ __forceinline__ bool spin_guard(uint32_t& n, uint32_t) {
  return ++n > (1u << 20);
}
__device__ __forceinline__ void mbar_wait(uint32_t a, int ph) {
  asm volatile("{\n.reg .pred p;\n.reg .u32 n;\nmov.u32 n, 0;\nW:\n.pragma \"nounroll\";\nmbarrier.try_wait.parity.shared::cta.b64 p, [%0], %1;\n"
               "add.u32 n, n, 1;\nsetp.ge.or.u32 p, n, 0x100000, p;\n@!p bra W;\n}" ::"r"(a), "r"(ph) : "memory");
}
__device__ __forceinline__ bool mbar_test(uint32_t a, int ph) {
  uint32_t ok;
  asm volatile("{\n.reg .pred p;\nmbarrier.test_wait.parity.shared::cta.b64 p, [%1], %2;\nselp.u32 %0, 1, 0, p;\n}" : "=r"(ok) : "r"(a), "r"(ph) : "memory");
  return __all_sync(0xffffffffu, ok);
}
__device__ __forceinline__ void sched_fence(uint32_t a) {
  asm volatile("{\n.reg .pred p;\nsetp.eq.u32 p, %0, 0;\n@p exit;\n}" ::"r"(a) : "memory");
}
__device__ __forceinline__ void tma2d(uint32_t dst, const CUtensorMap* tm, int c0, int c1, uint32_t bar) {
  asm volatile("cp.async.bulk.tensor.2d.shared::cluster.global.mbarrier::complete_tx::bytes [%0], [%1, {%3, %4}], [%2];"
               ::"r"(dst), "l"(tm), "r"(bar), "r"(c0), "r"(c1) : "memory");
}
__device__ __forceinline__ void tma3d(uint32_t dst, const CUtensorMap* tm, int c0, int c1, int c2, uint32_t bar) {
  asm volatile("cp.async.bulk.tensor.3d.shared::cluster.global.mbarrier::complete_tx::bytes [%0], [%1, {%3, %4, %5}], [%2];"
               ::"r"(dst), "l"(tm), "r"(bar), "r"(c0), "r"(c1), "r"(c2) : "memory");
}
__device__ __forceinline__ void tma2d_st(const CUtensorMap* tm, int c0, int c1, uint32_t src) {
  asm volatile("cp.async.bulk.tensor.2d.global.shared::cta.bulk_group [%0, {%2, %3}], [%1];" ::"l"(tm), "r"(src), "r"(c0), "r"(c1) : "memory");
}
__device__ __forceinline__ void tma3d_st(const CUtensorMap* tm, int c0, int c1, int c2, uint32_t src) {
  asm volatile("cp.async.bulk.tensor.3d.global.shared::cta.bulk_group [%0, {%2, %3, %4}], [%1];" ::"l"(tm), "r"(src), "r"(c0), "r"(c1), "r"(c2) : "memory");
}
__device__ __forceinline__ void bulk_g2s(uint32_t dst, const void* src, int bytes, uint32_t bar) {
  asm volatile("cp.async.bulk.shared::cluster.global.mbarrier::complete_tx::bytes [%0], [%1], %2, [%3];" ::"r"(dst), "l"(src), "r"(bytes), "r"(bar) : "memory");
}
__device__ __forceinline__ void bulk_commit() { asm volatile("cp.async.bulk.commit_group;" ::: "memory"); }
__device__ __forceinline__ void bulk_wait_read() { asm volatile("cp.async.bulk.wait_group.read 0;" ::: "memory"); }
__device__ __forceinline__ void bulk_wait_all() { asm volatile("cp.async.bulk.wait_group 0;" ::: "memory"); }
__device__ __forceinline__ void fence_async_smem() { asm volatile("fence.proxy.async.shared::cta;" ::: "memory"); }
__device__ __forceinline__ void fence_async_all() { asm volatile("fence.proxy.async;" ::: "memory"); }
__device__ __forceinline__ void fence_gpu() { asm volatile("fence.acq_rel.gpu;" ::: "memory"); }
#define bar_sync(id, n) asm volatile("bar.sync %0, %1;" ::"n"(id), "n"(n) : "memory")
#define bar_arrive(id, n) asm volatile("bar.arrive %0, %1;" ::"n"(id), "n"(n) : "memory")
__device__ __forceinline__ void wg_fence() { asm volatile("wgmma.fence.sync.aligned;" ::: "memory"); }
__device__ __forceinline__ void wg_commit() { asm volatile("wgmma.commit_group.sync.aligned;" ::: "memory"); }
template <int N> __device__ __forceinline__ void wg_wait() { asm volatile("wgmma.wait_group.sync.aligned %0;" ::"n"(N) : "memory"); }
__device__ __forceinline__ uint64_t mkdesc(uint32_t addr, uint32_t lbo, uint32_t sbo, int sw) {
  return (uint64_t)((addr & 0x3FFFF) >> 4) | ((uint64_t)(lbo >> 4) << 16) | ((uint64_t)(sbo >> 4) << 32) | ((uint64_t)sw << 62);
}
__device__ __forceinline__ uint32_t ldg32(const void* p) { uint32_t v; asm volatile("ld.global" LDQ ".b32 %0, [%1];" : "=r"(v) : "l"(p)); return v; }
template <int OFF> __device__ __forceinline__ uint32_t ldg32o(const void* p) { uint32_t v; asm volatile("ld.global" LDQ ".b32 %0, [%1+%2];" : "=r"(v) : "l"(p), "n"(OFF)); return v; }
template <int I> __device__ __forceinline__ void kv_loads(const void* kp, const void* vp, uint32_t (&kk)[16], uint32_t (&o)[16]) {
  kk[I] = ldg32o<I * DM * 2>(kp); o[I] = ldg32o<I * DM * 2>(vp);
  if constexpr (I < 15) kv_loads<I + 1>(kp, vp, kk, o);
}
__device__ __forceinline__ uint4 ldg128(const void* p) {
  uint4 v; asm volatile("ld.global" LDQ LDP ".v4.b32 {%0,%1,%2,%3}, [%4];" : "=r"(v.x), "=r"(v.y), "=r"(v.z), "=r"(v.w) : "l"(p)); return v;
}
__device__ __forceinline__ void stg128(void* p, uint32_t x, uint32_t y, uint32_t z, uint32_t w) {
  asm volatile("st.global.v4.b32 [%0], {%1,%2,%3,%4};" ::"l"(p), "r"(x), "r"(y), "r"(z), "r"(w) : "memory");
}
__device__ __forceinline__ uint4 ld_relaxed128(const void* p) {
  uint4 v; asm volatile("ld.relaxed.gpu.global.v4.b32 {%0,%1,%2,%3}, [%4];" : "=r"(v.x), "=r"(v.y), "=r"(v.z), "=r"(v.w) : "l"(p) : "memory"); return v;
}
__device__ __forceinline__ uint2 ld_relaxed64(const void* p) {
  uint2 v; asm volatile("ld.relaxed.gpu.global.v2.b32 {%0,%1}, [%2];" : "=r"(v.x), "=r"(v.y) : "l"(p) : "memory"); return v;
}
__device__ __forceinline__ uint4 ld_relaxed_b128(const void* p) {
  uint4 v; asm volatile("{\n.reg .b128 t;\nld.relaxed.gpu.global.b128 t, [%4];\nmov.b128 {%0,%1,%2,%3}, t;\n}" : "=r"(v.x), "=r"(v.y), "=r"(v.z), "=r"(v.w) : "l"(p) : "memory"); return v;
}
__device__ __forceinline__ void st_relaxed_b128(void* p, uint32_t x, uint32_t y, uint32_t z, uint32_t w) {
  asm volatile("{\n.reg .b128 t;\nmov.b128 t, {%1,%2,%3,%4};\nst.relaxed.gpu.global.b128 [%0], t;\n}" ::"l"(p), "r"(x), "r"(y), "r"(z), "r"(w) : "memory");
}
__device__ __forceinline__ void st_relaxed64(void* p, uint32_t x, uint32_t y) {
  asm volatile("{\n.reg .b64 t;\nmov.b64 t, {%1,%2};\nst.relaxed.gpu.global.b64 [%0], t;\n}" ::"l"(p), "r"(x), "r"(y) : "memory");
}
__device__ __forceinline__ void st_relaxed32(void* p, uint32_t x) { asm volatile("st.relaxed.gpu.global.b32 [%0], %1;" ::"l"(p), "r"(x) : "memory"); }
__device__ __forceinline__ uint32_t ld_relaxed32(const void* p) { uint32_t v; asm volatile("ld.relaxed.gpu.global.b32 %0, [%1];" : "=r"(v) : "l"(p) : "memory"); return v; }
__device__ __forceinline__ void st_relaxed128(void* p, uint32_t x, uint32_t y, uint32_t z, uint32_t w) {
  asm volatile("{\n.reg .b64 t, u;\nmov.b64 t, {%1,%2};\nmov.b64 u, {%3,%4};\nst.relaxed.gpu.global.v2.b64 [%0], {t, u};\n}" ::"l"(p), "r"(x), "r"(y), "r"(z), "r"(w) : "memory");
}
__device__ __forceinline__ void fence_release() { asm volatile("fence.proxy.async.global;\nfence.release.gpu;" ::: "memory"); }
__device__ __forceinline__ void fence_acquire() { asm volatile("fence.acquire.gpu;\nfence.proxy.async.global;" ::: "memory"); }
__device__ __forceinline__ void signal_cnt(int idx) { asm volatile("red.relaxed.gpu.global.add.u32 [%0], 1;" ::"l"(&g_cnt[idx * 32]) : "memory"); }
__device__ __forceinline__ void wait_cnt(int idx, unsigned target) {
  uint32_t n = 0;
#pragma unroll 1
  while (!__all_sync(0xffffffffu, (int)(ld_relaxed32(&g_cnt[idx * 32]) - target) >= 0)) {
    if (spin_guard(n, 0x100 + idx)) break;
  }
  fence_acquire();
}
__device__ __forceinline__ void bulk_s2g(void* dst, uint32_t src, int bytes) {
  asm volatile("cp.async.bulk.global.shared::cta.bulk_group [%0], [%1], %2;" ::"l"(dst), "r"(src), "r"(bytes) : "memory");
}
__device__ __forceinline__ void bulk_add_s2g(void* dst, uint32_t src, int bytes) {
  asm volatile("cp.reduce.async.bulk.global.shared::cta.bulk_group.add.noftz.bf16 [%0], [%1], %2;" ::"l"(dst), "r"(src), "r"(bytes) : "memory");
}
__device__ __forceinline__ void prefetch_l2(const void* p, int bytes) { asm volatile("cp.async.bulk.prefetch.L2.global [%0], %1;" ::"l"(p), "r"(bytes) : "memory"); }
__device__ __forceinline__ void prefetch_tile(const CUtensorMap* tm, int c0, int c1) {
  asm volatile("cp.async.bulk.prefetch.tensor.2d.L2.global.tile [%0, {%1, %2}];" ::"l"(tm), "r"(c0), "r"(c1) : "memory");
}
__device__ __forceinline__ void prefetch_map(const CUtensorMap* tm) { asm volatile("prefetch.tensormap [%0];" ::"l"(tm) : "memory"); }
__device__ __forceinline__ uint32_t pack_bf16(float lo, float hi) {
  uint32_t r; asm("cvt.rn.bf16x2.f32 %0, %1, %2;" : "=r"(r) : "f"(hi), "f"(lo)); return r;
}
__device__ __forceinline__ float bf_lo(uint32_t v) { return __uint_as_float(v << 16); }
__device__ __forceinline__ float bf_hi(uint32_t v) { return __uint_as_float(v & 0xFFFF0000u); }
__device__ __forceinline__ float bf_round(float x) { return __bfloat162float(__float2bfloat16_rn(x)); }
__device__ __forceinline__ uint32_t bmul2(uint32_t a, uint32_t b) { uint32_t r; asm("mul.rn.bf16x2 %0, %1, %2;" : "=r"(r) : "r"(a), "r"(b)); return r; }
__device__ __forceinline__ uint32_t bfma2(uint32_t a, uint32_t b, uint32_t c) { uint32_t r; asm("fma.rn.bf16x2 %0, %1, %2, %3;" : "=r"(r) : "r"(a), "r"(b), "r"(c)); return r; }
__device__ __forceinline__ uint32_t badd2(uint32_t a, uint32_t b) { uint32_t r; asm("add.rn.bf16x2 %0, %1, %2;" : "=r"(r) : "r"(a), "r"(b)); return r; }
__device__ __forceinline__ uint32_t bsub2(uint32_t a, uint32_t b) { uint32_t r; asm("sub.rn.bf16x2 %0, %1, %2;" : "=r"(r) : "r"(a), "r"(b)); return r; }
__device__ __forceinline__ float tanh_fast(float x) { float r; asm("tanh.approx.f32 %0, %1;" : "=f"(r) : "f"(x)); return r; }
__device__ __forceinline__ float rcp_fast(float x) { float r; asm("rcp.approx.ftz.f32 %0, %1;" : "=f"(r) : "f"(x)); return r; }
__device__ __forceinline__ float sqrt_fast(float x) { float r; asm("sqrt.approx.ftz.f32 %0, %1;" : "=f"(r) : "f"(x)); return r; }
__device__ __forceinline__ uint32_t lds32(uint32_t a) { uint32_t v; asm volatile("ld.shared.b32 %0, [%1];" : "=r"(v) : "r"(a)); return v; }
__device__ __forceinline__ uint4 lds128(uint32_t a) { uint4 v; asm volatile("ld.shared.v4.b32 {%0,%1,%2,%3}, [%4];" : "=r"(v.x), "=r"(v.y), "=r"(v.z), "=r"(v.w) : "r"(a)); return v; }
__device__ __forceinline__ float2 lds64f(uint32_t a) { float2 v; asm volatile("ld.shared.v2.f32 {%0,%1}, [%2];" : "=f"(v.x), "=f"(v.y) : "r"(a)); return v; }
__device__ __forceinline__ void sts64f(uint32_t a, float x, float y) { asm volatile("st.shared.v2.f32 [%0], {%1,%2};" ::"r"(a), "f"(x), "f"(y) : "memory"); }
__device__ __forceinline__ void sts32(uint32_t a, uint32_t x) { asm volatile("st.shared.b32 [%0], %1;" ::"r"(a), "r"(x) : "memory"); }
__device__ __forceinline__ void sts128(uint32_t a, uint32_t x, uint32_t y, uint32_t z, uint32_t w) { asm volatile("st.shared.v4.b32 [%0], {%1,%2,%3,%4};" ::"r"(a), "r"(x), "r"(y), "r"(z), "r"(w) : "memory"); }
__device__ __forceinline__ void stsm4(uint32_t a, uint32_t r0, uint32_t r1, uint32_t r2, uint32_t r3) {
  asm volatile("stmatrix.sync.aligned.m8n8.x4.shared.b16 [%0], {%1,%2,%3,%4};" ::"r"(a), "r"(r0), "r"(r1), "r"(r2), "r"(r3) : "memory");
}
__device__ __forceinline__ void stsm4t(uint32_t a, uint32_t r0, uint32_t r1, uint32_t r2, uint32_t r3) {
  asm volatile("stmatrix.sync.aligned.m8n8.x4.trans.shared.b16 [%0], {%1,%2,%3,%4};" ::"r"(a), "r"(r0), "r"(r1), "r"(r2), "r"(r3) : "memory");
}
__device__ __forceinline__ void stsm2(uint32_t a, uint32_t r0, uint32_t r1) {
  asm volatile("stmatrix.sync.aligned.m8n8.x2.shared.b16 [%0], {%1,%2};" ::"r"(a), "r"(r0), "r"(r1) : "memory");
}
__device__ __forceinline__ void ldsm4(uint32_t a, uint32_t& r0, uint32_t& r1, uint32_t& r2, uint32_t& r3) {
  asm volatile("ldmatrix.sync.aligned.m8n8.x4.shared.b16 {%0,%1,%2,%3}, [%4];" : "=r"(r0), "=r"(r1), "=r"(r2), "=r"(r3) : "r"(a) : "memory");
}
__device__ __forceinline__ void ldsm4t(uint32_t a, uint32_t& r0, uint32_t& r1, uint32_t& r2, uint32_t& r3) {
  asm volatile("ldmatrix.sync.aligned.m8n8.x4.trans.shared.b16 {%0,%1,%2,%3}, [%4];" : "=r"(r0), "=r"(r1), "=r"(r2), "=r"(r3) : "r"(a) : "memory");
}
__device__ __forceinline__ uint32_t mapa(uint32_t a, uint32_t rank) { uint32_t r; asm("mapa.shared::cluster.u32 %0, %1, %2;" : "=r"(r) : "r"(a), "r"(rank)); return r; }
__device__ __forceinline__ void mbar_arrive_remote(uint32_t a) { asm volatile("mbarrier.arrive.relaxed.cluster.shared::cluster.b64 _, [%0];" ::"r"(a) : "memory"); }
__device__ __forceinline__ void st_async128(uint32_t a, uint32_t x, uint32_t y, uint32_t z, uint32_t w, uint32_t bar) {
  asm volatile("st.async.weak.shared::cluster.mbarrier::complete_tx::bytes.v4.b32 [%0], {%1,%2,%3,%4}, [%5];" ::"r"(a), "r"(x), "r"(y), "r"(z), "r"(w), "r"(bar) : "memory");
}
#define TS(i)

#define TSKV
__device__ __forceinline__ void wg_ss_216(float (&d)[108], uint64_t da, uint64_t db, int sd) {
  asm volatile("{\n.reg .pred p;\nsetp.ne.b32 p, %110, 0;\n"
    "wgmma.mma_async.sync.aligned.m64n216k16.f32.bf16.bf16 {%0,%1,%2,%3,%4,%5,%6,%7,%8,%9,%10,%11,%12,%13,%14,%15,%16,%17,%18,%19,%20,%21,%22,%23,%24,%25,%26,%27,%28,%29,%30,%31,%32,%33,%34,%35,%36,%37,%38,%39,%40,%41,%42,%43,%44,%45,%46,%47,%48,%49,%50,%51,%52,%53,%54,%55,%56,%57,%58,%59,%60,%61,%62,%63,%64,%65,%66,%67,%68,%69,%70,%71,%72,%73,%74,%75,%76,%77,%78,%79,%80,%81,%82,%83,%84,%85,%86,%87,%88,%89,%90,%91,%92,%93,%94,%95,%96,%97,%98,%99,%100,%101,%102,%103,%104,%105,%106,%107}, %108, %109, p, 1, 1, 0, 1;\n}\n"
    : "+f"(d[0]),"+f"(d[1]),"+f"(d[2]),"+f"(d[3]),"+f"(d[4]),"+f"(d[5]),"+f"(d[6]),"+f"(d[7]),"+f"(d[8]),"+f"(d[9]),"+f"(d[10]),"+f"(d[11]),"+f"(d[12]),"+f"(d[13]),"+f"(d[14]),"+f"(d[15]),"+f"(d[16]),"+f"(d[17]),"+f"(d[18]),"+f"(d[19]),"+f"(d[20]),"+f"(d[21]),"+f"(d[22]),"+f"(d[23]),"+f"(d[24]),"+f"(d[25]),"+f"(d[26]),"+f"(d[27]),"+f"(d[28]),"+f"(d[29]),"+f"(d[30]),"+f"(d[31]),"+f"(d[32]),"+f"(d[33]),"+f"(d[34]),"+f"(d[35]),"+f"(d[36]),"+f"(d[37]),"+f"(d[38]),"+f"(d[39]),"+f"(d[40]),"+f"(d[41]),"+f"(d[42]),"+f"(d[43]),"+f"(d[44]),"+f"(d[45]),"+f"(d[46]),"+f"(d[47]),"+f"(d[48]),"+f"(d[49]),"+f"(d[50]),"+f"(d[51]),"+f"(d[52]),"+f"(d[53]),"+f"(d[54]),"+f"(d[55]),"+f"(d[56]),"+f"(d[57]),"+f"(d[58]),"+f"(d[59]),"+f"(d[60]),"+f"(d[61]),"+f"(d[62]),"+f"(d[63]),"+f"(d[64]),"+f"(d[65]),"+f"(d[66]),"+f"(d[67]),"+f"(d[68]),"+f"(d[69]),"+f"(d[70]),"+f"(d[71]),"+f"(d[72]),"+f"(d[73]),"+f"(d[74]),"+f"(d[75]),"+f"(d[76]),"+f"(d[77]),"+f"(d[78]),"+f"(d[79]),"+f"(d[80]),"+f"(d[81]),"+f"(d[82]),"+f"(d[83]),"+f"(d[84]),"+f"(d[85]),"+f"(d[86]),"+f"(d[87]),"+f"(d[88]),"+f"(d[89]),"+f"(d[90]),"+f"(d[91]),"+f"(d[92]),"+f"(d[93]),"+f"(d[94]),"+f"(d[95]),"+f"(d[96]),"+f"(d[97]),"+f"(d[98]),"+f"(d[99]),"+f"(d[100]),"+f"(d[101]),"+f"(d[102]),"+f"(d[103]),"+f"(d[104]),"+f"(d[105]),"+f"(d[106]),"+f"(d[107]) : "l"(da), "l"(db), "r"(sd));
}
__device__ __forceinline__ void wg_ss_160(float (&d)[80], uint64_t da, uint64_t db, int sd) {
  asm volatile("{\n.reg .pred p;\nsetp.ne.b32 p, %82, 0;\n"
    "wgmma.mma_async.sync.aligned.m64n160k16.f32.bf16.bf16 {%0,%1,%2,%3,%4,%5,%6,%7,%8,%9,%10,%11,%12,%13,%14,%15,%16,%17,%18,%19,%20,%21,%22,%23,%24,%25,%26,%27,%28,%29,%30,%31,%32,%33,%34,%35,%36,%37,%38,%39,%40,%41,%42,%43,%44,%45,%46,%47,%48,%49,%50,%51,%52,%53,%54,%55,%56,%57,%58,%59,%60,%61,%62,%63,%64,%65,%66,%67,%68,%69,%70,%71,%72,%73,%74,%75,%76,%77,%78,%79}, %80, %81, p, 1, 1, 0, 1;\n}\n"
    : "+f"(d[0]),"+f"(d[1]),"+f"(d[2]),"+f"(d[3]),"+f"(d[4]),"+f"(d[5]),"+f"(d[6]),"+f"(d[7]),"+f"(d[8]),"+f"(d[9]),"+f"(d[10]),"+f"(d[11]),"+f"(d[12]),"+f"(d[13]),"+f"(d[14]),"+f"(d[15]),"+f"(d[16]),"+f"(d[17]),"+f"(d[18]),"+f"(d[19]),"+f"(d[20]),"+f"(d[21]),"+f"(d[22]),"+f"(d[23]),"+f"(d[24]),"+f"(d[25]),"+f"(d[26]),"+f"(d[27]),"+f"(d[28]),"+f"(d[29]),"+f"(d[30]),"+f"(d[31]),"+f"(d[32]),"+f"(d[33]),"+f"(d[34]),"+f"(d[35]),"+f"(d[36]),"+f"(d[37]),"+f"(d[38]),"+f"(d[39]),"+f"(d[40]),"+f"(d[41]),"+f"(d[42]),"+f"(d[43]),"+f"(d[44]),"+f"(d[45]),"+f"(d[46]),"+f"(d[47]),"+f"(d[48]),"+f"(d[49]),"+f"(d[50]),"+f"(d[51]),"+f"(d[52]),"+f"(d[53]),"+f"(d[54]),"+f"(d[55]),"+f"(d[56]),"+f"(d[57]),"+f"(d[58]),"+f"(d[59]),"+f"(d[60]),"+f"(d[61]),"+f"(d[62]),"+f"(d[63]),"+f"(d[64]),"+f"(d[65]),"+f"(d[66]),"+f"(d[67]),"+f"(d[68]),"+f"(d[69]),"+f"(d[70]),"+f"(d[71]),"+f"(d[72]),"+f"(d[73]),"+f"(d[74]),"+f"(d[75]),"+f"(d[76]),"+f"(d[77]),"+f"(d[78]),"+f"(d[79]) : "l"(da), "l"(db), "r"(sd));
}
__device__ __forceinline__ void wg_rs_216(float (&d)[108], uint32_t a0, uint32_t a1, uint32_t a2, uint32_t a3, uint64_t db) {
  asm volatile("{\n.reg .pred p;\nsetp.ne.b32 p, 1, 0;\n"
    "wgmma.mma_async.sync.aligned.m64n216k16.f32.bf16.bf16 {%0,%1,%2,%3,%4,%5,%6,%7,%8,%9,%10,%11,%12,%13,%14,%15,%16,%17,%18,%19,%20,%21,%22,%23,%24,%25,%26,%27,%28,%29,%30,%31,%32,%33,%34,%35,%36,%37,%38,%39,%40,%41,%42,%43,%44,%45,%46,%47,%48,%49,%50,%51,%52,%53,%54,%55,%56,%57,%58,%59,%60,%61,%62,%63,%64,%65,%66,%67,%68,%69,%70,%71,%72,%73,%74,%75,%76,%77,%78,%79,%80,%81,%82,%83,%84,%85,%86,%87,%88,%89,%90,%91,%92,%93,%94,%95,%96,%97,%98,%99,%100,%101,%102,%103,%104,%105,%106,%107}, {%108,%109,%110,%111}, %112, p, 1, 1, 1;\n}\n"
    : "+f"(d[0]),"+f"(d[1]),"+f"(d[2]),"+f"(d[3]),"+f"(d[4]),"+f"(d[5]),"+f"(d[6]),"+f"(d[7]),"+f"(d[8]),"+f"(d[9]),"+f"(d[10]),"+f"(d[11]),"+f"(d[12]),"+f"(d[13]),"+f"(d[14]),"+f"(d[15]),"+f"(d[16]),"+f"(d[17]),"+f"(d[18]),"+f"(d[19]),"+f"(d[20]),"+f"(d[21]),"+f"(d[22]),"+f"(d[23]),"+f"(d[24]),"+f"(d[25]),"+f"(d[26]),"+f"(d[27]),"+f"(d[28]),"+f"(d[29]),"+f"(d[30]),"+f"(d[31]),"+f"(d[32]),"+f"(d[33]),"+f"(d[34]),"+f"(d[35]),"+f"(d[36]),"+f"(d[37]),"+f"(d[38]),"+f"(d[39]),"+f"(d[40]),"+f"(d[41]),"+f"(d[42]),"+f"(d[43]),"+f"(d[44]),"+f"(d[45]),"+f"(d[46]),"+f"(d[47]),"+f"(d[48]),"+f"(d[49]),"+f"(d[50]),"+f"(d[51]),"+f"(d[52]),"+f"(d[53]),"+f"(d[54]),"+f"(d[55]),"+f"(d[56]),"+f"(d[57]),"+f"(d[58]),"+f"(d[59]),"+f"(d[60]),"+f"(d[61]),"+f"(d[62]),"+f"(d[63]),"+f"(d[64]),"+f"(d[65]),"+f"(d[66]),"+f"(d[67]),"+f"(d[68]),"+f"(d[69]),"+f"(d[70]),"+f"(d[71]),"+f"(d[72]),"+f"(d[73]),"+f"(d[74]),"+f"(d[75]),"+f"(d[76]),"+f"(d[77]),"+f"(d[78]),"+f"(d[79]),"+f"(d[80]),"+f"(d[81]),"+f"(d[82]),"+f"(d[83]),"+f"(d[84]),"+f"(d[85]),"+f"(d[86]),"+f"(d[87]),"+f"(d[88]),"+f"(d[89]),"+f"(d[90]),"+f"(d[91]),"+f"(d[92]),"+f"(d[93]),"+f"(d[94]),"+f"(d[95]),"+f"(d[96]),"+f"(d[97]),"+f"(d[98]),"+f"(d[99]),"+f"(d[100]),"+f"(d[101]),"+f"(d[102]),"+f"(d[103]),"+f"(d[104]),"+f"(d[105]),"+f"(d[106]),"+f"(d[107]) : "r"(a0), "r"(a1), "r"(a2), "r"(a3), "l"(db));
}
__device__ __forceinline__ void wg_cv_0_0(float (&d)[128], uint32_t a0, uint32_t a1, uint32_t a2, uint32_t a3, uint64_t db) {
  asm volatile("{\n.reg .pred p;\nsetp.ne.b32 p, 0, 0;\n"
    "wgmma.mma_async.sync.aligned.m64n32k16.f32.bf16.bf16 {%0,%1,%2,%3,%4,%5,%6,%7,%8,%9,%10,%11,%12,%13,%14,%15}, {%16,%17,%18,%19}, %20, p, 1, 1, 0;\n}\n"
    : "+f"(d[0]),"+f"(d[1]),"+f"(d[2]),"+f"(d[3]),"+f"(d[4]),"+f"(d[5]),"+f"(d[6]),"+f"(d[7]),"+f"(d[8]),"+f"(d[9]),"+f"(d[10]),"+f"(d[11]),"+f"(d[12]),"+f"(d[13]),"+f"(d[14]),"+f"(d[15]) : "r"(a0), "r"(a1), "r"(a2), "r"(a3), "l"(db));
}
__device__ __forceinline__ void wg_cv_0_1(float (&d)[128], uint32_t a0, uint32_t a1, uint32_t a2, uint32_t a3, uint64_t db) {
  asm volatile("{\n.reg .pred p;\nsetp.ne.b32 p, 1, 0;\n"
    "wgmma.mma_async.sync.aligned.m64n32k16.f32.bf16.bf16 {%0,%1,%2,%3,%4,%5,%6,%7,%8,%9,%10,%11,%12,%13,%14,%15}, {%16,%17,%18,%19}, %20, p, 1, 1, 0;\n}\n"
    : "+f"(d[0]),"+f"(d[1]),"+f"(d[2]),"+f"(d[3]),"+f"(d[4]),"+f"(d[5]),"+f"(d[6]),"+f"(d[7]),"+f"(d[8]),"+f"(d[9]),"+f"(d[10]),"+f"(d[11]),"+f"(d[12]),"+f"(d[13]),"+f"(d[14]),"+f"(d[15]) : "r"(a0), "r"(a1), "r"(a2), "r"(a3), "l"(db));
}
__device__ __forceinline__ void wg_cv_1_0(float (&d)[128], uint32_t a0, uint32_t a1, uint32_t a2, uint32_t a3, uint64_t db) {
  asm volatile("{\n.reg .pred p;\nsetp.ne.b32 p, 0, 0;\n"
    "wgmma.mma_async.sync.aligned.m64n32k16.f32.bf16.bf16 {%0,%1,%2,%3,%4,%5,%6,%7,%8,%9,%10,%11,%12,%13,%14,%15}, {%16,%17,%18,%19}, %20, p, 1, 1, 0;\n}\n"
    : "+f"(d[16]),"+f"(d[17]),"+f"(d[18]),"+f"(d[19]),"+f"(d[20]),"+f"(d[21]),"+f"(d[22]),"+f"(d[23]),"+f"(d[24]),"+f"(d[25]),"+f"(d[26]),"+f"(d[27]),"+f"(d[28]),"+f"(d[29]),"+f"(d[30]),"+f"(d[31]) : "r"(a0), "r"(a1), "r"(a2), "r"(a3), "l"(db));
}
__device__ __forceinline__ void wg_cv_1_1(float (&d)[128], uint32_t a0, uint32_t a1, uint32_t a2, uint32_t a3, uint64_t db) {
  asm volatile("{\n.reg .pred p;\nsetp.ne.b32 p, 1, 0;\n"
    "wgmma.mma_async.sync.aligned.m64n32k16.f32.bf16.bf16 {%0,%1,%2,%3,%4,%5,%6,%7,%8,%9,%10,%11,%12,%13,%14,%15}, {%16,%17,%18,%19}, %20, p, 1, 1, 0;\n}\n"
    : "+f"(d[16]),"+f"(d[17]),"+f"(d[18]),"+f"(d[19]),"+f"(d[20]),"+f"(d[21]),"+f"(d[22]),"+f"(d[23]),"+f"(d[24]),"+f"(d[25]),"+f"(d[26]),"+f"(d[27]),"+f"(d[28]),"+f"(d[29]),"+f"(d[30]),"+f"(d[31]) : "r"(a0), "r"(a1), "r"(a2), "r"(a3), "l"(db));
}
__device__ __forceinline__ void wg_cv_2_0(float (&d)[128], uint32_t a0, uint32_t a1, uint32_t a2, uint32_t a3, uint64_t db) {
  asm volatile("{\n.reg .pred p;\nsetp.ne.b32 p, 0, 0;\n"
    "wgmma.mma_async.sync.aligned.m64n32k16.f32.bf16.bf16 {%0,%1,%2,%3,%4,%5,%6,%7,%8,%9,%10,%11,%12,%13,%14,%15}, {%16,%17,%18,%19}, %20, p, 1, 1, 0;\n}\n"
    : "+f"(d[32]),"+f"(d[33]),"+f"(d[34]),"+f"(d[35]),"+f"(d[36]),"+f"(d[37]),"+f"(d[38]),"+f"(d[39]),"+f"(d[40]),"+f"(d[41]),"+f"(d[42]),"+f"(d[43]),"+f"(d[44]),"+f"(d[45]),"+f"(d[46]),"+f"(d[47]) : "r"(a0), "r"(a1), "r"(a2), "r"(a3), "l"(db));
}
__device__ __forceinline__ void wg_cv_2_1(float (&d)[128], uint32_t a0, uint32_t a1, uint32_t a2, uint32_t a3, uint64_t db) {
  asm volatile("{\n.reg .pred p;\nsetp.ne.b32 p, 1, 0;\n"
    "wgmma.mma_async.sync.aligned.m64n32k16.f32.bf16.bf16 {%0,%1,%2,%3,%4,%5,%6,%7,%8,%9,%10,%11,%12,%13,%14,%15}, {%16,%17,%18,%19}, %20, p, 1, 1, 0;\n}\n"
    : "+f"(d[32]),"+f"(d[33]),"+f"(d[34]),"+f"(d[35]),"+f"(d[36]),"+f"(d[37]),"+f"(d[38]),"+f"(d[39]),"+f"(d[40]),"+f"(d[41]),"+f"(d[42]),"+f"(d[43]),"+f"(d[44]),"+f"(d[45]),"+f"(d[46]),"+f"(d[47]) : "r"(a0), "r"(a1), "r"(a2), "r"(a3), "l"(db));
}
__device__ __forceinline__ void wg_cv_3_0(float (&d)[128], uint32_t a0, uint32_t a1, uint32_t a2, uint32_t a3, uint64_t db) {
  asm volatile("{\n.reg .pred p;\nsetp.ne.b32 p, 0, 0;\n"
    "wgmma.mma_async.sync.aligned.m64n32k16.f32.bf16.bf16 {%0,%1,%2,%3,%4,%5,%6,%7,%8,%9,%10,%11,%12,%13,%14,%15}, {%16,%17,%18,%19}, %20, p, 1, 1, 0;\n}\n"
    : "+f"(d[48]),"+f"(d[49]),"+f"(d[50]),"+f"(d[51]),"+f"(d[52]),"+f"(d[53]),"+f"(d[54]),"+f"(d[55]),"+f"(d[56]),"+f"(d[57]),"+f"(d[58]),"+f"(d[59]),"+f"(d[60]),"+f"(d[61]),"+f"(d[62]),"+f"(d[63]) : "r"(a0), "r"(a1), "r"(a2), "r"(a3), "l"(db));
}
__device__ __forceinline__ void wg_cv_3_1(float (&d)[128], uint32_t a0, uint32_t a1, uint32_t a2, uint32_t a3, uint64_t db) {
  asm volatile("{\n.reg .pred p;\nsetp.ne.b32 p, 1, 0;\n"
    "wgmma.mma_async.sync.aligned.m64n32k16.f32.bf16.bf16 {%0,%1,%2,%3,%4,%5,%6,%7,%8,%9,%10,%11,%12,%13,%14,%15}, {%16,%17,%18,%19}, %20, p, 1, 1, 0;\n}\n"
    : "+f"(d[48]),"+f"(d[49]),"+f"(d[50]),"+f"(d[51]),"+f"(d[52]),"+f"(d[53]),"+f"(d[54]),"+f"(d[55]),"+f"(d[56]),"+f"(d[57]),"+f"(d[58]),"+f"(d[59]),"+f"(d[60]),"+f"(d[61]),"+f"(d[62]),"+f"(d[63]) : "r"(a0), "r"(a1), "r"(a2), "r"(a3), "l"(db));
}
__device__ __forceinline__ void wg_cv_4_0(float (&d)[128], uint32_t a0, uint32_t a1, uint32_t a2, uint32_t a3, uint64_t db) {
  asm volatile("{\n.reg .pred p;\nsetp.ne.b32 p, 0, 0;\n"
    "wgmma.mma_async.sync.aligned.m64n32k16.f32.bf16.bf16 {%0,%1,%2,%3,%4,%5,%6,%7,%8,%9,%10,%11,%12,%13,%14,%15}, {%16,%17,%18,%19}, %20, p, 1, 1, 0;\n}\n"
    : "+f"(d[64]),"+f"(d[65]),"+f"(d[66]),"+f"(d[67]),"+f"(d[68]),"+f"(d[69]),"+f"(d[70]),"+f"(d[71]),"+f"(d[72]),"+f"(d[73]),"+f"(d[74]),"+f"(d[75]),"+f"(d[76]),"+f"(d[77]),"+f"(d[78]),"+f"(d[79]) : "r"(a0), "r"(a1), "r"(a2), "r"(a3), "l"(db));
}
__device__ __forceinline__ void wg_cv_4_1(float (&d)[128], uint32_t a0, uint32_t a1, uint32_t a2, uint32_t a3, uint64_t db) {
  asm volatile("{\n.reg .pred p;\nsetp.ne.b32 p, 1, 0;\n"
    "wgmma.mma_async.sync.aligned.m64n32k16.f32.bf16.bf16 {%0,%1,%2,%3,%4,%5,%6,%7,%8,%9,%10,%11,%12,%13,%14,%15}, {%16,%17,%18,%19}, %20, p, 1, 1, 0;\n}\n"
    : "+f"(d[64]),"+f"(d[65]),"+f"(d[66]),"+f"(d[67]),"+f"(d[68]),"+f"(d[69]),"+f"(d[70]),"+f"(d[71]),"+f"(d[72]),"+f"(d[73]),"+f"(d[74]),"+f"(d[75]),"+f"(d[76]),"+f"(d[77]),"+f"(d[78]),"+f"(d[79]) : "r"(a0), "r"(a1), "r"(a2), "r"(a3), "l"(db));
}
__device__ __forceinline__ void wg_cv_5_0(float (&d)[128], uint32_t a0, uint32_t a1, uint32_t a2, uint32_t a3, uint64_t db) {
  asm volatile("{\n.reg .pred p;\nsetp.ne.b32 p, 0, 0;\n"
    "wgmma.mma_async.sync.aligned.m64n32k16.f32.bf16.bf16 {%0,%1,%2,%3,%4,%5,%6,%7,%8,%9,%10,%11,%12,%13,%14,%15}, {%16,%17,%18,%19}, %20, p, 1, 1, 0;\n}\n"
    : "+f"(d[80]),"+f"(d[81]),"+f"(d[82]),"+f"(d[83]),"+f"(d[84]),"+f"(d[85]),"+f"(d[86]),"+f"(d[87]),"+f"(d[88]),"+f"(d[89]),"+f"(d[90]),"+f"(d[91]),"+f"(d[92]),"+f"(d[93]),"+f"(d[94]),"+f"(d[95]) : "r"(a0), "r"(a1), "r"(a2), "r"(a3), "l"(db));
}
__device__ __forceinline__ void wg_cv_5_1(float (&d)[128], uint32_t a0, uint32_t a1, uint32_t a2, uint32_t a3, uint64_t db) {
  asm volatile("{\n.reg .pred p;\nsetp.ne.b32 p, 1, 0;\n"
    "wgmma.mma_async.sync.aligned.m64n32k16.f32.bf16.bf16 {%0,%1,%2,%3,%4,%5,%6,%7,%8,%9,%10,%11,%12,%13,%14,%15}, {%16,%17,%18,%19}, %20, p, 1, 1, 0;\n}\n"
    : "+f"(d[80]),"+f"(d[81]),"+f"(d[82]),"+f"(d[83]),"+f"(d[84]),"+f"(d[85]),"+f"(d[86]),"+f"(d[87]),"+f"(d[88]),"+f"(d[89]),"+f"(d[90]),"+f"(d[91]),"+f"(d[92]),"+f"(d[93]),"+f"(d[94]),"+f"(d[95]) : "r"(a0), "r"(a1), "r"(a2), "r"(a3), "l"(db));
}
__device__ __forceinline__ void wg_cv_6_0(float (&d)[128], uint32_t a0, uint32_t a1, uint32_t a2, uint32_t a3, uint64_t db) {
  asm volatile("{\n.reg .pred p;\nsetp.ne.b32 p, 0, 0;\n"
    "wgmma.mma_async.sync.aligned.m64n32k16.f32.bf16.bf16 {%0,%1,%2,%3,%4,%5,%6,%7,%8,%9,%10,%11,%12,%13,%14,%15}, {%16,%17,%18,%19}, %20, p, 1, 1, 0;\n}\n"
    : "+f"(d[96]),"+f"(d[97]),"+f"(d[98]),"+f"(d[99]),"+f"(d[100]),"+f"(d[101]),"+f"(d[102]),"+f"(d[103]),"+f"(d[104]),"+f"(d[105]),"+f"(d[106]),"+f"(d[107]),"+f"(d[108]),"+f"(d[109]),"+f"(d[110]),"+f"(d[111]) : "r"(a0), "r"(a1), "r"(a2), "r"(a3), "l"(db));
}
__device__ __forceinline__ void wg_cv_6_1(float (&d)[128], uint32_t a0, uint32_t a1, uint32_t a2, uint32_t a3, uint64_t db) {
  asm volatile("{\n.reg .pred p;\nsetp.ne.b32 p, 1, 0;\n"
    "wgmma.mma_async.sync.aligned.m64n32k16.f32.bf16.bf16 {%0,%1,%2,%3,%4,%5,%6,%7,%8,%9,%10,%11,%12,%13,%14,%15}, {%16,%17,%18,%19}, %20, p, 1, 1, 0;\n}\n"
    : "+f"(d[96]),"+f"(d[97]),"+f"(d[98]),"+f"(d[99]),"+f"(d[100]),"+f"(d[101]),"+f"(d[102]),"+f"(d[103]),"+f"(d[104]),"+f"(d[105]),"+f"(d[106]),"+f"(d[107]),"+f"(d[108]),"+f"(d[109]),"+f"(d[110]),"+f"(d[111]) : "r"(a0), "r"(a1), "r"(a2), "r"(a3), "l"(db));
}
__device__ __forceinline__ void wg_cv_7_0(float (&d)[128], uint32_t a0, uint32_t a1, uint32_t a2, uint32_t a3, uint64_t db) {
  asm volatile("{\n.reg .pred p;\nsetp.ne.b32 p, 0, 0;\n"
    "wgmma.mma_async.sync.aligned.m64n32k16.f32.bf16.bf16 {%0,%1,%2,%3,%4,%5,%6,%7,%8,%9,%10,%11,%12,%13,%14,%15}, {%16,%17,%18,%19}, %20, p, 1, 1, 0;\n}\n"
    : "+f"(d[112]),"+f"(d[113]),"+f"(d[114]),"+f"(d[115]),"+f"(d[116]),"+f"(d[117]),"+f"(d[118]),"+f"(d[119]),"+f"(d[120]),"+f"(d[121]),"+f"(d[122]),"+f"(d[123]),"+f"(d[124]),"+f"(d[125]),"+f"(d[126]),"+f"(d[127]) : "r"(a0), "r"(a1), "r"(a2), "r"(a3), "l"(db));
}
__device__ __forceinline__ void wg_cv_7_1(float (&d)[128], uint32_t a0, uint32_t a1, uint32_t a2, uint32_t a3, uint64_t db) {
  asm volatile("{\n.reg .pred p;\nsetp.ne.b32 p, 1, 0;\n"
    "wgmma.mma_async.sync.aligned.m64n32k16.f32.bf16.bf16 {%0,%1,%2,%3,%4,%5,%6,%7,%8,%9,%10,%11,%12,%13,%14,%15}, {%16,%17,%18,%19}, %20, p, 1, 1, 0;\n}\n"
    : "+f"(d[112]),"+f"(d[113]),"+f"(d[114]),"+f"(d[115]),"+f"(d[116]),"+f"(d[117]),"+f"(d[118]),"+f"(d[119]),"+f"(d[120]),"+f"(d[121]),"+f"(d[122]),"+f"(d[123]),"+f"(d[124]),"+f"(d[125]),"+f"(d[126]),"+f"(d[127]) : "r"(a0), "r"(a1), "r"(a2), "r"(a3), "l"(db));
}
template <class F> __device__ __forceinline__ void conv_chain_1(float (&d)[128], uint32_t (&a)[64], uint64_t db, uint32_t ab, F hand) {
  wg_cv_7_0(d, a[60], a[61], a[62], a[63], db + (uint64_t)(0));
  wg_cv_6_0(d, a[52], a[53], a[54], a[55], db + (uint64_t)(0));
  wg_cv_7_1(d, a[56], a[57], a[58], a[59], db + (uint64_t)(16));
  wg_cv_5_0(d, a[44], a[45], a[46], a[47], db + (uint64_t)(0));
  wg_cv_6_1(d, a[48], a[49], a[50], a[51], db + (uint64_t)(16));
  wg_cv_7_1(d, a[52], a[53], a[54], a[55], db + (uint64_t)(32));
  wg_cv_5_1(d, a[40], a[41], a[42], a[43], db + (uint64_t)(16));
  wg_cv_6_1(d, a[44], a[45], a[46], a[47], db + (uint64_t)(32));
  wg_cv_7_1(d, a[48], a[49], a[50], a[51], db + (uint64_t)(48));
  wg_cv_6_1(d, a[40], a[41], a[42], a[43], db + (uint64_t)(48));
  wg_cv_7_1(d, a[44], a[45], a[46], a[47], db + (uint64_t)(64));
  wg_cv_7_1(d, a[40], a[41], a[42], a[43], db + (uint64_t)(80));
  wg_commit();
  wg_cv_7_1(d, a[36], a[37], a[38], a[39], db + (uint64_t)(96));
  wg_cv_6_1(d, a[36], a[37], a[38], a[39], db + (uint64_t)(64));
  wg_cv_5_1(d, a[36], a[37], a[38], a[39], db + (uint64_t)(32));
  wg_cv_4_0(d, a[36], a[37], a[38], a[39], db + (uint64_t)(0));
  wg_commit(); wg_wait<1>();
  wg_cv_7_1(d, a[32], a[33], a[34], a[35], db + (uint64_t)(112));
  wg_cv_6_1(d, a[32], a[33], a[34], a[35], db + (uint64_t)(80));
  wg_cv_5_1(d, a[32], a[33], a[34], a[35], db + (uint64_t)(48));
  a[60] = lds32(ab + (3840));
  a[61] = lds32(ab + (3968));
  a[62] = lds32(ab + (3824));
  a[63] = lds32(ab + (3952));
  wg_cv_4_1(d, a[32], a[33], a[34], a[35], db + (uint64_t)(16));
  wg_cv_7_1(d, a[28], a[29], a[30], a[31], db + (uint64_t)(128));
  wg_cv_6_1(d, a[28], a[29], a[30], a[31], db + (uint64_t)(96));
  wg_cv_5_1(d, a[28], a[29], a[30], a[31], db + (uint64_t)(64));
  a[56] = lds32(ab + (3584));
  a[57] = lds32(ab + (3712));
  a[58] = lds32(ab + (3568));
  a[59] = lds32(ab + (3696));
  wg_cv_4_1(d, a[28], a[29], a[30], a[31], db + (uint64_t)(32));
  wg_cv_3_0(d, a[28], a[29], a[30], a[31], db + (uint64_t)(0));
  wg_cv_7_1(d, a[24], a[25], a[26], a[27], db + (uint64_t)(144));
  wg_cv_6_1(d, a[24], a[25], a[26], a[27], db + (uint64_t)(112));
  a[52] = lds32(ab + (3328));
  a[53] = lds32(ab + (3456));
  a[54] = lds32(ab + (3312));
  a[55] = lds32(ab + (3440));
  wg_cv_5_1(d, a[24], a[25], a[26], a[27], db + (uint64_t)(80));
  wg_cv_4_1(d, a[24], a[25], a[26], a[27], db + (uint64_t)(48));
  wg_cv_3_1(d, a[24], a[25], a[26], a[27], db + (uint64_t)(16));
  wg_commit();
  wg_cv_7_1(d, a[20], a[21], a[22], a[23], db + (uint64_t)(160));
  wg_cv_6_1(d, a[20], a[21], a[22], a[23], db + (uint64_t)(128));
  wg_cv_5_1(d, a[20], a[21], a[22], a[23], db + (uint64_t)(96));
  wg_cv_4_1(d, a[20], a[21], a[22], a[23], db + (uint64_t)(64));
  wg_commit(); wg_wait<1>();
  a[48] = lds32(ab + (3072));
  a[49] = lds32(ab + (3200));
  a[50] = lds32(ab + (3056));
  a[51] = lds32(ab + (3184));
  wg_cv_3_1(d, a[20], a[21], a[22], a[23], db + (uint64_t)(32));
  wg_cv_2_0(d, a[20], a[21], a[22], a[23], db + (uint64_t)(0));
  wg_cv_7_1(d, a[16], a[17], a[18], a[19], db + (uint64_t)(176));
  wg_cv_6_1(d, a[16], a[17], a[18], a[19], db + (uint64_t)(144));
  a[44] = lds32(ab + (2816));
  a[45] = lds32(ab + (2944));
  a[46] = lds32(ab + (2800));
  a[47] = lds32(ab + (2928));
  wg_cv_5_1(d, a[16], a[17], a[18], a[19], db + (uint64_t)(112));
  wg_cv_4_1(d, a[16], a[17], a[18], a[19], db + (uint64_t)(80));
  wg_cv_3_1(d, a[16], a[17], a[18], a[19], db + (uint64_t)(48));
  wg_cv_2_1(d, a[16], a[17], a[18], a[19], db + (uint64_t)(16));
  a[40] = lds32(ab + (2560));
  a[41] = lds32(ab + (2688));
  a[42] = lds32(ab + (2544));
  a[43] = lds32(ab + (2672));
  wg_cv_7_1(d, a[12], a[13], a[14], a[15], db + (uint64_t)(192));
  wg_cv_6_1(d, a[12], a[13], a[14], a[15], db + (uint64_t)(160));
  wg_cv_5_1(d, a[12], a[13], a[14], a[15], db + (uint64_t)(128));
  wg_cv_4_1(d, a[12], a[13], a[14], a[15], db + (uint64_t)(96));
  a[36] = lds32(ab + (2304));
  a[37] = lds32(ab + (2432));
  a[38] = lds32(ab + (2288));
  a[39] = lds32(ab + (2416));
  wg_cv_3_1(d, a[12], a[13], a[14], a[15], db + (uint64_t)(64));
  wg_cv_2_1(d, a[12], a[13], a[14], a[15], db + (uint64_t)(32));
  wg_cv_1_0(d, a[12], a[13], a[14], a[15], db + (uint64_t)(0));
  wg_cv_7_1(d, a[8], a[9], a[10], a[11], db + (uint64_t)(208));
  a[32] = lds32(ab + (2048));
  a[33] = lds32(ab + (2176));
  a[34] = lds32(ab + (2032));
  a[35] = lds32(ab + (2160));
  wg_cv_6_1(d, a[8], a[9], a[10], a[11], db + (uint64_t)(176));
  wg_cv_5_1(d, a[8], a[9], a[10], a[11], db + (uint64_t)(144));
  wg_cv_4_1(d, a[8], a[9], a[10], a[11], db + (uint64_t)(112));
  wg_cv_3_1(d, a[8], a[9], a[10], a[11], db + (uint64_t)(80));
  a[28] = lds32(ab + (1792));
  a[29] = lds32(ab + (1920));
  a[30] = lds32(ab + (1776));
  a[31] = lds32(ab + (1904));
  wg_cv_2_1(d, a[8], a[9], a[10], a[11], db + (uint64_t)(48));
  wg_cv_1_1(d, a[8], a[9], a[10], a[11], db + (uint64_t)(16));
  wg_commit();
  wg_cv_7_1(d, a[4], a[5], a[6], a[7], db + (uint64_t)(224));
  wg_cv_6_1(d, a[4], a[5], a[6], a[7], db + (uint64_t)(192));
  wg_cv_5_1(d, a[4], a[5], a[6], a[7], db + (uint64_t)(160));
  wg_cv_4_1(d, a[4], a[5], a[6], a[7], db + (uint64_t)(128));
  wg_commit(); wg_wait<1>();
  a[24] = lds32(ab + (1536));
  a[25] = lds32(ab + (1664));
  a[26] = lds32(ab + (1520));
  a[27] = lds32(ab + (1648));
  hand();
  wg_cv_3_1(d, a[4], a[5], a[6], a[7], db + (uint64_t)(96));
  wg_cv_2_1(d, a[4], a[5], a[6], a[7], db + (uint64_t)(64));
  wg_cv_1_1(d, a[4], a[5], a[6], a[7], db + (uint64_t)(32));
  wg_cv_0_0(d, a[4], a[5], a[6], a[7], db + (uint64_t)(0));
  a[20] = lds32(ab + (1280));
  a[21] = lds32(ab + (1408));
  a[22] = lds32(ab + (1264));
  a[23] = lds32(ab + (1392));
  wg_cv_7_1(d, a[0], a[1], a[2], a[3], db + (uint64_t)(240));
  wg_cv_6_1(d, a[0], a[1], a[2], a[3], db + (uint64_t)(208));
  wg_cv_5_1(d, a[0], a[1], a[2], a[3], db + (uint64_t)(176));
  wg_cv_4_1(d, a[0], a[1], a[2], a[3], db + (uint64_t)(144));
  a[16] = lds32(ab + (1024));
  a[17] = lds32(ab + (1152));
  a[18] = lds32(ab + (1008));
  a[19] = lds32(ab + (1136));
  wg_cv_3_1(d, a[0], a[1], a[2], a[3], db + (uint64_t)(112));
  wg_cv_2_1(d, a[0], a[1], a[2], a[3], db + (uint64_t)(80));
  wg_cv_1_1(d, a[0], a[1], a[2], a[3], db + (uint64_t)(48));
  wg_cv_0_1(d, a[0], a[1], a[2], a[3], db + (uint64_t)(16));
  wg_commit();
  a[12] = lds32(ab + (768));
  a[13] = lds32(ab + (896));
  a[14] = lds32(ab + (752));
  a[15] = lds32(ab + (880));
  a[8] = lds32(ab + (512));
  a[9] = lds32(ab + (640));
  a[10] = lds32(ab + (496));
  a[11] = lds32(ab + (624));
}
template <class F> __device__ __forceinline__ void conv_chain_0(float (&d)[128], uint32_t (&a)[64], uint64_t db, uint32_t ab, F hand) {
  wg_cv_7_0(d, a[60], a[61], a[62], a[63], db + (uint64_t)(0));
  wg_cv_6_0(d, a[52], a[53], a[54], a[55], db + (uint64_t)(0));
  wg_cv_7_1(d, a[56], a[57], a[58], a[59], db + (uint64_t)(16));
  wg_cv_5_0(d, a[44], a[45], a[46], a[47], db + (uint64_t)(0));
  wg_cv_6_1(d, a[48], a[49], a[50], a[51], db + (uint64_t)(16));
  wg_cv_7_1(d, a[52], a[53], a[54], a[55], db + (uint64_t)(32));
  wg_cv_5_1(d, a[40], a[41], a[42], a[43], db + (uint64_t)(16));
  wg_cv_6_1(d, a[44], a[45], a[46], a[47], db + (uint64_t)(32));
  wg_cv_7_1(d, a[48], a[49], a[50], a[51], db + (uint64_t)(48));
  wg_cv_6_1(d, a[40], a[41], a[42], a[43], db + (uint64_t)(48));
  wg_cv_7_1(d, a[44], a[45], a[46], a[47], db + (uint64_t)(64));
  wg_cv_7_1(d, a[40], a[41], a[42], a[43], db + (uint64_t)(80));
  wg_commit();
  wg_cv_7_1(d, a[36], a[37], a[38], a[39], db + (uint64_t)(96));
  wg_cv_6_1(d, a[36], a[37], a[38], a[39], db + (uint64_t)(64));
  wg_cv_5_1(d, a[36], a[37], a[38], a[39], db + (uint64_t)(32));
  wg_cv_4_0(d, a[36], a[37], a[38], a[39], db + (uint64_t)(0));
  wg_cv_7_1(d, a[32], a[33], a[34], a[35], db + (uint64_t)(112));
  wg_cv_6_1(d, a[32], a[33], a[34], a[35], db + (uint64_t)(80));
  wg_cv_5_1(d, a[32], a[33], a[34], a[35], db + (uint64_t)(48));
  wg_cv_4_1(d, a[32], a[33], a[34], a[35], db + (uint64_t)(16));
  wg_cv_7_1(d, a[28], a[29], a[30], a[31], db + (uint64_t)(128));
  wg_cv_6_1(d, a[28], a[29], a[30], a[31], db + (uint64_t)(96));
  wg_cv_5_1(d, a[28], a[29], a[30], a[31], db + (uint64_t)(64));
  wg_cv_4_1(d, a[28], a[29], a[30], a[31], db + (uint64_t)(32));
  wg_cv_3_0(d, a[28], a[29], a[30], a[31], db + (uint64_t)(0));
  wg_cv_7_1(d, a[24], a[25], a[26], a[27], db + (uint64_t)(144));
  wg_cv_6_1(d, a[24], a[25], a[26], a[27], db + (uint64_t)(112));
  wg_cv_5_1(d, a[24], a[25], a[26], a[27], db + (uint64_t)(80));
  wg_cv_4_1(d, a[24], a[25], a[26], a[27], db + (uint64_t)(48));
  wg_cv_3_1(d, a[24], a[25], a[26], a[27], db + (uint64_t)(16));
  wg_commit();
  wg_cv_7_1(d, a[20], a[21], a[22], a[23], db + (uint64_t)(160));
  wg_cv_6_1(d, a[20], a[21], a[22], a[23], db + (uint64_t)(128));
  wg_cv_5_1(d, a[20], a[21], a[22], a[23], db + (uint64_t)(96));
  wg_cv_4_1(d, a[20], a[21], a[22], a[23], db + (uint64_t)(64));
  wg_cv_3_1(d, a[20], a[21], a[22], a[23], db + (uint64_t)(32));
  wg_cv_2_0(d, a[20], a[21], a[22], a[23], db + (uint64_t)(0));
  wg_cv_7_1(d, a[16], a[17], a[18], a[19], db + (uint64_t)(176));
  wg_cv_6_1(d, a[16], a[17], a[18], a[19], db + (uint64_t)(144));
  wg_cv_5_1(d, a[16], a[17], a[18], a[19], db + (uint64_t)(112));
  wg_cv_4_1(d, a[16], a[17], a[18], a[19], db + (uint64_t)(80));
  wg_cv_3_1(d, a[16], a[17], a[18], a[19], db + (uint64_t)(48));
  wg_cv_2_1(d, a[16], a[17], a[18], a[19], db + (uint64_t)(16));
  wg_cv_7_1(d, a[12], a[13], a[14], a[15], db + (uint64_t)(192));
  wg_cv_6_1(d, a[12], a[13], a[14], a[15], db + (uint64_t)(160));
  wg_cv_5_1(d, a[12], a[13], a[14], a[15], db + (uint64_t)(128));
  wg_cv_4_1(d, a[12], a[13], a[14], a[15], db + (uint64_t)(96));
  wg_cv_3_1(d, a[12], a[13], a[14], a[15], db + (uint64_t)(64));
  wg_cv_2_1(d, a[12], a[13], a[14], a[15], db + (uint64_t)(32));
  wg_cv_1_0(d, a[12], a[13], a[14], a[15], db + (uint64_t)(0));
  wg_cv_7_1(d, a[8], a[9], a[10], a[11], db + (uint64_t)(208));
  wg_cv_6_1(d, a[8], a[9], a[10], a[11], db + (uint64_t)(176));
  wg_cv_5_1(d, a[8], a[9], a[10], a[11], db + (uint64_t)(144));
  wg_cv_4_1(d, a[8], a[9], a[10], a[11], db + (uint64_t)(112));
  wg_cv_3_1(d, a[8], a[9], a[10], a[11], db + (uint64_t)(80));
  wg_cv_2_1(d, a[8], a[9], a[10], a[11], db + (uint64_t)(48));
  wg_cv_1_1(d, a[8], a[9], a[10], a[11], db + (uint64_t)(16));
  wg_commit();
  wg_cv_7_1(d, a[4], a[5], a[6], a[7], db + (uint64_t)(224));
  wg_cv_6_1(d, a[4], a[5], a[6], a[7], db + (uint64_t)(192));
  wg_cv_5_1(d, a[4], a[5], a[6], a[7], db + (uint64_t)(160));
  wg_cv_4_1(d, a[4], a[5], a[6], a[7], db + (uint64_t)(128));
  hand();
  wg_cv_3_1(d, a[4], a[5], a[6], a[7], db + (uint64_t)(96));
  wg_cv_2_1(d, a[4], a[5], a[6], a[7], db + (uint64_t)(64));
  wg_cv_1_1(d, a[4], a[5], a[6], a[7], db + (uint64_t)(32));
  wg_cv_0_0(d, a[4], a[5], a[6], a[7], db + (uint64_t)(0));
  wg_cv_7_1(d, a[0], a[1], a[2], a[3], db + (uint64_t)(240));
  wg_cv_6_1(d, a[0], a[1], a[2], a[3], db + (uint64_t)(208));
  wg_cv_5_1(d, a[0], a[1], a[2], a[3], db + (uint64_t)(176));
  wg_cv_4_1(d, a[0], a[1], a[2], a[3], db + (uint64_t)(144));
  wg_cv_3_1(d, a[0], a[1], a[2], a[3], db + (uint64_t)(112));
  wg_cv_2_1(d, a[0], a[1], a[2], a[3], db + (uint64_t)(80));
  wg_cv_1_1(d, a[0], a[1], a[2], a[3], db + (uint64_t)(48));
  wg_cv_0_1(d, a[0], a[1], a[2], a[3], db + (uint64_t)(16));
  wg_commit();
}
constexpr int CV_RELOADED = 2;

struct Params {
  const __nv_bfloat16 *q, *k, *v, *shift_k, *ssm_k, *ssm_D, *w1, *b1, *w2, *b2;
  __nv_bfloat16* out;
};
struct Maps { CUtensorMap qa, w1, w1x, k, v, hs, hx, ha, hn, w2, w2x, kvs, qf, y, out; };

__global__ void __cluster_dims__(2, 1, 1) __launch_bounds__(384, 1) h3_kernel(const __grid_constant__ Maps M, const Params P) {
  extern __shared__ __align__(1024) uint8_t smem_raw[];
  constexpr uint32_t sc = 1024;
  const int tid = threadIdx.x, lane = tid & 31;
  const int warp = __shfl_sync(0xffffffffu, tid >> 5, 0);
  const uint32_t sb = __shfl_sync(0xffffffffu, s32(smem_raw), 0);
  const int b = blockIdx.x, pr = b >> 1;
  const int G = pr < 4 ? 0 : (pr < 36 ? (pr - 4) & 7 : 1 + (pr - 36) % 7), gi = pr < 4 ? 4 + pr : (pr < 36 ? (pr - 4) >> 3 : 4 + (pr - 36) / 7);
  const int kh = b & 1, nt = (G & 1) * 2 + (gi & 1), rb = (G >> 1) * 4 + (gi >> 1);
  const int dir = (G ^ (G >> 1)) & 1, ri = (gi & 1) * 2 + kh, ci = (G >> 2) * 4 + (gi >> 1);
  const uint32_t gmap = (nt & 1) ? 0x03412u : 0x43210u;
  const int j = kh * 4 + nt;
  const uint32_t bar = sb + M_BAR;
  auto BAR = [&](int i) { return bar + 8 * i; };
  auto g1_load = [&](int kc) {
    const uint32_t st = sb + (kc & 3) * G1_STAGE, fb = BAR(B_F1 + (kc & 3));
    const int k0 = dir ? 576 - kc * 64 : kc * 64;
    mbar_expect(fb, G1_TX);
    tma2d(st, &M.qa, k0, rb * 128, fb);
    tma3d(st + 16384, &M.w1, 0, k0, 3 * j, fb);
    tma2d(st + 40960, &M.w1x, 1536 + 24 * j, k0, fb);
  };
  auto kv_load = [&](int r, int hf) {
    const uint32_t st = sb + KVS + (r < 3 ? r : r - 3) * KV_BUF, fb = BAR((hf ? B_KIN1 : B_KIN) + r);
    mbar_expect(fb, KV_BUF / 2);
    tma2d(st + 4096 + hf * 2432, &M.k, 128 * r + 64 * (b & 1), 32 * (b >> 1) + 16 * hf - 3, fb);
    tma2d(st + hf * 2048, &M.v, 128 * r + 64 * (b & 1), 32 * (b >> 1) + 16 * hf, fb);
  };
  auto conv_sum = [&](int c, int ck, bool third) {
    const uint32_t ra = sb + cv_p(c) + ck * 16;
    __nv_bfloat16* yp = g_yT + (size_t)(128 * c + b) * SL + ck * 8;
    uint4 p[2][4];
    auto ld = [&](int u) {
#pragma unroll
      for (int w = 0; w < 4; w++) p[u & 1][w] = lds128((u == 0 && ck < 2 * w) ? sb + M_ZERO : ra + u * 512 + w * (4096 - 32));
    };
    auto st = [&](int u) {
      auto sum = [&](uint32_t a0, uint32_t a1, uint32_t a2, uint32_t a3) { return badd2(badd2(badd2(a3, a2), a1), a0); };
      const uint4* r = p[u & 1];
      stg128(yp + u * 256, sum(r[0].x, r[1].x, r[2].x, r[3].x), sum(r[0].y, r[1].y, r[2].y, r[3].y), sum(r[0].z, r[1].z, r[2].z, r[3].z), sum(r[0].w, r[1].w, r[2].w, r[3].w));
    };
    ld(0); ld(1); st(0);
    if (third) ld(2);
    st(1);
    if (third) st(2);
  };
  if (warp == 8) {
    if (lane == 0) {
      TS(0);
#pragma unroll
      for (int s = 0; s < 4; s++) mbar_init(BAR(B_F1 + s), 1);
    }
    __syncwarp();
    bar_arrive(NB_INIT, 384);
    ONE(g1_load(0));
  }
  if ((sb & 0xFFFFFFu) != sc) { if (warp == 8) mbar_wait(BAR(B_F1), 0); return; }

  if (warp >= 8) {
    asm volatile("setmaxnreg.dec.sync.aligned.u32 " REG_AUX ";");
    auto table = [&](int c, int aw) {
      const uint32_t kb = sb + cv_t(c);
      const uint32_t dd = lds32(sb + M_AUX + aw * 32 + c * 4);
      if (lane < 2) sts128(kb + lane * (KT_E - 16), 0u, 0u, 0u, 0u);
      uint4 r[8];
#pragma unroll
      for (int it = 0; it < 8; it++) r[it] = lds128(kb + KT_E + (it * 32 + lane) * 16);
      if (lane == 0) { r[0].x = __byte_perm(badd2(r[0].x, dd), r[0].x, 0x7610); sts32(kb + KT_E, r[0].x); }
#pragma unroll
      for (int it = 0; it < 8; it++) {
        const uint32_t pv = __shfl_sync(0xffffffffu, lane == 31 ? (it ? r[it ? it - 1 : 0].w : 0u) : r[it].w, lane - 1);
        sts128(kb + KT_O + (it * 32 + lane) * 16, __byte_perm(pv, r[it].x, 0x5432), __byte_perm(r[it].x, r[it].y, 0x5432),
               __byte_perm(r[it].y, r[it].z, 0x5432), __byte_perm(r[it].z, r[it].w, 0x5432));
      }
      __syncwarp();
      if (lane == 0) mbar_arrive(BAR(B_KT + c));
    };
    if (warp == 8) {
      ONE(g1_load(1); g1_load(2); g1_load(3));
      bar_sync(NB_INIT2, 128);
#pragma unroll
      for (int kc = 3; kc < 10; kc++) {
        if (kc > 3) mbar_wait(BAR(B_E1 + (kc & 3)), (kc >> 3) & 1);
        ONE(if (kc > 3) g1_load(kc);
            for (int r = 0; r < 3; r++) if (kc == ((KV_MAP >> (4 * r)) & 15)) { kv_load(r, 0); kv_load(r, 1); }
            for (int c = 0; c < 5; c++) if (kc == ((PF_RAW >> (4 * c)) & 15)) prefetch_l2(P.ssm_k + (size_t)(128 * c + b) * SL, 4096));
      }
      ONE(prefetch_map(&M.hs); prefetch_map(&M.hx); prefetch_map(&M.ha); prefetch_map(&M.hn); prefetch_map(&M.w2); prefetch_map(&M.w2x));
      bar_sync(NB_INIT3, 64);
      const unsigned ep = lds32(sb + M_AUX + 20);
      const int hc = kh * 896 + nt * 192, hx = kh * 896 + 768 + nt * 24;
#pragma unroll 1
      for (int n = 0; n < 32; n += 4) {
        const int i = (H_ORD >> n) & 7, hw = i >> 2, blk = i & 3;
        if (n == 4 * W2_PF) ONE(prefetch_l2(P.w2 + (size_t)b * (FF * DM / NCTA), FF * DM / NCTA * 2));
        mbar_wait(BAR(B_HB + i), 0);
        fence_async_smem();
        asm volatile("cp.async.bulk.wait_group %0;" ::"n"(H_FLY - 1) : "memory");
        ONE(tma2d_st(blk < 3 ? &M.hs : &M.hx, blk < 3 ? hc + blk * 64 : hx, rb * 128 + hw * 64, sb + hw * HST + blk * 8192); bulk_commit());
      }
      const int cf = (nt * 160 + (nt & 1) * 32) >> 6, ch = (nt >> 1) * 320 + 128;
      auto g2_load_b = [&](int kc) {
        const int s = kc & 3, wr = kc < 2 ? 1536 + kh * 96 + (1 - kc) * 64 : kh * 768 + (kc - 2) * 64;
        const uint32_t fb = BAR(B_F2 + s);
        mbar_expect(fb, kc == 0 ? 8192 + 24576 : 16384 + 24576);
        tma3d(sb + g2_b(s), &M.w2, 0, wr, cf, fb);
        tma2d(sb + g2_b(s) + 16384, &M.w2x, ch, wr, fb);
      };
      auto g2_load_a = [&](int kc) {
        const int s = kc & 3;
        tma2d(sb + g2_a(s), kc == 0 ? &M.hn : &M.ha, kh * 896 + (kc < 2 ? 768 + (1 - kc) * 64 : (kc - 2) * 64), rb * 128, BAR(B_F2 + s));
      };
      bulk_wait_all();
      ONE(g2_load_b(0); g2_load_b(1));
      fence_release();
      ONE(signal_cnt(CNT_H + rb * 2 + kh); TS(37));
      wait_cnt(CNT_H + rb * 2 + kh, 4 * ep);
      ONE(TS(39); g2_load_a(0); g2_load_a(1); prefetch_map(&M.qf); prefetch_map(&M.y); prefetch_map(&M.out));
      mbar_wait(BAR(B_KD), 0);
      ONE(g2_load_b(3));
      mbar_wait(BAR(B_TD + 1), 0);
      ONE(g2_load_b(2); g2_load_a(2));
      mbar_wait(BAR(SUM3 ? B_TD : B_SD + 3), 0);
      ONE(mbar_expect(BAR(B_FINQ), 20480); tma3d(sb + FIN_Q, &M.qf, 0, rb * 128 + kh * 64, nt * 5, BAR(B_FINQ)));
      mbar_wait(BAR(B_RF + 2), 0);
      ONE(g2_load_a(3); TS(38));
#pragma unroll 1
      for (int kc = 4; kc < 14; kc++) {
        mbar_wait(BAR(B_E2 + (kc & 3)), ((kc >> 2) - 1) & 1);
                ONE(g2_load_a(kc); g2_load_b(kc));
      }
      if (lane == 0) g_launch[b * 8] = ep;
#pragma unroll 1
      for (int i = 0; i < 5; i++) {
        const int gi = (gmap >> (4 * i)) & 7;
        mbar_wait(BAR(B_OUT + i), 0);
        fence_async_smem();
        ONE(tma2d_st(&M.out, nt * 160 + gi * 32, rb * 128 + kh * 64, sb + FIN_Q + gi * 4096));
      }
      ONE(bulk_commit());
      bulk_wait_read();
    } else {
      const int aw = warp - 9, at = tid - 288;
      if (aw == 0) {
        if (lane == 0) {
#pragma unroll
          for (int s = 0; s < 4; s++) { mbar_init(BAR(B_E1 + s), 8); mbar_init(BAR(B_FR + s), 8); mbar_init(BAR(B_F2 + s), 1); mbar_init(BAR(B_E2 + s), 8); }
          mbar_init(BAR(B_KRAW), 1); mbar_init(BAR(B_KRAW + 1), 1);
          mbar_init(BAR(B_RED), 8); mbar_init(BAR(B_BX), 1);
        }
      } else if (aw == 1) {
        if (lane == 0) {
#pragma unroll
          for (int c = 0; c < 5; c++) { if (c == 0) { mbar_init(BAR(B_SK), 1); mbar_init(BAR(B_KD), 2); } mbar_init(BAR(B_XL + c), 1); mbar_init(BAR(B_KT + c), 1); mbar_init(BAR(B_XF + c), 1); mbar_init(BAR(B_SD + c), 4); }
        }
      } else if (lane == 0) {
#pragma unroll
        for (int i = 0; i < 8; i++) mbar_init(BAR(B_HB + i), 4);
#pragma unroll
        for (int c = 0; c < 3; c++) mbar_init(BAR(B_RF + c), 3);
        for (int r = 0; r < 5; r++) { mbar_init(BAR(B_KIN + r), 1); mbar_init(BAR(B_KIN1 + r), 1); }
        mbar_init(BAR(B_YSLOT), 8); mbar_init(BAR(B_XR), 1);
        for (int i = 0; i < 5; i++) mbar_init(BAR(B_OUT + i), 4);
        mbar_init(BAR(B_XD), 1); mbar_expect(BAR(B_XD), 8192); mbar_init(BAR(B_XD + 1), 1); mbar_expect(BAR(B_XD + 1), 12288);
        asm volatile("fence.mbarrier_init.release.cluster;" ::: "memory");
        mbar_init(BAR(B_TD), 4); mbar_init(BAR(B_TD + 1), 8); mbar_init(BAR(B_FINQ), 1); mbar_init(BAR(B_FINY), 1);
      }
      __syncwarp();
      bar_arrive(NB_INIT, 384);
      if (aw == 1) ONE(prefetch_map(&M.k); prefetch_map(&M.v); mbar_expect(BAR(B_SK), 2560);
                       for (int r = 0; r < 5; r++) bulk_g2s(sb + M_SK + r * 512, P.shift_k + (128 * r + 64 * (b & 1)) * 4, 512, BAR(B_SK)));
      const uint32_t dv0 = ld_relaxed32(lane < 5 ? static_cast<const void*>(P.ssm_D + 128 * lane + (b & ~1)) : &g_launch[b * 8]);
      const uint32_t b2v = ldg32(reinterpret_cast<const uint32_t*>(P.b2 + nt * 160) + ((gmap >> (4 * (min(at, 79) >> 4))) & 7) * 16 + (at & 15));
      const int l27 = min(lane, 26), col = l27 < 24 ? 192 * j + 8 * l27 : 1536 + 24 * j + 8 * (l27 - 24);
      uint4 bb;
      if (aw == 2) bb = ldg128(P.b1 + col);
      bar_sync(NB_INIT2, 128);
      if (aw == 0) ONE(prefetch_map(&M.kvs));
      if (lane < 4) sts32(sb + M_ZERO + lane * 4, 0u);
      if (lane < 8) sts32(sb + M_AUX + aw * 32 + lane * 4, lane >= 5 ? dv0 + 1 : ((b & 1) ? dv0 >> 16 : dv0 & 0xFFFFu));
      if (at < 80) sts64f(sb + M_B2 + at * 8, 0.5f * bf_lo(b2v), 0.5f * bf_hi(b2v));
      __syncwarp();
      if (aw == 0) bar_arrive(NB_INIT3, 64);
      if (aw == 2) {
        const unsigned ep = lds32(sb + M_AUX + 64 + 20);
        const uint32_t ba = sb + M_BX + (l27 >> 2) * 512 + ((l27 & 3) << 4);
        mbar_wait(BAR(B_RED), 0);
        const uint32_t tg = ep & 15u;
        auto tagged = [&](float v) { return (__float_as_uint(v) & ~15u) | tg; };
        float c0 = 0.f, c1 = 0.f, s1 = 0.f, s2 = 0.f;
#pragma unroll
        for (int i = 0; i < 16; i += 2) { c0 += __uint_as_float(lds32(sb + M_RED1 + i * 128 + lane * 4)); c1 += __uint_as_float(lds32(sb + M_RED1 + i * 128 + 128 + lane * 4)); }
        st_relaxed32(&g_cs[(dir * 8 + j) * 256 + ci * 32 + lane], tagged(c0 + c1));
        float2 u[8];
#pragma unroll
        for (int i = 0; i < 8; i++) u[i] = lds64f(sb + M_RED0 + (lane & 15) * 128 + ((i + lane) & 7) * 16 + (lane >> 4) * 8);
        const float c = bf_round(u[0].x * (1.f / 40)), cc = 40.f * c * c;
#pragma unroll
        for (int i = 0; i < 8; i++) { s1 += fmaf(-40.f, c, u[i].x); s2 += fmaf(-2.f * c, u[i].x, u[i].y) + cc; }
        const float dm = s1 * (1.f / 320);
        st_relaxed64(&g_stat[dir * SL + rb * 128 + ri * 32 + lane], tagged(c + dm), tagged(fmaf(-dm, s1, s2)));
        __syncwarp();
        if (lane == 0) TS(30);
        sts128((ba + 128) ^ 16, 0u, 0u, 0u, 0u); sts128((ba + 192) ^ 16, bb.x, bb.y, bb.z, bb.w);
#pragma unroll
        for (int i = 4; i < 8; i++) sts128((ba + i * 64) ^ ((i >> 1) << 4), 0u, 0u, 0u, 0u);
        mbar_wait(BAR(B_FR), 0);
        auto raw_load = [&]() {
          ONE(mbar_expect(BAR(B_KRAW), 4096); mbar_expect(BAR(B_KRAW + 1), 4 * 4096);
              for (int c = 0; c < 5; c++) bulk_g2s(sb + cv_t(c) + KT_E, P.ssm_k + (size_t)(128 * c + b) * SL, 4096, BAR(B_KRAW + (c >= 1))));
        };
        uint32_t x[32], n = 0;
#pragma unroll 1
        while (true) {
#pragma unroll
          for (int i = 0; i < 8; i++) {
            const uint4 v = ld_relaxed128(i < 4 ? static_cast<const void*>(g_cs + ((i >> 1) * 8 + j) * 256 + l27 * 8 + (i & 1) * 4)
                                                : g_stat + ((i >> 1) & 1) * SL + rb * 128 + lane * 4 + (i & 1) * 2);
            x[4 * i] = v.x; x[4 * i + 1] = v.y; x[4 * i + 2] = v.z; x[4 * i + 3] = v.w;
          }
          if (!RAW_LATE && n == 0) raw_load();
          uint32_t bad = 0;
#pragma unroll
          for (int i = 0; i < 32; i++) { x[i] ^= tg; bad |= x[i]; }
          if (__all_sync(0xffffffffu, (bad & 15u) == 0) || spin_guard(n, 0x131)) break;
        }
        if (RAW_LATE) raw_load();
        uint32_t st[4];
#pragma unroll
        for (int i = 0; i < 4; i++) {
          const float ma = __uint_as_float(x[16 + 2 * i]), mb = __uint_as_float(x[24 + 2 * i]), dl = ma - mb;
          const float m2 = fmaf(dl * dl, 160.f, __uint_as_float(x[17 + 2 * i]) + __uint_as_float(x[25 + 2 * i]));
          const float vb = bf_round(fmaxf(m2, 0.f) * (1.f / DM));
          st[i] = pack_bf16(0.5f * (ma + mb), sqrt_fast(bf_round(vb + 1e-5f)));
        }
        sts128(sb + M_STAT + lane * 16, st[0], st[1], st[2], st[3]);
        uint32_t hi[4], lo[4];
#pragma unroll
        for (int i = 0; i < 4; i++) {
          const float x0 = __uint_as_float(x[2 * i]) + __uint_as_float(x[8 + 2 * i]), x1 = __uint_as_float(x[2 * i + 1]) + __uint_as_float(x[9 + 2 * i]);
          hi[i] = pack_bf16(x0, x1); lo[i] = pack_bf16(x0 - bf_lo(hi[i]), x1 - bf_hi(hi[i]));
        }
        sts128(ba, hi[0], hi[1], hi[2], hi[3]); sts128(ba + 64, lo[0], lo[1], lo[2], lo[3]);
        fence_async_smem();
        __syncwarp();
        ONE(mbar_arrive(BAR(B_BX)); TS(54));
      }
      if (aw < 2) {
        auto done = [&](int r) {
          bulk_wait_read();
          ONE(kv_load(r + 3, aw); TSKV);
        };
        const uint32_t par = lds32(sb + M_AUX + aw * 32 + 20) & 1u;
        bool pend = false;
        mbar_wait(BAR(B_SK), 0);
#pragma unroll 1
        for (int r = 0; r < 5; r++) {
          const int c0 = 128 * r + 64 * (b & 1);
          const uint32_t buf = sb + KVS + (r < 3 ? r : r - 3) * KV_BUF, stg = buf + aw * 2048, vb = stg + lane * 4, kb = buf + 4096 + aw * 2432 + lane * 4;
          const uint4 sk = lds128(sb + M_SK + r * 512 + lane * 16);
          const uint32_t w0 = __byte_perm(sk.x, sk.z, 0x5410), w1 = __byte_perm(sk.x, sk.z, 0x7632);
          const uint32_t w2 = __byte_perm(sk.y, sk.w, 0x5410), w3 = __byte_perm(sk.y, sk.w, 0x7632);
          mbar_wait(BAR((aw ? B_KIN1 : B_KIN) + r), 0);
          if (at == 0 && r == 0) TS(56);
          uint32_t kk[19], o[16];
#pragma unroll
          for (int i = 0; i < 19; i++) { kk[i] = lds32(kb + i * 128); if (i >= 3) o[i - 3] = lds32(vb + (i - 3) * 128); }
#pragma unroll
          for (int i = 0; i < 16; i++) o[i] = bmul2(bfma2(kk[i + 3], w0, bfma2(kk[i + 2], w1, bfma2(kk[i + 1], w2, bmul2(kk[i], w3)))), o[i]);
          __syncwarp();
          const uint32_t a0 = stg + lane * 64 + ((lane & 6) << 3);
          const uint32_t s0 = (lane & 4) ? 0x7632 : 0x5410, s1 = s0 ^ 0x2222;
#pragma unroll
          for (int hh = 0; hh < 2; hh++) {
            const uint32_t* u = o + 8 * hh;
            const uint32_t a = a0 ^ (hh << 4);
            auto nz = [&](uint32_t x) { return hh ? x : (x & ~1u) | par; };
            sts128(a, nz(__byte_perm(u[1], u[0], s0)), __byte_perm(u[3], u[2], s0), __byte_perm(u[5], u[4], s0), __byte_perm(u[7], u[6], s0));
            sts128(a ^ 32, nz(__byte_perm(u[1], u[0], s1)), __byte_perm(u[3], u[2], s1), __byte_perm(u[5], u[4], s1), __byte_perm(u[7], u[6], s1));
          }
          if (pend) done(r - 1);
          fence_async_smem();
          __syncwarp();
          ONE(tma2d_st(&M.kvs, 32 * (b >> 1) + 16 * aw, c0, stg); bulk_commit());
          pend = r < 2 && mbar_test(BAR((aw ? B_KIN1 : B_KIN) + r + 1), 0);
          if (!pend && r < 2) done(r);
        }
      }
      const unsigned ep = lds32(sb + M_AUX + aw * 32 + 20);
      auto x_load = [&](int c) { mbar_expect(BAR(B_XL + c), 4096); bulk_g2s(sb + cv_x(c) + XD, g_kvT + (size_t)(128 * c + b) * SL, 4096, BAR(B_XL + c)); };
      auto x_pad = [&](int c0, int c1) {
        if (lane < 17) for (int c = c0; c < c1; c++) sts128(sb + cv_x(c) + lane * 16, 0u, 0u, 0u, 0u);
        fence_async_smem();
        __syncwarp();
      };
      if (aw == 2) {
        mbar_wait(BAR(B_FR + 1), 0);
        ONE(for (int c = 0; c < X_A; c++) x_load(c));
        x_pad(0, 4);
      }
#pragma unroll 1
      for (int c = 2 - aw; c < 5; c += 2) {
        mbar_wait(BAR(B_KRAW + (c > 0)), 0);
        if (lane == 0 && c == 2) TS(35);
        table(c, aw);
        if (lane == 0 && c == 2) TS(55);
        if (c == 0) break;
        if (c < 3) { bulk_wait_read(); ONE(mbar_arrive(BAR(B_KD)); if (aw == 0) TS(34)); }
      }
      if (aw == 2) {
#pragma unroll 1
        for (int c = 0, n = 0; c < 5;) {
          mbar_wait(BAR(B_XL + c), n & 1);
          const uint32_t a = sb + cv_x(c) + XD + lane * 32;
          const uint32_t v = ((lds32(a) ^ ep) | (lds32(a + 1024) ^ ep) | (lds32(a + 2048) ^ ep) | (lds32(a + 3072) ^ ep)) & 1u;
          int nx = c;
          if (__all_sync(0xffffffffu, v == 0) || n > 100000) {
            ONE(mbar_arrive(BAR(B_XF + c)); if (c == 0) TS(36); if (c >= 3) TS(28 + c));
            nx = c + X_A; c++; n = 0;
            if (nx == 4) { mbar_wait(BAR(B_KD), 0); x_pad(4, 5); }
          } else {
            n++;
            if (lane == 0) TS(33);
          }
          if (nx < 5) ONE(x_load(nx));
        }
      }
      if (RED_GATE) mbar_wait(BAR(RED_GATE == 1 ? B_TD + 1 : B_SD + RED_GATE - 1), 0);
#pragma unroll 1
      for (int c = 0; c < 5; c++) {
        mbar_wait(BAR(B_SD + c), 0);
        if (c == 3 && SUM3) continue;
        conv_sum(c, aw * 96 + lane, aw < 2);
        __syncwarp();
        if (c < 3 && lane == 0) mbar_arrive(BAR(B_RF + c));
        if (at == 0) TS(59 + c);
      }
      bar_sync(NB_AUX, 96);
      if (aw == 0) {
        fence_release();
        ONE(signal_cnt(CNT_Y); TS(3));
        wait_cnt(CNT_Y, 128 * ep);
        ONE(TS(40); mbar_arrive(BAR(B_XR)));
        mbar_wait(BAR(B_YSLOT), 0);
        ONE(mbar_expect(BAR(B_FINY), 20480); tma2d(sb + FIN_Y, &M.y, rb * 128 + kh * 64, nt * 160, BAR(B_FINY)));
      }
    }
  } else {
    asm volatile("setmaxnreg.inc.sync.aligned.u32 " REG_CON ";");
    const int wg = warp >> 2, w = warp & 3, g = lane >> 2, q = lane & 3;
    constexpr bool elect = false;
    uint32_t ca[64];
    const uint32_t ab0 = sb + ((g & 1) ? KT_E : KT_O) + (8 * w + 4 + (g >> 1) - q) * 4;
    auto conv_lda = [&](int c, int k0, int k1) {
      const uint32_t ab = ab0 + cv_t(c);
#pragma unroll
      for (int ks = 15; ks >= 0; ks--) {
        if (ks >= k0 && ks < k1) {
          ca[4 * ks + 0] = lds32(ab + ks * 256);
          ca[4 * ks + 1] = lds32(ab + ks * 256 + 128);
          ca[4 * ks + 2] = lds32(ab + ks * 256 - 16);
          ca[4 * ks + 3] = lds32(ab + ks * 256 + 112);
        }
      }
    };
    {
      float d[108];
      auto g1_release = [&](int kc) { if (lane == 0) mbar_arrive(BAR(kc < 6 ? B_E1 + (kc & 3) : B_FR + kc - 6)); };
      auto g1_wait = [&](int kc) { mbar_wait(BAR(B_F1 + (kc & 3)), (kc >> 2) & 1); };
      auto g1_issue = [&](int kc) {
        const int s = kc & 3;
        if (kc == 0) { mbar_wait(BAR(B_F1), 0); if (wg == 1) bar_sync(NB_LEAD, 256); }
        if (tid == 0) TS(8 + kc);
        const uint32_t st = sc + s * G1_STAGE;
        const uint64_t da = mkdesc(st + wg * 8192, 16, 1024, 1), db = mkdesc(st + 16384, 8192, 1024, 1);
        wg_fence();
#pragma unroll
        for (int k = 0; k < 4; k++) {
          wg_ss_216(d, da + k * 2, db + k * 128, (kc | k) != 0);
          if (k == REL_K || k == 3) wg_commit();
          if (k == REL_K && kc > 0) { wg_wait<1>(); g1_release(kc - 1); }
        }
        if (kc == 0 && wg == 0) bar_arrive(NB_LEAD, 256);
      };
      const int t7 = tid & 127, wr = ((t7 >> 3) & 1) * 4 + (t7 >> 4) * 8, wc = 4 * min(ci, 6) + ((t7 >> 1) & 3);
      const uint32_t sa0 = sb + (wg ? 16384 + (wc >> 3) * 8192 + wr * 128 + (((wc ^ wr) & 7) << 4) + (t7 & 1) * 8 : ri * 4096 + t7 * 16);
      float t1 = 0.f, t2 = 0.f, t3 = 0.f, t4 = 0.f;
      auto piece = [&](int i) {
        if (wg == 0) {
          const uint4 x = lds128(sa0 + (i & 3) * G1_STAGE), y = lds128(sa0 + (i & 3) * G1_STAGE + 2048);
          const uint32_t xx[4] = {x.x, x.y, x.z, x.w}, yy[4] = {y.x, y.y, y.z, y.w};
#pragma unroll
          for (int e = 0; e < 4; e++) {
            const float u = bf_lo(xx[e]), v = bf_hi(xx[e]), r = bf_lo(yy[e]), z = bf_hi(yy[e]);
            t1 += u; t2 = fmaf(u, u, t2); t3 += r; t4 = fmaf(r, r, t4);
            t1 += v; t2 = fmaf(v, v, t2); t3 += z; t4 = fmaf(z, z, t4);
          }
        } else {
          float2 xx[4];
#pragma unroll
          for (int e = 0; e < 4; e++) xx[e] = lds64f((sa0 ^ (e * 144)) + (i & 3) * G1_STAGE);
#pragma unroll
          for (int e = 0; e < 4; e++) {
            const uint32_t u = __float_as_uint(xx[e].x), v = __float_as_uint(xx[e].y);
            t1 += bf_lo(u); t2 += bf_hi(u); t3 += bf_lo(v); t4 += bf_hi(v);
          }
        }
      };
      bar_sync(NB_INIT, 384);
#pragma unroll
      for (int kc = 0; kc < 10; kc++) {
        g1_issue(kc);
        if (kc < 5) { g1_wait(kc); piece(kc); }
        if (kc == 4) {
          sts128(sb + (wg ? M_RED1 : M_RED0) + t7 * 16, __float_as_uint(t1), __float_as_uint(t2), __float_as_uint(t3), __float_as_uint(t4));
          __syncwarp();
          if (lane == 0) mbar_arrive(BAR(B_RED));
        }
        if (kc < 9) g1_wait(kc + 1);
      }
      uint2 s0, s1;
      {
        mbar_wait(BAR(B_BX), 0);
        s0.x = lds32(sb + M_STAT + (wg * 64 + w * 16 + g) * 4); s1.x = lds32(sb + M_STAT + (wg * 64 + w * 16 + g + 8) * 4);
        if (tid == 0) TS(46);
        const uint32_t f0 = q == 0 ? ((s0.x & 0xFFFFu) * 0x10001u) ^ 0x80008000u : (q == 1 ? s0.x ^ 0x8000u : 0u);
        const uint32_t f1 = q == 0 ? ((s1.x & 0xFFFFu) * 0x10001u) ^ 0x80008000u : (q == 1 ? s1.x ^ 0x8000u : 0u);
        wg_fence();
        wg_rs_216(d, f0, f1, 0u, 0u, mkdesc(sc + M_BX, 512, 0, 2));
        wg_commit();
      }
      wg_wait<1>();
      if (lane == 0) mbar_arrive(BAR(B_FR + 3));
      const float r0 = rcp_fast(bf_hi(s0.x)), r1 = rcp_fast(bf_hi(s1.x));
      constexpr float C1 = 0.7978845608028654f, C2 = 0.7978845608028654f * 0.044715f;
      const float ga0 = C1 * r0, gb0 = C2 * r0 * r0 * r0, ga1 = C1 * r1, gb1 = C2 * r1 * r1 * r1;
      if (wg == 0) mbar_wait(BAR(B_FR + 2), 0);
      wg_wait<0>();
      if (elect) TS(1 + 47 * wg);
      if (wg == 1) bar_sync(NB_GELU, 256);
      sched_fence(sb);
      const int mi = lane >> 3, row = w * 16 + (mi & 1) * 8 + (lane & 7);
      const uint32_t hs = sb + wg * HST;
      float u[2][8];
#pragma unroll
      for (int st = -1; st < 15; st++) {
        const int nb = 2 * (st - 1);
        if (st >= 1) {
          uint32_t p[4];
#pragma unroll
          for (int e = 0; e < (nb < 26 ? 4 : 2); e++) {
            const float x = d[4 * nb + 2 * e], y = d[4 * nb + 2 * e + 1];
            p[e] = pack_bf16(fmaf(x, u[(st - 1) & 1][2 * e], x), fmaf(y, u[(st - 1) & 1][2 * e + 1], y));
          }
          const int nbm = nb + (mi >> 1);
          if (nb < 24) stsm4(hs + (nb >> 3) * 8192 + row * 128 + (((nbm & 7) ^ (row & 7)) << 4), p[0], p[1], p[2], p[3]);
          else if (nb == 24) stsm4(hs + 24576 + row * 48 + (mi >> 1) * 16, p[0], p[1], p[2], p[3]);
          else stsm2(hs + 24576 + row * 48 + 32, p[0], p[1]);
          if ((nb & 7) == 6 || nb == 26) {
            __syncwarp();
            if (lane == 0) mbar_arrive(BAR(B_HB + wg * 4 + (nb >> 3)));
          }
        }
        if (st >= 0 && st < 14) {
#pragma unroll
          for (int i = 0; i < (st < 13 ? 8 : 4); i++) u[st & 1][i] = tanh_fast(u[st & 1][i]);
        }
        if (st + 1 < 14) {
#pragma unroll
          for (int i = 0; i < (st + 1 < 13 ? 8 : 4); i++) {
            const float x = d[8 * (st + 1) + i];
            u[(st + 1) & 1][i] = x * fmaf(x * ((i & 2) ? gb1 : gb0), x, (i & 2) ? ga1 : ga0);
          }
        }
        constexpr int S0 = A_NB0 / 2;
        if (st >= S0 && st < 14) conv_lda(wg, 16 - (st + 1 - S0) * 16 / (S0 < 14 ? 14 - S0 : 1), 16 - (st - S0) * 16 / (S0 < 14 ? 14 - S0 : 1));
        if (2 * st == GELU_NB && wg == 0) bar_arrive(NB_GELU, 256);
        if (st + 1 == S0) mbar_wait(BAR(B_KT + wg), 0); else if (st < 14 && (st + 1) % SCH == 0) sched_fence(sb);
      }
      if (A_NB0 >= 28) { mbar_wait(BAR(B_KT + wg), 0); conv_lda(wg, 0, 16); }
      if (elect) TS(2 + 47 * wg);
    }
#pragma unroll 1
    for (int c = wg; c < 5; c += 2) {
      float d[128];
      mbar_wait(BAR(B_XF + c), 0);
      if (c < 3) mbar_wait(BAR(B_KT + c + 2), 0);
      const uint64_t db = mkdesc(sc + cv_x(c), 16, 128, 0);
      if (c > 0) { if (wg) bar_sync(NB_TURN + 1, 256); else bar_sync(NB_TURN, 256); }
      wg_fence();
      auto hand = [&]() { if (wg) bar_arrive(NB_TURN, 256); else bar_arrive(NB_TURN + 1, 256); };
      if (c < 3) conv_chain_1(d, ca, db, ab0 + cv_t(c + 2), hand); else conv_chain_0(d, ca, db, 0, hand);
      mbar_wait(BAR(c >= 3 ? B_RF + c - 3 : B_FR + 3), 0);
      wg_wait<0>();
      if (elect) TS(41 + c);
      const uint32_t wa = sb + cv_p(c) + w * 4096 + lane * 16;
#pragma unroll
      for (int n4 = 0; n4 < 32; n4 += 4) {
        uint32_t p[4];
#pragma unroll
        for (int e = 0; e < 4; e++) {
          const int nb = n4 + e;
          float x = d[4 * nb], y = d[4 * nb + 1];
          if (nb > 0) { x += d[4 * nb - 2]; y += d[4 * nb - 1]; }
          p[e] = pack_bf16(x, y);
        }
        stsm4t(wa + n4 * 128, p[0], p[1], p[2], p[3]);
      }
      if (c == 3 && SUM3) break;
      __syncwarp();
      if (lane == 0) mbar_arrive(BAR(B_SD + c));
      if (c < 3) {
        conv_lda(c + 2, 0, CV_RELOADED);
        if (c > 0) {
          fence_async_smem();
          __syncwarp();
          if (lane == 0) mbar_arrive(BAR(B_TD + 1));
        }
      }
    }
    if (elect) TS(51 + wg);
    {
      float d[80];
      const uint32_t aoff = (wg ^ kh) * 8192;
      const uint64_t boff = (uint64_t)(nt & 1) << 51;
      const uint32_t s0 = lds32(sb + M_STAT + ((wg ^ kh) * 64 + w * 16 + g) * 4), s1 = lds32(sb + M_STAT + ((wg ^ kh) * 64 + w * 16 + g + 8) * 4);
      auto g2_release = [&](int kc) { if (lane == 0) mbar_arrive(BAR(kc == 10 ? B_YSLOT : B_E2 + (kc & 3))); };
      auto g2_mma = [&](int kc, int first, bool rel) {
        const int s = kc & 3;
        mbar_wait(BAR(B_F2 + s), (kc >> 2) & 1);
        const uint64_t da = mkdesc(sc + g2_a(s) + aoff, 16, 1024, 1), db = mkdesc(sc + g2_b(s), 8192, 1024, 1) | boff;
        wg_fence();
#pragma unroll
        for (int k = 0; k < (kc ? 4 : 2); k++) {
          wg_ss_160(d, da + k * 2, db + k * 128, k ? 1 : first);
          if ((k == REL_K && rel) || k == (kc ? 3 : 1)) wg_commit();
          if (k == REL_K && rel) { wg_wait<1>(); g2_release(kc - 1); }
        }
      };
      if (wg == 1) {
        if (SUM3) {
          bar_sync(NB_WG1, 128);
          if (lane == 0) mbar_arrive(BAR(B_TD));
          conv_sum(3, w * 64 + lane, false);
          __syncwarp();
          if (lane == 0) mbar_arrive(BAR(B_SD + 3));
          if (elect) TS(62);
        }
        float bi[40];
#pragma unroll
        for (int nb = 0; nb < 20; nb++) { const float2 v = lds64f(sb + M_B2 + nb * 32 + q * 8); bi[2 * nb] = v.x; bi[2 * nb + 1] = v.y; }
        const float c0 = 0.25f * rcp_fast(bf_hi(s0)), c1 = 0.25f * rcp_fast(bf_hi(s1));
        bar_sync(NB_TURN + 1, 256);
        g2_mma(0, 0, false);
#pragma unroll
        for (int kc = 1; kc < 14; kc++) {
          if (kc == LEAD_KC) bar_sync(NB_LEAD, 256);
          g2_mma(kc, 1, kc < 12);
          if (kc == END_KC) bar_arrive(NB_END, 256);
        }
        mbar_wait(BAR(B_XR), 0);
        wg_wait<0>();
        if (elect) TS(53);
        const uint32_t ra = mapa(sb, kh ^ 1), rbar = ra + M_BAR + 8 * B_XD, dst = ra + (tid & 127) * 16;
#pragma unroll
        for (int i = 0; i < 10; i++) {
          const float *dd = d + 8 * i, *bb = bi + 4 * i;
          st_async128(dst + (i < 5 ? P0 + i * 2048 : P1 + (i - 5) * 2048), pack_bf16(fmaf(dd[0], c0, bb[0]), fmaf(dd[1], c0, bb[1])), pack_bf16(fmaf(dd[2], c1, bb[0]), fmaf(dd[3], c1, bb[1])),
                      pack_bf16(fmaf(dd[4], c0, bb[2]), fmaf(dd[5], c0, bb[3])), pack_bf16(fmaf(dd[6], c1, bb[2]), fmaf(dd[7], c1, bb[3])), rbar + 8 * (i >= 4));
        }
        if (elect) TS(7);
      } else {
        const int mi = lane >> 3, row = (mi & 1) * 8 + (lane & 7);
        const uint32_t qa = sb + FIN_Q + (w * 16 + row) * 64;
        auto q_addr = [&](int np) {
          const int gi = (gmap >> (4 * (np >> 1))) & 7;
          return qa + gi * 4096 + ((((np & 1) * 2 + (mi >> 1)) ^ ((row >> 1) & 3)) << 4);
        };
        uint32_t sv[40];
        uint32_t m0, m1; float rs0, rs1;
        g2_mma(0, 0, false);
        if (LEAD_KC && LEAD_F == 0) bar_arrive(NB_LEAD, 256);
#pragma unroll
        for (int kc = 1; kc < 10; kc++) {
          if (tid == 0) TS(17 + kc);
          g2_mma(kc, 1, true);
          if (LEAD_KC && LEAD_F == kc) bar_arrive(NB_LEAD, 256);
          if (kc == XP_KC - 1) {
            m0 = (s0 & 0xFFFFu) * 0x10001u; m1 = (s1 & 0xFFFFu) * 0x10001u;
            rs0 = rcp_fast(bf_hi(s0)); rs1 = rcp_fast(bf_hi(s1));
          }
          if (kc >= XP_KC && XP_KC < 10) {
            mbar_wait(BAR(B_FINQ), 0);
#pragma unroll
            for (int np = 10 * (kc - XP_KC) / (XP_KC < 10 ? 10 - XP_KC : 1); np < 10 * (kc + 1 - XP_KC) / (XP_KC < 10 ? 10 - XP_KC : 1); np++) {
              uint32_t xq[4];
              ldsm4(q_addr(np), xq[0], xq[1], xq[2], xq[3]);
#pragma unroll
              for (int e = 0; e < 4; e++) {
                const uint32_t dm = bsub2(xq[e], (e & 1) ? m1 : m0);
                const float rs = (e & 1) ? rs1 : rs0;
                sv[4 * np + e] = pack_bf16(bf_lo(dm) * rs, bf_hi(dm) * rs);
              }
            }
          }
        }
        auto y_prep = [&](int n0, int n1) {
          if (n1 > n0) mbar_wait(BAR(B_FINY), 0);
#pragma unroll
          for (int np = n0; np < n1; np++) {
            const int cb = ((gmap >> (4 * (np >> 1))) & 7) * 4 + (np & 1) * 2 + (mi >> 1);
            const uint32_t ya = sb + FIN_Y + cb * 1024 + (lane & 7) * 128 + (((2 * w + (mi & 1)) ^ (lane & 7)) << 4);
            uint32_t y[4];
            ldsm4t(ya, y[0], y[1], y[2], y[3]);
#pragma unroll
            for (int e = 0; e < 4; e++) sv[4 * np + e] = bmul2(sv[4 * np + e], y[e]);
          }
        };
        rs0 *= 0.25f; rs1 *= 0.25f;
        if (tid == 0) TS(27);
#pragma unroll
        for (int kc = 10; kc < 14; kc++) {
          g2_mma(kc, 1, kc == 10 || (kc == 11 && HOLD_KC > 10));
          if (kc == HOLD_KC) {
            if (kc == 10) { wg_wait<0>(); g2_release(10); }
            if (tid == 0) TS(28);
            bar_sync(NB_END, 256);
          }
          if (kc == 12) y_prep(0, YP_N);
        }
        if (tid == 0) TS(29);
        y_prep(YP_N, 10);
        if (tid == 0) TS(47);
        mbar_wait(BAR(B_XD), 0);
        if (tid == 0) TS(5);
        uint4 v0 = lds128(sb + tid * 16 + P0), v1 = lds128(sb + tid * 16 + P0 + 2048);
        wg_wait<0>();
        if (tid == 0) TS(4);
#pragma unroll
        for (int np = 0; np < 10; np++) {
          const uint32_t pw[4] = {v0.x, v0.y, v0.z, v0.w};
          v0 = v1;
          if (np < 8) {
            if (np == 2) mbar_wait(BAR(B_XD + 1), 0);
            v1 = lds128(sb + tid * 16 + (np + 2 < 5 ? P0 + (np + 2) * 2048 : P1 + (np - 3) * 2048));
          }
          uint32_t o[4];
          ldsm4(q_addr(np), o[0], o[1], o[2], o[3]);
#pragma unroll
          for (int e = 0; e < 4; e++) {
            const float h0 = fmaf(d[8 * np + 2 * e], (e & 1) ? rs1 : rs0, bf_lo(pw[e])), h1 = fmaf(d[8 * np + 2 * e + 1], (e & 1) ? rs1 : rs0, bf_hi(pw[e]));
            o[e] = bfma2(sv[4 * np + e], pack_bf16(fmaf(h0, tanh_fast(h0), h0), fmaf(h1, tanh_fast(h1), h1)), o[e]);
          }
          stsm4(q_addr(np), o[0], o[1], o[2], o[3]);
          if (np & 1) {
            if (np == 9 && tid == 0) TS(50);
            __syncwarp();
            if (lane == 0) mbar_arrive(BAR(B_OUT + (np >> 1)));
          }
        }
      }
    }
  }
}

typedef CUresult (*EncFn)(CUtensorMap*, CUtensorMapDataType, cuuint32_t, void*, const cuuint64_t*, const cuuint64_t*, const cuuint32_t*, const cuuint32_t*,
                          CUtensorMapInterleave, CUtensorMapSwizzle, CUtensorMapL2promotion, CUtensorMapFloatOOBfill);

static void make_map(EncFn enc, CUtensorMap* tm, const void* ptr, int cols, int rows, int bc, int br, int grp, CUtensorMapSwizzle sw,
                     CUtensorMapL2promotion promo = CU_TENSOR_MAP_L2_PROMOTION_NONE) {
  cuuint64_t gd[3] = {(cuuint64_t)(grp ? bc : cols), (cuuint64_t)rows, (cuuint64_t)(cols / bc)};
  cuuint64_t gs[2] = {(cuuint64_t)cols * 2, (cuuint64_t)bc * 2};
  cuuint32_t bd[3] = {(cuuint32_t)bc, (cuuint32_t)br, (cuuint32_t)grp};
  cuuint32_t es[3] = {1, 1, 1};
  CUresult r = enc(tm, CU_TENSOR_MAP_DATA_TYPE_BFLOAT16, grp ? 3 : 2, const_cast<void*>(ptr), gd, gs, bd, es, CU_TENSOR_MAP_INTERLEAVE_NONE, sw,
                   promo, CU_TENSOR_MAP_FLOAT_OOB_FILL_NONE);
  (void)r;
}

}

extern "C" void kernel_launch(void* const* d_in, const int* in_sizes, int n_in, void* d_out, int out_size) {
  using namespace h3;
  (void)in_sizes; (void)n_in; (void)out_size;
  static EncFn enc = nullptr;
  static void *p_h = nullptr, *p_yT = nullptr, *p_kvT = nullptr;
  if (!enc) {
    void* fn = nullptr; cudaDriverEntryPointQueryResult qr;
    cudaGetDriverEntryPoint("cuTensorMapEncodeTiled", &fn, cudaEnableDefault, &qr);
    enc = (EncFn)fn;
    cudaGetSymbolAddress(&p_h, g_h);
    cudaGetSymbolAddress(&p_yT, g_yT);
    cudaGetSymbolAddress(&p_kvT, g_kvT);
    cudaFuncSetAttribute(h3_kernel, cudaFuncAttributeMaxDynamicSharedMemorySize, SMEM_BYTES);
  }
  Params P;
  P.q = (const __nv_bfloat16*)d_in[0]; P.k = (const __nv_bfloat16*)d_in[1]; P.v = (const __nv_bfloat16*)d_in[2];
  P.shift_k = (const __nv_bfloat16*)d_in[3]; P.ssm_k = (const __nv_bfloat16*)d_in[4]; P.ssm_D = (const __nv_bfloat16*)d_in[5];
  P.out = (__nv_bfloat16*)d_out;
  P.w1 = (const __nv_bfloat16*)d_in[7]; P.b1 = (const __nv_bfloat16*)d_in[8]; P.w2 = (const __nv_bfloat16*)d_in[9]; P.b2 = (const __nv_bfloat16*)d_in[10];
  const CUtensorMapSwizzle S128 = CU_TENSOR_MAP_SWIZZLE_128B, S64 = CU_TENSOR_MAP_SWIZZLE_64B, S0 = CU_TENSOR_MAP_SWIZZLE_NONE;
  Maps M;
  make_map(enc, &M.qa, P.q, DM, SL, 64, 128, 0, S128);
  make_map(enc, &M.w1, P.w1, FF, DM, 64, 64, 3, S128);
  make_map(enc, &M.w1x, P.w1, FF, DM, 24, 64, 0, S128, WS_PROMO);
  make_map(enc, &M.k, P.k, DM, SL, 64, 19, 0, S0);
  make_map(enc, &M.v, P.v, DM, SL, 64, 16, 0, S0);
  make_map(enc, &M.hs, p_h, HP, SL, 64, 64, 0, S128);
  make_map(enc, &M.hx, p_h, HP, SL, 24, 64, 0, S0);
  make_map(enc, &M.ha, p_h, HP, SL, 64, 128, 0, S128);
  make_map(enc, &M.hn, p_h, HP, SL, 32, 128, 0, S128);
  make_map(enc, &M.w2, P.w2, DM, FF, 64, 64, 2, S128);
  make_map(enc, &M.w2x, P.w2, DM, FF, 64, 64, 0, S128);
  make_map(enc, &M.kvs, p_kvT, SL, DM, 16, 64, 0, CU_TENSOR_MAP_SWIZZLE_32B);
  make_map(enc, &M.qf, P.q, DM, SL, 32, 64, 5, S64);
  make_map(enc, &M.y, p_yT, SL, DM, 64, 160, 0, S128);
  make_map(enc, &M.out, d_out, DM, SL, 32, 64, 0, S64);
  h3_kernel<<<NCTA, 384, SMEM_BYTES>>>(M, P);
}
```

```cpp
#include <cuda_runtime.h>
#include <cuda_bf16.h>
#include <cuda.h>
#include <stdint.h>

namespace h3 {

constexpr int SL = 2048, DM = 640, FF = 1728;
constexpr int NCTA = 128;

__device__ __align__(1024) __nv_bfloat16 g_h[SL * FF];
__device__ __align__(1024) __nv_bfloat16 g_kvT[DM * SL];
__device__ __align__(1024) __nv_bfloat16 g_yT[DM * SL];
__device__ __align__(1024) uint2 g_stat[2 * SL];
__device__ __align__(1024) uint32_t g_cs[2 * 8 * 256];
__device__ __align__(1024) unsigned g_cnt[64 * 32];
__device__ __align__(1024) unsigned g_launch[NCTA * 8];
constexpr int CNT_H = 0;

constexpr int G1_STAGE = 49152, G1_TX = 16384 + 24576 + 3072;
constexpr int HST = 49152;
constexpr int P0 = 81920, P1 = 140288, P2 = 156672;
constexpr int XCH = 4368, XD = 272, X0 = 173056, X4 = 221184;
constexpr int KVS = 196608, KV_BUF = 8960;
constexpr int KT_CH = 8240, KT_O = 16, KT_E = 4144, KT0 = 98304;
constexpr int FIN_Q = X0;
constexpr int MISC = 226816;
constexpr int M_BX = MISC;
constexpr int M_RED0 = M_BX + 2048, M_RED1 = M_BX;
constexpr int M_SK = KVS + 3 * KV_BUF;
constexpr int M_STAT = M_BX + 3584;
constexpr int M_B2 = MISC - 640;
constexpr int M_AUX = M_STAT + 512;
constexpr int M_ZERO = M_AUX + 96;
constexpr int M_BAR = M_ZERO + 16;
constexpr int M_TS = M_BAR + 86 * 8;
constexpr int SMEM_BYTES = M_TS + 256;
__host__ __device__ constexpr int fin_y(int np) {
  return np < 3 ? P0 + 10240 + np * 2048 : (np < 6 ? P1 + 10240 + (np - 3) * 2048 : (np == 6 ? FIN_Q + 20480 : (np < 9 ? X4 + (np - 7) * 2048 : M_BX + 512)));
}
static_assert(fin_y(9) % 1024 == 0 && fin_y(6) % 1024 == 0 && fin_y(6) + 2048 <= KVS && fin_y(7) % 1024 == 0, "smem");
__host__ __device__ constexpr int cv_x(int c) { return c == 4 ? X4 : X0 + c * XCH; }
__host__ __device__ constexpr int cv_p(int c) { return c == 2 ? P2 : ((c == 0 || c == 3) ? P0 : P1); }
__host__ __device__ constexpr int cv_t(int c) { return KT0 + c * KT_CH; }
__host__ __device__ constexpr int g2_a(int s) { return s == 0 ? 0 : (s == 1 ? 40960 : (s == 2 ? 98304 : P2)); }
__host__ __device__ constexpr int g2_b(int s) { return s == 0 ? 16384 : (s == 1 ? 57344 : (s == 2 ? 114688 : KVS)); }
static_assert(M_SK + 2560 <= M_B2 && X4 + XCH <= M_B2 && KVS + 24576 <= X4 && X0 + 4 * XCH <= KVS && FIN_Q + 20480 <= KVS, "smem");
static_assert(KT0 + 5 * KT_CH <= P1 && P1 + 16384 <= P2 && P2 + 16384 <= X0 && SMEM_BYTES <= 232448 && MISC % 512 == 0 && M_BAR % 8 == 0, "smem");
constexpr int B_F1 = 0, B_E1 = 4, B_FR = 8, B_F2 = 12, B_E2 = 16, B_KRAW = 20, B_KT = 22, B_XF = 27, B_HB = 32, B_SD = 40, B_RF = 45,
              B_TD = 48, B_FINQ = 50, B_FINY = 51, B_RED = 52, B_BX = 53, B_KIN = 54, B_XR = 59, B_OUT = 61, B_SK = 66, B_YSLOT = 80, B_YL = 83, B_XD = 68, B_KIN1 = 70, B_XL = 75, B_KD = 60;
constexpr int NB_INIT = 1, NB_INIT2 = 2, NB_AUX = 3, NB_LEAD = 4, NB_GELU = 5, NB_TURN = 6  , NB_END = 8, NB_INIT3 = 9, NB_WG1 = 10;

#define KV_MAP 0x543
#define KV_LATE 1
#define PF_KV 0
#define PF_G1 0
#define WS_PROMO CU_TENSOR_MAP_L2_PROMOTION_L2_128B
#define RAW_LATE 0
#define PF_RAW 0
#define SIDE_LD 4
#define SIDE_USE 0x554
#define REL_K 0
#define CS_WAIT 1
#define GELU_NB 8
#define H_ORD 0x73625410
#define W2_PF 7
#define H_FLY 8
#define TB2 2
#define X_A 2
#define FENCE_KIND 1
#define SCH 1
#define A_NB0 14
#define RED_GATE 2
#define XP_KC 4
#define YP_N 10
#define YP_H 10
#define Y_KC 8
#define HOLD_KC 10
#define END_KC 12
#define REG_AUX "56"
#define REG_CON "224"
#define LDQ ".nc.L1::no_allocate"
#define LDP ""

__device__ __forceinline__ uint32_t s32(const void* p) { return (uint32_t)__cvta_generic_to_shared(p); }
__device__ __forceinline__ uint32_t clk() { uint32_t t; asm volatile("mov.u32 %0, %%clock;" : "=r"(t)); return t; }
__device__ __forceinline__ bool elect_one() {
  uint32_t p; asm volatile("{\n.reg .pred P;\nelect.sync _|P, 0xffffffff;\nselp.u32 %0, 1, 0, P;\n}" : "=r"(p)); return p;
}
#define ONE(...) do { if (elect_one()) { __VA_ARGS__; } __syncwarp(); } while (0)
__device__ __forceinline__ void mbar_init(uint32_t a, int c) { asm volatile("mbarrier.init.shared::cta.b64 [%0], %1;" ::"r"(a), "r"(c) : "memory"); }
__device__ __forceinline__ void mbar_expect(uint32_t a, int b) { asm volatile("mbarrier.arrive.expect_tx.shared::cta.b64 _, [%0], %1;" ::"r"(a), "r"(b) : "memory"); }
__device__ __forceinline__ void mbar_arrive(uint32_t a) { asm volatile("mbarrier.arrive.shared::cta.b64 _, [%0];" ::"r"(a) : "memory"); }
__device__ __forceinline__ bool spin_guard(uint32_t& n, uint32_t) {
  return ++n > (1u << 20);
}
__device__ __forceinline__ void mbar_wait(uint32_t a, int ph) {
  asm volatile("{\n.reg .pred p;\n.reg .u32 n;\nmov.u32 n, 0;\nW:\n.pragma \"nounroll\";\nmbarrier.try_wait.parity.shared::cta.b64 p, [%0], %1;\n"
               "add.u32 n, n, 1;\nsetp.ge.or.u32 p, n, 0x100000, p;\n@!p bra W;\n}" ::"r"(a), "r"(ph) : "memory");
}
__device__ __forceinline__ bool mbar_test(uint32_t a, int ph) {
  uint32_t ok;
  asm volatile("{\n.reg .pred p;\nmbarrier.test_wait.parity.shared::cta.b64 p, [%1], %2;\nselp.u32 %0, 1, 0, p;\n}" : "=r"(ok) : "r"(a), "r"(ph) : "memory");
  return __all_sync(0xffffffffu, ok);
}
__device__ __forceinline__ void sched_fence(uint32_t a) {
  asm volatile("{\n.reg .pred p;\nsetp.eq.u32 p, %0, 0;\n@p exit;\n}" ::"r"(a) : "memory");
}
__device__ __forceinline__ void tma2d(uint32_t dst, const CUtensorMap* tm, int c0, int c1, uint32_t bar) {
  asm volatile("cp.async.bulk.tensor.2d.shared::cluster.global.mbarrier::complete_tx::bytes [%0], [%1, {%3, %4}], [%2];"
               ::"r"(dst), "l"(tm), "r"(bar), "r"(c0), "r"(c1) : "memory");
}
__device__ __forceinline__ void tma3d(uint32_t dst, const CUtensorMap* tm, int c0, int c1, int c2, uint32_t bar) {
  asm volatile("cp.async.bulk.tensor.3d.shared::cluster.global.mbarrier::complete_tx::bytes [%0], [%1, {%3, %4, %5}], [%2];"
               ::"r"(dst), "l"(tm), "r"(bar), "r"(c0), "r"(c1), "r"(c2) : "memory");
}
__device__ __forceinline__ void tma2d_st(const CUtensorMap* tm, int c0, int c1, uint32_t src) {
  asm volatile("cp.async.bulk.tensor.2d.global.shared::cta.bulk_group [%0, {%2, %3}], [%1];" ::"l"(tm), "r"(src), "r"(c0), "r"(c1) : "memory");
}
__device__ __forceinline__ void tma3d_st(const CUtensorMap* tm, int c0, int c1, int c2, uint32_t src) {
  asm volatile("cp.async.bulk.tensor.3d.global.shared::cta.bulk_group [%0, {%2, %3, %4}], [%1];" ::"l"(tm), "r"(src), "r"(c0), "r"(c1), "r"(c2) : "memory");
}
__device__ __forceinline__ void bulk_g2s(uint32_t dst, const void* src, int bytes, uint32_t bar) {
  asm volatile("cp.async.bulk.shared::cluster.global.mbarrier::complete_tx::bytes [%0], [%1], %2, [%3];" ::"r"(dst), "l"(src), "r"(bytes), "r"(bar) : "memory");
}
__device__ __forceinline__ void bulk_commit() { asm volatile("cp.async.bulk.commit_group;" ::: "memory"); }
__device__ __forceinline__ void bulk_wait_read() { asm volatile("cp.async.bulk.wait_group.read 0;" ::: "memory"); }
__device__ __forceinline__ void bulk_wait_all() { asm volatile("cp.async.bulk.wait_group 0;" ::: "memory"); }
__device__ __forceinline__ void fence_async_smem() { asm volatile("fence.proxy.async.shared::cta;" ::: "memory"); }
__device__ __forceinline__ void fence_async_all() { asm volatile("fence.proxy.async;" ::: "memory"); }
__device__ __forceinline__ void fence_gpu() { asm volatile("fence.acq_rel.gpu;" ::: "memory"); }
#define bar_sync(id, n) asm volatile("bar.sync %0, %1;" ::"n"(id), "n"(n) : "memory")
#define bar_arrive(id, n) asm volatile("bar.arrive %0, %1;" ::"n"(id), "n"(n) : "memory")
__device__ __forceinline__ void wg_fence() { asm volatile("wgmma.fence.sync.aligned;" ::: "memory"); }
__device__ __forceinline__ void wg_commit() { asm volatile("wgmma.commit_group.sync.aligned;" ::: "memory"); }
template <int N> __device__ __forceinline__ void wg_wait() { asm volatile("wgmma.wait_group.sync.aligned %0;" ::"n"(N) : "memory"); }
__device__ __forceinline__ uint64_t mkdesc(uint32_t addr, uint32_t lbo, uint32_t sbo, int sw) {
  return (uint64_t)((addr & 0x3FFFF) >> 4) | ((uint64_t)(lbo >> 4) << 16) | ((uint64_t)(sbo >> 4) << 32) | ((uint64_t)sw << 62);
}
__device__ __forceinline__ uint32_t ldg32(const void* p) { uint32_t v; asm volatile("ld.global" LDQ ".b32 %0, [%1];" : "=r"(v) : "l"(p)); return v; }
template <int OFF> __device__ __forceinline__ uint32_t ldg32o(const void* p) { uint32_t v; asm volatile("ld.global" LDQ ".b32 %0, [%1+%2];" : "=r"(v) : "l"(p), "n"(OFF)); return v; }
template <int I> __device__ __forceinline__ void kv_loads(const void* kp, const void* vp, uint32_t (&kk)[16], uint32_t (&o)[16]) {
  kk[I] = ldg32o<I * DM * 2>(kp); o[I] = ldg32o<I * DM * 2>(vp);
  if constexpr (I < 15) kv_loads<I + 1>(kp, vp, kk, o);
}
__device__ __forceinline__ uint4 ldg128(const void* p) {
  uint4 v; asm volatile("ld.global" LDQ LDP ".v4.b32 {%0,%1,%2,%3}, [%4];" : "=r"(v.x), "=r"(v.y), "=r"(v.z), "=r"(v.w) : "l"(p)); return v;
}
__device__ __forceinline__ void stg128(void* p, uint32_t x, uint32_t y, uint32_t z, uint32_t w) {
  asm volatile("st.global.v4.b32 [%0], {%1,%2,%3,%4};" ::"l"(p), "r"(x), "r"(y), "r"(z), "r"(w) : "memory");
}
__device__ __forceinline__ uint4 ld_relaxed128(const void* p) {
  uint4 v; asm volatile("ld.relaxed.gpu.global.v4.b32 {%0,%1,%2,%3}, [%4];" : "=r"(v.x), "=r"(v.y), "=r"(v.z), "=r"(v.w) : "l"(p) : "memory"); return v;
}
__device__ __forceinline__ uint2 ld_relaxed64(const void* p) {
  uint2 v; asm volatile("ld.relaxed.gpu.global.v2.b32 {%0,%1}, [%2];" : "=r"(v.x), "=r"(v.y) : "l"(p) : "memory"); return v;
}
__device__ __forceinline__ uint4 ld_relaxed_b128(const void* p) {
  uint4 v; asm volatile("{\n.reg .b128 t;\nld.relaxed.gpu.global.b128 t, [%4];\nmov.b128 {%0,%1,%2,%3}, t;\n}" : "=r"(v.x), "=r"(v.y), "=r"(v.z), "=r"(v.w) : "l"(p) : "memory"); return v;
}
__device__ __forceinline__ void st_relaxed_b128(void* p, uint32_t x, uint32_t y, uint32_t z, uint32_t w) {
  asm volatile("{\n.reg .b128 t;\nmov.b128 t, {%1,%2,%3,%4};\nst.relaxed.gpu.global.b128 [%0], t;\n}" ::"l"(p), "r"(x), "r"(y), "r"(z), "r"(w) : "memory");
}
__device__ __forceinline__ void st_relaxed64(void* p, uint32_t x, uint32_t y) {
  asm volatile("{\n.reg .b64 t;\nmov.b64 t, {%1,%2};\nst.relaxed.gpu.global.b64 [%0], t;\n}" ::"l"(p), "r"(x), "r"(y) : "memory");
}
__device__ __forceinline__ void st_relaxed32(void* p, uint32_t x) { asm volatile("st.relaxed.gpu.global.b32 [%0], %1;" ::"l"(p), "r"(x) : "memory"); }
__device__ __forceinline__ uint32_t ld_relaxed32(const void* p) { uint32_t v; asm volatile("ld.relaxed.gpu.global.b32 %0, [%1];" : "=r"(v) : "l"(p) : "memory"); return v; }
__device__ __forceinline__ void st_relaxed128(void* p, uint32_t x, uint32_t y, uint32_t z, uint32_t w) {
  asm volatile("{\n.reg .b64 t, u;\nmov.b64 t, {%1,%2};\nmov.b64 u, {%3,%4};\nst.relaxed.gpu.global.v2.b64 [%0], {t, u};\n}" ::"l"(p), "r"(x), "r"(y), "r"(z), "r"(w) : "memory");
}
__device__ __forceinline__ void fence_release() { asm volatile("fence.proxy.async.global;\nfence.release.gpu;" ::: "memory"); }
__device__ __forceinline__ void fence_acquire() { asm volatile("fence.acquire.gpu;\nfence.proxy.async.global;" ::: "memory"); }
__device__ __forceinline__ void signal_cnt(int idx) { asm volatile("red.relaxed.gpu.global.add.u32 [%0], 1;" ::"l"(&g_cnt[idx * 32]) : "memory"); }
__device__ __forceinline__ void wait_cnt(int idx, unsigned target) {
  uint32_t n = 0;
#pragma unroll 1
  while (!__all_sync(0xffffffffu, (int)(ld_relaxed32(&g_cnt[idx * 32]) - target) >= 0)) {
    if (spin_guard(n, 0x100 + idx)) break;
  }
  fence_acquire();
}
__device__ __forceinline__ void bulk_s2g(void* dst, uint32_t src, int bytes) {
  asm volatile("cp.async.bulk.global.shared::cta.bulk_group [%0], [%1], %2;" ::"l"(dst), "r"(src), "r"(bytes) : "memory");
}
__device__ __forceinline__ void bulk_add_s2g(void* dst, uint32_t src, int bytes) {
  asm volatile("cp.reduce.async.bulk.global.shared::cta.bulk_group.add.noftz.bf16 [%0], [%1], %2;" ::"l"(dst), "r"(src), "r"(bytes) : "memory");
}
__device__ __forceinline__ void prefetch_l2(const void* p, int bytes) { asm volatile("cp.async.bulk.prefetch.L2.global [%0], %1;" ::"l"(p), "r"(bytes) : "memory"); }
__device__ __forceinline__ void prefetch_tile(const CUtensorMap* tm, int c0, int c1) {
  asm volatile("cp.async.bulk.prefetch.tensor.2d.L2.global.tile [%0, {%1, %2}];" ::"l"(tm), "r"(c0), "r"(c1) : "memory");
}
__device__ __forceinline__ void prefetch_map(const CUtensorMap* tm) { asm volatile("prefetch.tensormap [%0];" ::"l"(tm) : "memory"); }
__device__ __forceinline__ uint32_t pack_bf16(float lo, float hi) {
  uint32_t r; asm("cvt.rn.bf16x2.f32 %0, %1, %2;" : "=r"(r) : "f"(hi), "f"(lo)); return r;
}
__device__ __forceinline__ float bf_lo(uint32_t v) { return __uint_as_float(v << 16); }
__device__ __forceinline__ float bf_hi(uint32_t v) { return __uint_as_float(v & 0xFFFF0000u); }
__device__ __forceinline__ float bf_round(float x) { return __bfloat162float(__float2bfloat16_rn(x)); }
__device__ __forceinline__ uint32_t bmul2(uint32_t a, uint32_t b) { uint32_t r; asm("mul.rn.bf16x2 %0, %1, %2;" : "=r"(r) : "r"(a), "r"(b)); return r; }
__device__ __forceinline__ uint32_t bfma2(uint32_t a, uint32_t b, uint32_t c) { uint32_t r; asm("fma.rn.bf16x2 %0, %1, %2, %3;" : "=r"(r) : "r"(a), "r"(b), "r"(c)); return r; }
__device__ __forceinline__ uint32_t badd2(uint32_t a, uint32_t b) { uint32_t r; asm("add.rn.bf16x2 %0, %1, %2;" : "=r"(r) : "r"(a), "r"(b)); return r; }
__device__ __forceinline__ uint32_t bsub2(uint32_t a, uint32_t b) { uint32_t r; asm("sub.rn.bf16x2 %0, %1, %2;" : "=r"(r) : "r"(a), "r"(b)); return r; }
__device__ __forceinline__ float tanh_fast(float x) { float r; asm("tanh.approx.f32 %0, %1;" : "=f"(r) : "f"(x)); return r; }
__device__ __forceinline__ float rcp_fast(float x) { float r; asm("rcp.approx.ftz.f32 %0, %1;" : "=f"(r) : "f"(x)); return r; }
__device__ __forceinline__ float sqrt_fast(float x) { float r; asm("sqrt.approx.ftz.f32 %0, %1;" : "=f"(r) : "f"(x)); return r; }
__device__ __forceinline__ uint32_t lds32(uint32_t a) { uint32_t v; asm volatile("ld.shared.b32 %0, [%1];" : "=r"(v) : "r"(a)); return v; }
__device__ __forceinline__ uint4 lds128(uint32_t a) { uint4 v; asm volatile("ld.shared.v4.b32 {%0,%1,%2,%3}, [%4];" : "=r"(v.x), "=r"(v.y), "=r"(v.z), "=r"(v.w) : "r"(a)); return v; }
__device__ __forceinline__ float2 lds64f(uint32_t a) { float2 v; asm volatile("ld.shared.v2.f32 {%0,%1}, [%2];" : "=f"(v.x), "=f"(v.y) : "r"(a)); return v; }
__device__ __forceinline__ void sts64f(uint32_t a, float x, float y) { asm volatile("st.shared.v2.f32 [%0], {%1,%2};" ::"r"(a), "f"(x), "f"(y) : "memory"); }
__device__ __forceinline__ void sts32(uint32_t a, uint32_t x) { asm volatile("st.shared.b32 [%0], %1;" ::"r"(a), "r"(x) : "memory"); }
__device__ __forceinline__ void sts128(uint32_t a, uint32_t x, uint32_t y, uint32_t z, uint32_t w) { asm volatile("st.shared.v4.b32 [%0], {%1,%2,%3,%4};" ::"r"(a), "r"(x), "r"(y), "r"(z), "r"(w) : "memory"); }
__device__ __forceinline__ void stsm4(uint32_t a, uint32_t r0, uint32_t r1, uint32_t r2, uint32_t r3) {
  asm volatile("stmatrix.sync.aligned.m8n8.x4.shared.b16 [%0], {%1,%2,%3,%4};" ::"r"(a), "r"(r0), "r"(r1), "r"(r2), "r"(r3) : "memory");
}
__device__ __forceinline__ void stsm4t(uint32_t a, uint32_t r0, uint32_t r1, uint32_t r2, uint32_t r3) {
  asm volatile("stmatrix.sync.aligned.m8n8.x4.trans.shared.b16 [%0], {%1,%2,%3,%4};" ::"r"(a), "r"(r0), "r"(r1), "r"(r2), "r"(r3) : "memory");
}
__device__ __forceinline__ void stsm2(uint32_t a, uint32_t r0, uint32_t r1) {
  asm volatile("stmatrix.sync.aligned.m8n8.x2.shared.b16 [%0], {%1,%2};" ::"r"(a), "r"(r0), "r"(r1) : "memory");
}
__device__ __forceinline__ void ldsm4(uint32_t a, uint32_t& r0, uint32_t& r1, uint32_t& r2, uint32_t& r3) {
  asm volatile("ldmatrix.sync.aligned.m8n8.x4.shared.b16 {%0,%1,%2,%3}, [%4];" : "=r"(r0), "=r"(r1), "=r"(r2), "=r"(r3) : "r"(a) : "memory");
}
__device__ __forceinline__ void ldsm4t(uint32_t a, uint32_t& r0, uint32_t& r1, uint32_t& r2, uint32_t& r3) {
  asm volatile("ldmatrix.sync.aligned.m8n8.x4.trans.shared.b16 {%0,%1,%2,%3}, [%4];" : "=r"(r0), "=r"(r1), "=r"(r2), "=r"(r3) : "r"(a) : "memory");
}
__device__ __forceinline__ uint32_t mapa(uint32_t a, uint32_t rank) { uint32_t r; asm("mapa.shared::cluster.u32 %0, %1, %2;" : "=r"(r) : "r"(a), "r"(rank)); return r; }
__device__ __forceinline__ void mbar_arrive_remote(uint32_t a) { asm volatile("mbarrier.arrive.relaxed.cluster.shared::cluster.b64 _, [%0];" ::"r"(a) : "memory"); }
__device__ __forceinline__ void st_async128(uint32_t a, uint32_t x, uint32_t y, uint32_t z, uint32_t w, uint32_t bar) {
  asm volatile("st.async.weak.shared::cluster.mbarrier::complete_tx::bytes.v4.b32 [%0], {%1,%2,%3,%4}, [%5];" ::"r"(a), "r"(x), "r"(y), "r"(z), "r"(w), "r"(bar) : "memory");
}
#define TS(i)

#define TSKV
__device__ __forceinline__ void wg_ss_216(float (&d)[108], uint64_t da, uint64_t db, int sd) {
  asm volatile("{\n.reg .pred p;\nsetp.ne.b32 p, %110, 0;\n"
    "wgmma.mma_async.sync.aligned.m64n216k16.f32.bf16.bf16 {%0,%1,%2,%3,%4,%5,%6,%7,%8,%9,%10,%11,%12,%13,%14,%15,%16,%17,%18,%19,%20,%21,%22,%23,%24,%25,%26,%27,%28,%29,%30,%31,%32,%33,%34,%35,%36,%37,%38,%39,%40,%41,%42,%43,%44,%45,%46,%47,%48,%49,%50,%51,%52,%53,%54,%55,%56,%57,%58,%59,%60,%61,%62,%63,%64,%65,%66,%67,%68,%69,%70,%71,%72,%73,%74,%75,%76,%77,%78,%79,%80,%81,%82,%83,%84,%85,%86,%87,%88,%89,%90,%91,%92,%93,%94,%95,%96,%97,%98,%99,%100,%101,%102,%103,%104,%105,%106,%107}, %108, %109, p, 1, 1, 0, 1;\n}\n"
    : "+f"(d[0]),"+f"(d[1]),"+f"(d[2]),"+f"(d[3]),"+f"(d[4]),"+f"(d[5]),"+f"(d[6]),"+f"(d[7]),"+f"(d[8]),"+f"(d[9]),"+f"(d[10]),"+f"(d[11]),"+f"(d[12]),"+f"(d[13]),"+f"(d[14]),"+f"(d[15]),"+f"(d[16]),"+f"(d[17]),"+f"(d[18]),"+f"(d[19]),"+f"(d[20]),"+f"(d[21]),"+f"(d[22]),"+f"(d[23]),"+f"(d[24]),"+f"(d[25]),"+f"(d[26]),"+f"(d[27]),"+f"(d[28]),"+f"(d[29]),"+f"(d[30]),"+f"(d[31]),"+f"(d[32]),"+f"(d[33]),"+f"(d[34]),"+f"(d[35]),"+f"(d[36]),"+f"(d[37]),"+f"(d[38]),"+f"(d[39]),"+f"(d[40]),"+f"(d[41]),"+f"(d[42]),"+f"(d[43]),"+f"(d[44]),"+f"(d[45]),"+f"(d[46]),"+f"(d[47]),"+f"(d[48]),"+f"(d[49]),"+f"(d[50]),"+f"(d[51]),"+f"(d[52]),"+f"(d[53]),"+f"(d[54]),"+f"(d[55]),"+f"(d[56]),"+f"(d[57]),"+f"(d[58]),"+f"(d[59]),"+f"(d[60]),"+f"(d[61]),"+f"(d[62]),"+f"(d[63]),"+f"(d[64]),"+f"(d[65]),"+f"(d[66]),"+f"(d[67]),"+f"(d[68]),"+f"(d[69]),"+f"(d[70]),"+f"(d[71]),"+f"(d[72]),"+f"(d[73]),"+f"(d[74]),"+f"(d[75]),"+f"(d[76]),"+f"(d[77]),"+f"(d[78]),"+f"(d[79]),"+f"(d[80]),"+f"(d[81]),"+f"(d[82]),"+f"(d[83]),"+f"(d[84]),"+f"(d[85]),"+f"(d[86]),"+f"(d[87]),"+f"(d[88]),"+f"(d[89]),"+f"(d[90]),"+f"(d[91]),"+f"(d[92]),"+f"(d[93]),"+f"(d[94]),"+f"(d[95]),"+f"(d[96]),"+f"(d[97]),"+f"(d[98]),"+f"(d[99]),"+f"(d[100]),"+f"(d[101]),"+f"(d[102]),"+f"(d[103]),"+f"(d[104]),"+f"(d[105]),"+f"(d[106]),"+f"(d[107]) : "l"(da), "l"(db), "r"(sd));
}
__device__ __forceinline__ void wg_ss_160(float (&d)[80], uint64_t da, uint64_t db, int sd) {
  asm volatile("{\n.reg .pred p;\nsetp.ne.b32 p, %82, 0;\n"
    "wgmma.mma_async.sync.aligned.m64n160k16.f32.bf16.bf16 {%0,%1,%2,%3,%4,%5,%6,%7,%8,%9,%10,%11,%12,%13,%14,%15,%16,%17,%18,%19,%20,%21,%22,%23,%24,%25,%26,%27,%28,%29,%30,%31,%32,%33,%34,%35,%36,%37,%38,%39,%40,%41,%42,%43,%44,%45,%46,%47,%48,%49,%50,%51,%52,%53,%54,%55,%56,%57,%58,%59,%60,%61,%62,%63,%64,%65,%66,%67,%68,%69,%70,%71,%72,%73,%74,%75,%76,%77,%78,%79}, %80, %81, p, 1, 1, 0, 1;\n}\n"
    : "+f"(d[0]),"+f"(d[1]),"+f"(d[2]),"+f"(d[3]),"+f"(d[4]),"+f"(d[5]),"+f"(d[6]),"+f"(d[7]),"+f"(d[8]),"+f"(d[9]),"+f"(d[10]),"+f"(d[11]),"+f"(d[12]),"+f"(d[13]),"+f"(d[14]),"+f"(d[15]),"+f"(d[16]),"+f"(d[17]),"+f"(d[18]),"+f"(d[19]),"+f"(d[20]),"+f"(d[21]),"+f"(d[22]),"+f"(d[23]),"+f"(d[24]),"+f"(d[25]),"+f"(d[26]),"+f"(d[27]),"+f"(d[28]),"+f"(d[29]),"+f"(d[30]),"+f"(d[31]),"+f"(d[32]),"+f"(d[33]),"+f"(d[34]),"+f"(d[35]),"+f"(d[36]),"+f"(d[37]),"+f"(d[38]),"+f"(d[39]),"+f"(d[40]),"+f"(d[41]),"+f"(d[42]),"+f"(d[43]),"+f"(d[44]),"+f"(d[45]),"+f"(d[46]),"+f"(d[47]),"+f"(d[48]),"+f"(d[49]),"+f"(d[50]),"+f"(d[51]),"+f"(d[52]),"+f"(d[53]),"+f"(d[54]),"+f"(d[55]),"+f"(d[56]),"+f"(d[57]),"+f"(d[58]),"+f"(d[59]),"+f"(d[60]),"+f"(d[61]),"+f"(d[62]),"+f"(d[63]),"+f"(d[64]),"+f"(d[65]),"+f"(d[66]),"+f"(d[67]),"+f"(d[68]),"+f"(d[69]),"+f"(d[70]),"+f"(d[71]),"+f"(d[72]),"+f"(d[73]),"+f"(d[74]),"+f"(d[75]),"+f"(d[76]),"+f"(d[77]),"+f"(d[78]),"+f"(d[79]) : "l"(da), "l"(db), "r"(sd));
}
__device__ __forceinline__ void wg_rs_216(float (&d)[108], uint32_t a0, uint32_t a1, uint32_t a2, uint32_t a3, uint64_t db) {
  asm volatile("{\n.reg .pred p;\nsetp.ne.b32 p, 1, 0;\n"
    "wgmma.mma_async.sync.aligned.m64n216k16.f32.bf16.bf16 {%0,%1,%2,%3,%4,%5,%6,%7,%8,%9,%10,%11,%12,%13,%14,%15,%16,%17,%18,%19,%20,%21,%22,%23,%24,%25,%26,%27,%28,%29,%30,%31,%32,%33,%34,%35,%36,%37,%38,%39,%40,%41,%42,%43,%44,%45,%46,%47,%48,%49,%50,%51,%52,%53,%54,%55,%56,%57,%58,%59,%60,%61,%62,%63,%64,%65,%66,%67,%68,%69,%70,%71,%72,%73,%74,%75,%76,%77,%78,%79,%80,%81,%82,%83,%84,%85,%86,%87,%88,%89,%90,%91,%92,%93,%94,%95,%96,%97,%98,%99,%100,%101,%102,%103,%104,%105,%106,%107}, {%108,%109,%110,%111}, %112, p, 1, 1, 1;\n}\n"
    : "+f"(d[0]),"+f"(d[1]),"+f"(d[2]),"+f"(d[3]),"+f"(d[4]),"+f"(d[5]),"+f"(d[6]),"+f"(d[7]),"+f"(d[8]),"+f"(d[9]),"+f"(d[10]),"+f"(d[11]),"+f"(d[12]),"+f"(d[13]),"+f"(d[14]),"+f"(d[15]),"+f"(d[16]),"+f"(d[17]),"+f"(d[18]),"+f"(d[19]),"+f"(d[20]),"+f"(d[21]),"+f"(d[22]),"+f"(d[23]),"+f"(d[24]),"+f"(d[25]),"+f"(d[26]),"+f"(d[27]),"+f"(d[28]),"+f"(d[29]),"+f"(d[30]),"+f"(d[31]),"+f"(d[32]),"+f"(d[33]),"+f"(d[34]),"+f"(d[35]),"+f"(d[36]),"+f"(d[37]),"+f"(d[38]),"+f"(d[39]),"+f"(d[40]),"+f"(d[41]),"+f"(d[42]),"+f"(d[43]),"+f"(d[44]),"+f"(d[45]),"+f"(d[46]),"+f"(d[47]),"+f"(d[48]),"+f"(d[49]),"+f"(d[50]),"+f"(d[51]),"+f"(d[52]),"+f"(d[53]),"+f"(d[54]),"+f"(d[55]),"+f"(d[56]),"+f"(d[57]),"+f"(d[58]),"+f"(d[59]),"+f"(d[60]),"+f"(d[61]),"+f"(d[62]),"+f"(d[63]),"+f"(d[64]),"+f"(d[65]),"+f"(d[66]),"+f"(d[67]),"+f"(d[68]),"+f"(d[69]),"+f"(d[70]),"+f"(d[71]),"+f"(d[72]),"+f"(d[73]),"+f"(d[74]),"+f"(d[75]),"+f"(d[76]),"+f"(d[77]),"+f"(d[78]),"+f"(d[79]),"+f"(d[80]),"+f"(d[81]),"+f"(d[82]),"+f"(d[83]),"+f"(d[84]),"+f"(d[85]),"+f"(d[86]),"+f"(d[87]),"+f"(d[88]),"+f"(d[89]),"+f"(d[90]),"+f"(d[91]),"+f"(d[92]),"+f"(d[93]),"+f"(d[94]),"+f"(d[95]),"+f"(d[96]),"+f"(d[97]),"+f"(d[98]),"+f"(d[99]),"+f"(d[100]),"+f"(d[101]),"+f"(d[102]),"+f"(d[103]),"+f"(d[104]),"+f"(d[105]),"+f"(d[106]),"+f"(d[107]) : "r"(a0), "r"(a1), "r"(a2), "r"(a3), "l"(db));
}
__device__ __forceinline__ void wg_cv_0_0(float (&d)[128], uint32_t a0, uint32_t a1, uint32_t a2, uint32_t a3, uint64_t db) {
  asm volatile("{\n.reg .pred p;\nsetp.ne.b32 p, 0, 0;\n"
    "wgmma.mma_async.sync.aligned.m64n32k16.f32.bf16.bf16 {%0,%1,%2,%3,%4,%5,%6,%7,%8,%9,%10,%11,%12,%13,%14,%15}, {%16,%17,%18,%19}, %20, p, 1, 1, 0;\n}\n"
    : "+f"(d[0]),"+f"(d[1]),"+f"(d[2]),"+f"(d[3]),"+f"(d[4]),"+f"(d[5]),"+f"(d[6]),"+f"(d[7]),"+f"(d[8]),"+f"(d[9]),"+f"(d[10]),"+f"(d[11]),"+f"(d[12]),"+f"(d[13]),"+f"(d[14]),"+f"(d[15]) : "r"(a0), "r"(a1), "r"(a2), "r"(a3), "l"(db));
}
__device__ __forceinline__ void wg_cv_0_1(float (&d)[128], uint32_t a0, uint32_t a1, uint32_t a2, uint32_t a3, uint64_t db) {
  asm volatile("{\n.reg .pred p;\nsetp.ne.b32 p, 1, 0;\n"
    "wgmma.mma_async.sync.aligned.m64n32k16.f32.bf16.bf16 {%0,%1,%2,%3,%4,%5,%6,%7,%8,%9,%10,%11,%12,%13,%14,%15}, {%16,%17,%18,%19}, %20, p, 1, 1, 0;\n}\n"
    : "+f"(d[0]),"+f"(d[1]),"+f"(d[2]),"+f"(d[3]),"+f"(d[4]),"+f"(d[5]),"+f"(d[6]),"+f"(d[7]),"+f"(d[8]),"+f"(d[9]),"+f"(d[10]),"+f"(d[11]),"+f"(d[12]),"+f"(d[13]),"+f"(d[14]),"+f"(d[15]) : "r"(a0), "r"(a1), "r"(a2), "r"(a3), "l"(db));
}
__device__ __forceinline__ void wg_cv_1_0(float (&d)[128], uint32_t a0, uint32_t a1, uint32_t a2, uint32_t a3, uint64_t db) {
  asm volatile("{\n.reg .pred p;\nsetp.ne.b32 p, 0, 0;\n"
    "wgmma.mma_async.sync.aligned.m64n32k16.f32.bf16.bf16 {%0,%1,%2,%3,%4,%5,%6,%7,%8,%9,%10,%11,%12,%13,%14,%15}, {%16,%17,%18,%19}, %20, p, 1, 1, 0;\n}\n"
    : "+f"(d[16]),"+f"(d[17]),"+f"(d[18]),"+f"(d[19]),"+f"(d[20]),"+f"(d[21]),"+f"(d[22]),"+f"(d[23]),"+f"(d[24]),"+f"(d[25]),"+f"(d[26]),"+f"(d[27]),"+f"(d[28]),"+f"(d[29]),"+f"(d[30]),"+f"(d[31]) : "r"(a0), "r"(a1), "r"(a2), "r"(a3), "l"(db));
}
__device__ __forceinline__ void wg_cv_1_1(float (&d)[128], uint32_t a0, uint32_t a1, uint32_t a2, uint32_t a3, uint64_t db) {
  asm volatile("{\n.reg .pred p;\nsetp.ne.b32 p, 1, 0;\n"
    "wgmma.mma_async.sync.aligned.m64n32k16.f32.bf16.bf16 {%0,%1,%2,%3,%4,%5,%6,%7,%8,%9,%10,%11,%12,%13,%14,%15}, {%16,%17,%18,%19}, %20, p, 1, 1, 0;\n}\n"
    : "+f"(d[16]),"+f"(d[17]),"+f"(d[18]),"+f"(d[19]),"+f"(d[20]),"+f"(d[21]),"+f"(d[22]),"+f"(d[23]),"+f"(d[24]),"+f"(d[25]),"+f"(d[26]),"+f"(d[27]),"+f"(d[28]),"+f"(d[29]),"+f"(d[30]),"+f"(d[31]) : "r"(a0), "r"(a1), "r"(a2), "r"(a3), "l"(db));
}
__device__ __forceinline__ void wg_cv_2_0(float (&d)[128], uint32_t a0, uint32_t a1, uint32_t a2, uint32_t a3, uint64_t db) {
  asm volatile("{\n.reg .pred p;\nsetp.ne.b32 p, 0, 0;\n"
    "wgmma.mma_async.sync.aligned.m64n32k16.f32.bf16.bf16 {%0,%1,%2,%3,%4,%5,%6,%7,%8,%9,%10,%11,%12,%13,%14,%15}, {%16,%17,%18,%19}, %20, p, 1, 1, 0;\n}\n"
    : "+f"(d[32]),"+f"(d[33]),"+f"(d[34]),"+f"(d[35]),"+f"(d[36]),"+f"(d[37]),"+f"(d[38]),"+f"(d[39]),"+f"(d[40]),"+f"(d[41]),"+f"(d[42]),"+f"(d[43]),"+f"(d[44]),"+f"(d[45]),"+f"(d[46]),"+f"(d[47]) : "r"(a0), "r"(a1), "r"(a2), "r"(a3), "l"(db));
}
__device__ __forceinline__ void wg_cv_2_1(float (&d)[128], uint32_t a0, uint32_t a1, uint32_t a2, uint32_t a3, uint64_t db) {
  asm volatile("{\n.reg .pred p;\nsetp.ne.b32 p, 1, 0;\n"
    "wgmma.mma_async.sync.aligned.m64n32k16.f32.bf16.bf16 {%0,%1,%2,%3,%4,%5,%6,%7,%8,%9,%10,%11,%12,%13,%14,%15}, {%16,%17,%18,%19}, %20, p, 1, 1, 0;\n}\n"
    : "+f"(d[32]),"+f"(d[33]),"+f"(d[34]),"+f"(d[35]),"+f"(d[36]),"+f"(d[37]),"+f"(d[38]),"+f"(d[39]),"+f"(d[40]),"+f"(d[41]),"+f"(d[42]),"+f"(d[43]),"+f"(d[44]),"+f"(d[45]),"+f"(d[46]),"+f"(d[47]) : "r"(a0), "r"(a1), "r"(a2), "r"(a3), "l"(db));
}
__device__ __forceinline__ void wg_cv_3_0(float (&d)[128], uint32_t a0, uint32_t a1, uint32_t a2, uint32_t a3, uint64_t db) {
  asm volatile("{\n.reg .pred p;\nsetp.ne.b32 p, 0, 0;\n"
    "wgmma.mma_async.sync.aligned.m64n32k16.f32.bf16.bf16 {%0,%1,%2,%3,%4,%5,%6,%7,%8,%9,%10,%11,%12,%13,%14,%15}, {%16,%17,%18,%19}, %20, p, 1, 1, 0;\n}\n"
    : "+f"(d[48]),"+f"(d[49]),"+f"(d[50]),"+f"(d[51]),"+f"(d[52]),"+f"(d[53]),"+f"(d[54]),"+f"(d[55]),"+f"(d[56]),"+f"(d[57]),"+f"(d[58]),"+f"(d[59]),"+f"(d[60]),"+f"(d[61]),"+f"(d[62]),"+f"(d[63]) : "r"(a0), "r"(a1), "r"(a2), "r"(a3), "l"(db));
}
__device__ __forceinline__ void wg_cv_3_1(float (&d)[128], uint32_t a0, uint32_t a1, uint32_t a2, uint32_t a3, uint64_t db) {
  asm volatile("{\n.reg .pred p;\nsetp.ne.b32 p, 1, 0;\n"
    "wgmma.mma_async.sync.aligned.m64n32k16.f32.bf16.bf16 {%0,%1,%2,%3,%4,%5,%6,%7,%8,%9,%10,%11,%12,%13,%14,%15}, {%16,%17,%18,%19}, %20, p, 1, 1, 0;\n}\n"
    : "+f"(d[48]),"+f"(d[49]),"+f"(d[50]),"+f"(d[51]),"+f"(d[52]),"+f"(d[53]),"+f"(d[54]),"+f"(d[55]),"+f"(d[56]),"+f"(d[57]),"+f"(d[58]),"+f"(d[59]),"+f"(d[60]),"+f"(d[61]),"+f"(d[62]),"+f"(d[63]) : "r"(a0), "r"(a1), "r"(a2), "r"(a3), "l"(db));
}
__device__ __forceinline__ void wg_cv_4_0(float (&d)[128], uint32_t a0, uint32_t a1, uint32_t a2, uint32_t a3, uint64_t db) {
  asm volatile("{\n.reg .pred p;\nsetp.ne.b32 p, 0, 0;\n"
    "wgmma.mma_async.sync.aligned.m64n32k16.f32.bf16.bf16 {%0,%1,%2,%3,%4,%5,%6,%7,%8,%9,%10,%11,%12,%13,%14,%15}, {%16,%17,%18,%19}, %20, p, 1, 1, 0;\n}\n"
    : "+f"(d[64]),"+f"(d[65]),"+f"(d[66]),"+f"(d[67]),"+f"(d[68]),"+f"(d[69]),"+f"(d[70]),"+f"(d[71]),"+f"(d[72]),"+f"(d[73]),"+f"(d[74]),"+f"(d[75]),"+f"(d[76]),"+f"(d[77]),"+f"(d[78]),"+f"(d[79]) : "r"(a0), "r"(a1), "r"(a2), "r"(a3), "l"(db));
}
__device__ __forceinline__ void wg_cv_4_1(float (&d)[128], uint32_t a0, uint32_t a1, uint32_t a2, uint32_t a3, uint64_t db) {
  asm volatile("{\n.reg .pred p;\nsetp.ne.b32 p, 1, 0;\n"
    "wgmma.mma_async.sync.aligned.m64n32k16.f32.bf16.bf16 {%0,%1,%2,%3,%4,%5,%6,%7,%8,%9,%10,%11,%12,%13,%14,%15}, {%16,%17,%18,%19}, %20, p, 1, 1, 0;\n}\n"
    : "+f"(d[64]),"+f"(d[65]),"+f"(d[66]),"+f"(d[67]),"+f"(d[68]),"+f"(d[69]),"+f"(d[70]),"+f"(d[71]),"+f"(d[72]),"+f"(d[73]),"+f"(d[74]),"+f"(d[75]),"+f"(d[76]),"+f"(d[77]),"+f"(d[78]),"+f"(d[79]) : "r"(a0), "r"(a1), "r"(a2), "r"(a3), "l"(db));
}
__device__ __forceinline__ void wg_cv_5_0(float (&d)[128], uint32_t a0, uint32_t a1, uint32_t a2, uint32_t a3, uint64_t db) {
  asm volatile("{\n.reg .pred p;\nsetp.ne.b32 p, 0, 0;\n"
    "wgmma.mma_async.sync.aligned.m64n32k16.f32.bf16.bf16 {%0,%1,%2,%3,%4,%5,%6,%7,%8,%9,%10,%11,%12,%13,%14,%15}, {%16,%17,%18,%19}, %20, p, 1, 1, 0;\n}\n"
    : "+f"(d[80]),"+f"(d[81]),"+f"(d[82]),"+f"(d[83]),"+f"(d[84]),"+f"(d[85]),"+f"(d[86]),"+f"(d[87]),"+f"(d[88]),"+f"(d[89]),"+f"(d[90]),"+f"(d[91]),"+f"(d[92]),"+f"(d[93]),"+f"(d[94]),"+f"(d[95]) : "r"(a0), "r"(a1), "r"(a2), "r"(a3), "l"(db));
}
__device__ __forceinline__ void wg_cv_5_1(float (&d)[128], uint32_t a0, uint32_t a1, uint32_t a2, uint32_t a3, uint64_t db) {
  asm volatile("{\n.reg .pred p;\nsetp.ne.b32 p, 1, 0;\n"
    "wgmma.mma_async.sync.aligned.m64n32k16.f32.bf16.bf16 {%0,%1,%2,%3,%4,%5,%6,%7,%8,%9,%10,%11,%12,%13,%14,%15}, {%16,%17,%18,%19}, %20, p, 1, 1, 0;\n}\n"
    : "+f"(d[80]),"+f"(d[81]),"+f"(d[82]),"+f"(d[83]),"+f"(d[84]),"+f"(d[85]),"+f"(d[86]),"+f"(d[87]),"+f"(d[88]),"+f"(d[89]),"+f"(d[90]),"+f"(d[91]),"+f"(d[92]),"+f"(d[93]),"+f"(d[94]),"+f"(d[95]) : "r"(a0), "r"(a1), "r"(a2), "r"(a3), "l"(db));
}
__device__ __forceinline__ void wg_cv_6_0(float (&d)[128], uint32_t a0, uint32_t a1, uint32_t a2, uint32_t a3, uint64_t db) {
  asm volatile("{\n.reg .pred p;\nsetp.ne.b32 p, 0, 0;\n"
    "wgmma.mma_async.sync.aligned.m64n32k16.f32.bf16.bf16 {%0,%1,%2,%3,%4,%5,%6,%7,%8,%9,%10,%11,%12,%13,%14,%15}, {%16,%17,%18,%19}, %20, p, 1, 1, 0;\n}\n"
    : "+f"(d[96]),"+f"(d[97]),"+f"(d[98]),"+f"(d[99]),"+f"(d[100]),"+f"(d[101]),"+f"(d[102]),"+f"(d[103]),"+f"(d[104]),"+f"(d[105]),"+f"(d[106]),"+f"(d[107]),"+f"(d[108]),"+f"(d[109]),"+f"(d[110]),"+f"(d[111]) : "r"(a0), "r"(a1), "r"(a2), "r"(a3), "l"(db));
}
__device__ __forceinline__ void wg_cv_6_1(float (&d)[128], uint32_t a0, uint32_t a1, uint32_t a2, uint32_t a3, uint64_t db) {
  asm volatile("{\n.reg .pred p;\nsetp.ne.b32 p, 1, 0;\n"
    "wgmma.mma_async.sync.aligned.m64n32k16.f32.bf16.bf16 {%0,%1,%2,%3,%4,%5,%6,%7,%8,%9,%10,%11,%12,%13,%14,%15}, {%16,%17,%18,%19}, %20, p, 1, 1, 0;\n}\n"
    : "+f"(d[96]),"+f"(d[97]),"+f"(d[98]),"+f"(d[99]),"+f"(d[100]),"+f"(d[101]),"+f"(d[102]),"+f"(d[103]),"+f"(d[104]),"+f"(d[105]),"+f"(d[106]),"+f"(d[107]),"+f"(d[108]),"+f"(d[109]),"+f"(d[110]),"+f"(d[111]) : "r"(a0), "r"(a1), "r"(a2), "r"(a3), "l"(db));
}
__device__ __forceinline__ void wg_cv_7_0(float (&d)[128], uint32_t a0, uint32_t a1, uint32_t a2, uint32_t a3, uint64_t db) {
  asm volatile("{\n.reg .pred p;\nsetp.ne.b32 p, 0, 0;\n"
    "wgmma.mma_async.sync.aligned.m64n32k16.f32.bf16.bf16 {%0,%1,%2,%3,%4,%5,%6,%7,%8,%9,%10,%11,%12,%13,%14,%15}, {%16,%17,%18,%19}, %20, p, 1, 1, 0;\n}\n"
    : "+f"(d[112]),"+f"(d[113]),"+f"(d[114]),"+f"(d[115]),"+f"(d[116]),"+f"(d[117]),"+f"(d[118]),"+f"(d[119]),"+f"(d[120]),"+f"(d[121]),"+f"(d[122]),"+f"(d[123]),"+f"(d[124]),"+f"(d[125]),"+f"(d[126]),"+f"(d[127]) : "r"(a0), "r"(a1), "r"(a2), "r"(a3), "l"(db));
}
__device__ __forceinline__ void wg_cv_7_1(float (&d)[128], uint32_t a0, uint32_t a1, uint32_t a2, uint32_t a3, uint64_t db) {
  asm volatile("{\n.reg .pred p;\nsetp.ne.b32 p, 1, 0;\n"
    "wgmma.mma_async.sync.aligned.m64n32k16.f32.bf16.bf16 {%0,%1,%2,%3,%4,%5,%6,%7,%8,%9,%10,%11,%12,%13,%14,%15}, {%16,%17,%18,%19}, %20, p, 1, 1, 0;\n}\n"
    : "+f"(d[112]),"+f"(d[113]),"+f"(d[114]),"+f"(d[115]),"+f"(d[116]),"+f"(d[117]),"+f"(d[118]),"+f"(d[119]),"+f"(d[120]),"+f"(d[121]),"+f"(d[122]),"+f"(d[123]),"+f"(d[124]),"+f"(d[125]),"+f"(d[126]),"+f"(d[127]) : "r"(a0), "r"(a1), "r"(a2), "r"(a3), "l"(db));
}
template <class F> __device__ __forceinline__ void conv_chain_1(float (&d)[128], uint32_t (&a)[64], uint64_t db, uint32_t ab, F hand) {
  wg_cv_7_0(d, a[60], a[61], a[62], a[63], db + (uint64_t)(0));
  wg_cv_6_0(d, a[52], a[53], a[54], a[55], db + (uint64_t)(0));
  wg_cv_7_1(d, a[56], a[57], a[58], a[59], db + (uint64_t)(16));
  wg_cv_5_0(d, a[44], a[45], a[46], a[47], db + (uint64_t)(0));
  wg_cv_6_1(d, a[48], a[49], a[50], a[51], db + (uint64_t)(16));
  wg_cv_7_1(d, a[52], a[53], a[54], a[55], db + (uint64_t)(32));
  wg_cv_5_1(d, a[40], a[41], a[42], a[43], db + (uint64_t)(16));
  wg_cv_6_1(d, a[44], a[45], a[46], a[47], db + (uint64_t)(32));
  wg_cv_7_1(d, a[48], a[49], a[50], a[51], db + (uint64_t)(48));
  wg_cv_6_1(d, a[40], a[41], a[42], a[43], db + (uint64_t)(48));
  wg_cv_7_1(d, a[44], a[45], a[46], a[47], db + (uint64_t)(64));
  wg_cv_7_1(d, a[40], a[41], a[42], a[43], db + (uint64_t)(80));
  wg_commit();
  wg_cv_7_1(d, a[36], a[37], a[38], a[39], db + (uint64_t)(96));
  wg_cv_6_1(d, a[36], a[37], a[38], a[39], db + (uint64_t)(64));
  wg_cv_5_1(d, a[36], a[37], a[38], a[39], db + (uint64_t)(32));
  wg_cv_4_0(d, a[36], a[37], a[38], a[39], db + (uint64_t)(0));
  wg_commit(); wg_wait<1>();
  wg_cv_7_1(d, a[32], a[33], a[34], a[35], db + (uint64_t)(112));
  wg_cv_6_1(d, a[32], a[33], a[34], a[35], db + (uint64_t)(80));
  wg_cv_5_1(d, a[32], a[33], a[34], a[35], db + (uint64_t)(48));
  a[60] = lds32(ab + (3840));
  a[61] = lds32(ab + (3968));
  a[62] = lds32(ab + (3824));
  a[63] = lds32(ab + (3952));
  wg_cv_4_1(d, a[32], a[33], a[34], a[35], db + (uint64_t)(16));
  wg_cv_7_1(d, a[28], a[29], a[30], a[31], db + (uint64_t)(128));
  wg_cv_6_1(d, a[28], a[29], a[30], a[31], db + (uint64_t)(96));
  wg_cv_5_1(d, a[28], a[29], a[30], a[31], db + (uint64_t)(64));
  a[56] = lds32(ab + (3584));
  a[57] = lds32(ab + (3712));
  a[58] = lds32(ab + (3568));
  a[59] = lds32(ab + (3696));
  wg_cv_4_1(d, a[28], a[29], a[30], a[31], db + (uint64_t)(32));
  wg_cv_3_0(d, a[28], a[29], a[30], a[31], db + (uint64_t)(0));
  wg_cv_7_1(d, a[24], a[25], a[26], a[27], db + (uint64_t)(144));
  wg_cv_6_1(d, a[24], a[25], a[26], a[27], db + (uint64_t)(112));
  a[52] = lds32(ab + (3328));
  a[53] = lds32(ab + (3456));
  a[54] = lds32(ab + (3312));
  a[55] = lds32(ab + (3440));
  wg_cv_5_1(d, a[24], a[25], a[26], a[27], db + (uint64_t)(80));
  wg_cv_4_1(d, a[24], a[25], a[26], a[27], db + (uint64_t)(48));
  wg_cv_3_1(d, a[24], a[25], a[26], a[27], db + (uint64_t)(16));
  wg_commit();
  wg_cv_7_1(d, a[20], a[21], a[22], a[23], db + (uint64_t)(160));
  wg_cv_6_1(d, a[20], a[21], a[22], a[23], db + (uint64_t)(128));
  wg_cv_5_1(d, a[20], a[21], a[22], a[23], db + (uint64_t)(96));
  wg_cv_4_1(d, a[20], a[21], a[22], a[23], db + (uint64_t)(64));
  wg_commit(); wg_wait<1>();
  a[48] = lds32(ab + (3072));
  a[49] = lds32(ab + (3200));
  a[50] = lds32(ab + (3056));
  a[51] = lds32(ab + (3184));
  wg_cv_3_1(d, a[20], a[21], a[22], a[23], db + (uint64_t)(32));
  wg_cv_2_0(d, a[20], a[21], a[22], a[23], db + (uint64_t)(0));
  wg_cv_7_1(d, a[16], a[17], a[18], a[19], db + (uint64_t)(176));
  wg_cv_6_1(d, a[16], a[17], a[18], a[19], db + (uint64_t)(144));
  a[44] = lds32(ab + (2816));
  a[45] = lds32(ab + (2944));
  a[46] = lds32(ab + (2800));
  a[47] = lds32(ab + (2928));
  wg_cv_5_1(d, a[16], a[17], a[18], a[19], db + (uint64_t)(112));
  wg_cv_4_1(d, a[16], a[17], a[18], a[19], db + (uint64_t)(80));
  wg_cv_3_1(d, a[16], a[17], a[18], a[19], db + (uint64_t)(48));
  wg_cv_2_1(d, a[16], a[17], a[18], a[19], db + (uint64_t)(16));
  a[40] = lds32(ab + (2560));
  a[41] = lds32(ab + (2688));
  a[42] = lds32(ab + (2544));
  a[43] = lds32(ab + (2672));
  wg_cv_7_1(d, a[12], a[13], a[14], a[15], db + (uint64_t)(192));
  wg_cv_6_1(d, a[12], a[13], a[14], a[15], db + (uint64_t)(160));
  wg_cv_5_1(d, a[12], a[13], a[14], a[15], db + (uint64_t)(128));
  wg_cv_4_1(d, a[12], a[13], a[14], a[15], db + (uint64_t)(96));
  a[36] = lds32(ab + (2304));
  a[37] = lds32(ab + (2432));
  a[38] = lds32(ab + (2288));
  a[39] = lds32(ab + (2416));
  wg_cv_3_1(d, a[12], a[13], a[14], a[15], db + (uint64_t)(64));
  wg_cv_2_1(d, a[12], a[13], a[14], a[15], db + (uint64_t)(32));
  wg_cv_1_0(d, a[12], a[13], a[14], a[15], db + (uint64_t)(0));
  wg_cv_7_1(d, a[8], a[9], a[10], a[11], db + (uint64_t)(208));
  a[32] = lds32(ab + (2048));
  a[33] = lds32(ab + (2176));
  a[34] = lds32(ab + (2032));
  a[35] = lds32(ab + (2160));
  wg_cv_6_1(d, a[8], a[9], a[10], a[11], db + (uint64_t)(176));
  wg_cv_5_1(d, a[8], a[9], a[10], a[11], db + (uint64_t)(144));
  wg_cv_4_1(d, a[8], a[9], a[10], a[11], db + (uint64_t)(112));
  wg_cv_3_1(d, a[8], a[9], a[10], a[11], db + (uint64_t)(80));
  a[28] = lds32(ab + (1792));
  a[29] = lds32(ab + (1920));
  a[30] = lds32(ab + (1776));
  a[31] = lds32(ab + (1904));
  wg_cv_2_1(d, a[8], a[9], a[10], a[11], db + (uint64_t)(48));
  wg_cv_1_1(d, a[8], a[9], a[10], a[11], db + (uint64_t)(16));
  wg_commit();
  wg_cv_7_1(d, a[4], a[5], a[6], a[7], db + (uint64_t)(224));
  wg_cv_6_1(d, a[4], a[5], a[6], a[7], db + (uint64_t)(192));
  wg_cv_5_1(d, a[4], a[5], a[6], a[7], db + (uint64_t)(160));
  wg_cv_4_1(d, a[4], a[5], a[6], a[7], db + (uint64_t)(128));
  wg_commit(); wg_wait<1>();
  a[24] = lds32(ab + (1536));
  a[25] = lds32(ab + (1664));
  a[26] = lds32(ab + (1520));
  a[27] = lds32(ab + (1648));
  hand();
  wg_cv_3_1(d, a[4], a[5], a[6], a[7], db + (uint64_t)(96));
  wg_cv_2_1(d, a[4], a[5], a[6], a[7], db + (uint64_t)(64));
  wg_cv_1_1(d, a[4], a[5], a[6], a[7], db + (uint64_t)(32));
  wg_cv_0_0(d, a[4], a[5], a[6], a[7], db + (uint64_t)(0));
  a[20] = lds32(ab + (1280));
  a[21] = lds32(ab + (1408));
  a[22] = lds32(ab + (1264));
  a[23] = lds32(ab + (1392));
  wg_cv_7_1(d, a[0], a[1], a[2], a[3], db + (uint64_t)(240));
  wg_cv_6_1(d, a[0], a[1], a[2], a[3], db + (uint64_t)(208));
  wg_cv_5_1(d, a[0], a[1], a[2], a[3], db + (uint64_t)(176));
  wg_cv_4_1(d, a[0], a[1], a[2], a[3], db + (uint64_t)(144));
  a[16] = lds32(ab + (1024));
  a[17] = lds32(ab + (1152));
  a[18] = lds32(ab + (1008));
  a[19] = lds32(ab + (1136));
  wg_cv_3_1(d, a[0], a[1], a[2], a[3], db + (uint64_t)(112));
  wg_cv_2_1(d, a[0], a[1], a[2], a[3], db + (uint64_t)(80));
  wg_cv_1_1(d, a[0], a[1], a[2], a[3], db + (uint64_t)(48));
  wg_cv_0_1(d, a[0], a[1], a[2], a[3], db + (uint64_t)(16));
  wg_commit();
  a[12] = lds32(ab + (768));
  a[13] = lds32(ab + (896));
  a[14] = lds32(ab + (752));
  a[15] = lds32(ab + (880));
  a[8] = lds32(ab + (512));
  a[9] = lds32(ab + (640));
  a[10] = lds32(ab + (496));
  a[11] = lds32(ab + (624));
}
template <class F> __device__ __forceinline__ void conv_chain_0(float (&d)[128], uint32_t (&a)[64], uint64_t db, uint32_t ab, F hand) {
  wg_cv_7_0(d, a[60], a[61], a[62], a[63], db + (uint64_t)(0));
  wg_cv_6_0(d, a[52], a[53], a[54], a[55], db + (uint64_t)(0));
  wg_cv_7_1(d, a[56], a[57], a[58], a[59], db + (uint64_t)(16));
  wg_cv_5_0(d, a[44], a[45], a[46], a[47], db + (uint64_t)(0));
  wg_cv_6_1(d, a[48], a[49], a[50], a[51], db + (uint64_t)(16));
  wg_cv_7_1(d, a[52], a[53], a[54], a[55], db + (uint64_t)(32));
  wg_cv_5_1(d, a[40], a[41], a[42], a[43], db + (uint64_t)(16));
  wg_cv_6_1(d, a[44], a[45], a[46], a[47], db + (uint64_t)(32));
  wg_cv_7_1(d, a[48], a[49], a[50], a[51], db + (uint64_t)(48));
  wg_cv_6_1(d, a[40], a[41], a[42], a[43], db + (uint64_t)(48));
  wg_cv_7_1(d, a[44], a[45], a[46], a[47], db + (uint64_t)(64));
  wg_cv_7_1(d, a[40], a[41], a[42], a[43], db + (uint64_t)(80));
  wg_commit();
  wg_cv_7_1(d, a[36], a[37], a[38], a[39], db + (uint64_t)(96));
  wg_cv_6_1(d, a[36], a[37], a[38], a[39], db + (uint64_t)(64));
  wg_cv_5_1(d, a[36], a[37], a[38], a[39], db + (uint64_t)(32));
  wg_cv_4_0(d, a[36], a[37], a[38], a[39], db + (uint64_t)(0));
  wg_cv_7_1(d, a[32], a[33], a[34], a[35], db + (uint64_t)(112));
  wg_cv_6_1(d, a[32], a[33], a[34], a[35], db + (uint64_t)(80));
  wg_cv_5_1(d, a[32], a[33], a[34], a[35], db + (uint64_t)(48));
  wg_cv_4_1(d, a[32], a[33], a[34], a[35], db + (uint64_t)(16));
  wg_cv_7_1(d, a[28], a[29], a[30], a[31], db + (uint64_t)(128));
  wg_cv_6_1(d, a[28], a[29], a[30], a[31], db + (uint64_t)(96));
  wg_cv_5_1(d, a[28], a[29], a[30], a[31], db + (uint64_t)(64));
  wg_cv_4_1(d, a[28], a[29], a[30], a[31], db + (uint64_t)(32));
  wg_cv_3_0(d, a[28], a[29], a[30], a[31], db + (uint64_t)(0));
  wg_cv_7_1(d, a[24], a[25], a[26], a[27], db + (uint64_t)(144));
  wg_cv_6_1(d, a[24], a[25], a[26], a[27], db + (uint64_t)(112));
  wg_cv_5_1(d, a[24], a[25], a[26], a[27], db + (uint64_t)(80));
  wg_cv_4_1(d, a[24], a[25], a[26], a[27], db + (uint64_t)(48));
  wg_cv_3_1(d, a[24], a[25], a[26], a[27], db + (uint64_t)(16));
  wg_commit();
  wg_cv_7_1(d, a[20], a[21], a[22], a[23], db + (uint64_t)(160));
  wg_cv_6_1(d, a[20], a[21], a[22], a[23], db + (uint64_t)(128));
  wg_cv_5_1(d, a[20], a[21], a[22], a[23], db + (uint64_t)(96));
  wg_cv_4_1(d, a[20], a[21], a[22], a[23], db + (uint64_t)(64));
  wg_cv_3_1(d, a[20], a[21], a[22], a[23], db + (uint64_t)(32));
  wg_cv_2_0(d, a[20], a[21], a[22], a[23], db + (uint64_t)(0));
  wg_cv_7_1(d, a[16], a[17], a[18], a[19], db + (uint64_t)(176));
  wg_cv_6_1(d, a[16], a[17], a[18], a[19], db + (uint64_t)(144));
  wg_cv_5_1(d, a[16], a[17], a[18], a[19], db + (uint64_t)(112));
  wg_cv_4_1(d, a[16], a[17], a[18], a[19], db + (uint64_t)(80));
  wg_cv_3_1(d, a[16], a[17], a[18], a[19], db + (uint64_t)(48));
  wg_cv_2_1(d, a[16], a[17], a[18], a[19], db + (uint64_t)(16));
  wg_cv_7_1(d, a[12], a[13], a[14], a[15], db + (uint64_t)(192));
  wg_cv_6_1(d, a[12], a[13], a[14], a[15], db + (uint64_t)(160));
  wg_cv_5_1(d, a[12], a[13], a[14], a[15], db + (uint64_t)(128));
  wg_cv_4_1(d, a[12], a[13], a[14], a[15], db + (uint64_t)(96));
  wg_cv_3_1(d, a[12], a[13], a[14], a[15], db + (uint64_t)(64));
  wg_cv_2_1(d, a[12], a[13], a[14], a[15], db + (uint64_t)(32));
  wg_cv_1_0(d, a[12], a[13], a[14], a[15], db + (uint64_t)(0));
  wg_cv_7_1(d, a[8], a[9], a[10], a[11], db + (uint64_t)(208));
  wg_cv_6_1(d, a[8], a[9], a[10], a[11], db + (uint64_t)(176));
  wg_cv_5_1(d, a[8], a[9], a[10], a[11], db + (uint64_t)(144));
  wg_cv_4_1(d, a[8], a[9], a[10], a[11], db + (uint64_t)(112));
  wg_cv_3_1(d, a[8], a[9], a[10], a[11], db + (uint64_t)(80));
  wg_cv_2_1(d, a[8], a[9], a[10], a[11], db + (uint64_t)(48));
  wg_cv_1_1(d, a[8], a[9], a[10], a[11], db + (uint64_t)(16));
  wg_commit();
  wg_cv_7_1(d, a[4], a[5], a[6], a[7], db + (uint64_t)(224));
  wg_cv_6_1(d, a[4], a[5], a[6], a[7], db + (uint64_t)(192));
  wg_cv_5_1(d, a[4], a[5], a[6], a[7], db + (uint64_t)(160));
  wg_cv_4_1(d, a[4], a[5], a[6], a[7], db + (uint64_t)(128));
  hand();
  wg_cv_3_1(d, a[4], a[5], a[6], a[7], db + (uint64_t)(96));
  wg_cv_2_1(d, a[4], a[5], a[6], a[7], db + (uint64_t)(64));
  wg_cv_1_1(d, a[4], a[5], a[6], a[7], db + (uint64_t)(32));
  wg_cv_0_0(d, a[4], a[5], a[6], a[7], db + (uint64_t)(0));
  wg_cv_7_1(d, a[0], a[1], a[2], a[3], db + (uint64_t)(240));
  wg_cv_6_1(d, a[0], a[1], a[2], a[3], db + (uint64_t)(208));
  wg_cv_5_1(d, a[0], a[1], a[2], a[3], db + (uint64_t)(176));
  wg_cv_4_1(d, a[0], a[1], a[2], a[3], db + (uint64_t)(144));
  wg_cv_3_1(d, a[0], a[1], a[2], a[3], db + (uint64_t)(112));
  wg_cv_2_1(d, a[0], a[1], a[2], a[3], db + (uint64_t)(80));
  wg_cv_1_1(d, a[0], a[1], a[2], a[3], db + (uint64_t)(48));
  wg_cv_0_1(d, a[0], a[1], a[2], a[3], db + (uint64_t)(16));
  wg_commit();
}
constexpr int CV_RELOADED = 2;

struct Params {
  const __nv_bfloat16 *q, *k, *v, *shift_k, *ssm_k, *ssm_D, *w1, *b1, *w2, *b2;
  __nv_bfloat16* out;
};
struct Maps { CUtensorMap qa, w1, w1x, k, v, hs, hx, ha, w2, w2x, kvs, qf, y, out; };

__global__ void __cluster_dims__(2, 1, 1) __launch_bounds__(384, 1) h3_kernel(const __grid_constant__ Maps M, const Params P) {
  extern __shared__ __align__(1024) uint8_t smem_raw[];
  constexpr uint32_t sc = 1024;
  const int tid = threadIdx.x, lane = tid & 31;
  const int warp = __shfl_sync(0xffffffffu, tid >> 5, 0);
  const uint32_t sb = __shfl_sync(0xffffffffu, s32(smem_raw), 0);
  const int b = blockIdx.x, pr = b >> 1;
  const int G = pr < 4 ? 0 : (pr < 36 ? (pr - 4) & 7 : 1 + (pr - 36) % 7), gi = pr < 4 ? 4 + pr : (pr < 36 ? (pr - 4) >> 3 : 4 + (pr - 36) / 7);
  const int kh = b & 1, nt = (G & 1) * 2 + (gi & 1), rb = (G >> 1) * 4 + (gi >> 1);
  const int dir = (G ^ (G >> 1)) & 1, ri = (gi & 1) * 2 + kh, ci = (G >> 2) * 4 + (gi >> 1);
  const uint32_t gmap = (nt & 1) ? 0x03412u : 0x43210u;
  const int j = kh * 4 + nt;
  const uint32_t bar = sb + M_BAR;
  auto BAR = [&](int i) { return bar + 8 * i; };
  auto g1_load = [&](int kc) {
    const uint32_t st = sb + (kc & 3) * G1_STAGE, fb = BAR(B_F1 + (kc & 3));
    const int k0 = dir ? 576 - kc * 64 : kc * 64;
    mbar_expect(fb, G1_TX);
    tma2d(st, &M.qa, k0, rb * 128, fb);
    tma3d(st + 16384, &M.w1, 0, k0, 3 * j, fb);
    tma2d(st + 40960, &M.w1x, 1536 + 24 * j, k0, fb);
  };
  auto kv_load = [&](int r, int hf) {
    const uint32_t st = sb + KVS + (r < 3 ? r : r - 3) * KV_BUF, fb = BAR((hf ? B_KIN1 : B_KIN) + r);
    mbar_expect(fb, KV_BUF / 2);
    tma2d(st + 4096 + hf * 2432, &M.k, 128 * r + 64 * (b & 1), 32 * (b >> 1) + 16 * hf - 3, fb);
    tma2d(st + hf * 2048, &M.v, 128 * r + 64 * (b & 1), 32 * (b >> 1) + 16 * hf, fb);
  };
  auto conv_sum = [&](int c, int ck, bool third, uint32_t ep) {
    const uint32_t ra = sb + cv_p(c) + ck * 16;
    __nv_bfloat16* yp = g_yT + (size_t)(128 * c + b) * SL + ck * 8;
    uint4 p[2][4];
    auto ld = [&](int u) {
#pragma unroll
      for (int w = 0; w < 4; w++) p[u & 1][w] = lds128((u == 0 && ck < 2 * w) ? sb + M_ZERO : ra + u * 512 + w * (4096 - 32));
    };
    auto st = [&](int u) {
      auto sum = [&](uint32_t a0, uint32_t a1, uint32_t a2, uint32_t a3) { return badd2(badd2(badd2(a3, a2), a1), a0); };
      const uint4* r = p[u & 1];
      const uint32_t m = ~ck & 1u;
      stg128(yp + u * 256, (sum(r[0].x, r[1].x, r[2].x, r[3].x) & ~m) | (ep & m), sum(r[0].y, r[1].y, r[2].y, r[3].y), sum(r[0].z, r[1].z, r[2].z, r[3].z), sum(r[0].w, r[1].w, r[2].w, r[3].w));
    };
    ld(0); ld(1); st(0);
    if (third) ld(2);
    st(1);
    if (third) st(2);
  };
  if (warp == 8) {
    if (lane == 0) {
      TS(0);
#pragma unroll
      for (int s = 0; s < 4; s++) mbar_init(BAR(B_F1 + s), 1);
    }
    __syncwarp();
    bar_arrive(NB_INIT, 384);
    ONE(g1_load(0));
  }
  if ((sb & 0xFFFFFFu) != sc) { if (warp == 8) mbar_wait(BAR(B_F1), 0); return; }

  if (warp >= 8) {
    asm volatile("setmaxnreg.dec.sync.aligned.u32 " REG_AUX ";");
    auto table = [&](int c, int aw) {
      const uint32_t kb = sb + cv_t(c);
      const uint32_t dd = lds32(sb + M_AUX + aw * 32 + c * 4);
      if (lane < 2) sts128(kb + lane * (KT_E - 16), 0u, 0u, 0u, 0u);
      uint4 r[8];
#pragma unroll
      for (int it = 0; it < 8; it++) r[it] = lds128(kb + KT_E + (it * 32 + lane) * 16);
      if (lane == 0) { r[0].x = __byte_perm(badd2(r[0].x, dd), r[0].x, 0x7610); sts32(kb + KT_E, r[0].x); }
#pragma unroll
      for (int it = 0; it < 8; it++) {
        const uint32_t pv = __shfl_sync(0xffffffffu, lane == 31 ? (it ? r[it ? it - 1 : 0].w : 0u) : r[it].w, lane - 1);
        sts128(kb + KT_O + (it * 32 + lane) * 16, __byte_perm(pv, r[it].x, 0x5432), __byte_perm(r[it].x, r[it].y, 0x5432),
               __byte_perm(r[it].y, r[it].z, 0x5432), __byte_perm(r[it].z, r[it].w, 0x5432));
      }
      __syncwarp();
      if (lane == 0) mbar_arrive(BAR(B_KT + c));
    };
    if (warp == 8) {
      ONE(g1_load(1); g1_load(2); g1_load(3));
      bar_sync(NB_INIT2, 128);
#pragma unroll
      for (int kc = 3; kc < 10; kc++) {
        if (kc > 3) mbar_wait(BAR(B_E1 + (kc & 3)), (kc >> 3) & 1);
        ONE(if (kc > 3) g1_load(kc);
            for (int r = 0; r < 3; r++) if (kc == ((KV_MAP >> (4 * r)) & 15)) { kv_load(r, 0); kv_load(r, 1); }
            for (int c = 0; c < 5; c++) if (kc == ((PF_RAW >> (4 * c)) & 15)) prefetch_l2(P.ssm_k + (size_t)(128 * c + b) * SL, 4096));
      }
      ONE(prefetch_map(&M.hs); prefetch_map(&M.hx); prefetch_map(&M.ha); prefetch_map(&M.w2); prefetch_map(&M.w2x));
      bar_sync(NB_INIT3, 64);
      const unsigned ep = lds32(sb + M_AUX + 20);
      const int hc = j * 192, hx = 1536 + j * 24;
#pragma unroll 1
      for (int n = 0; n < 32; n += 4) {
        const int i = (H_ORD >> n) & 7, hw = i >> 2, blk = i & 3;
        if (n == 4 * W2_PF) ONE(prefetch_l2(P.w2 + (size_t)b * (FF * DM / NCTA), FF * DM / NCTA * 2));
        mbar_wait(BAR(B_HB + i), 0);
        fence_async_smem();
        asm volatile("cp.async.bulk.wait_group %0;" ::"n"(H_FLY - 1) : "memory");
        ONE(tma2d_st(blk < 3 ? &M.hs : &M.hx, blk < 3 ? hc + blk * 64 : hx, rb * 128 + hw * 64, sb + hw * HST + blk * 8192); bulk_commit());
      }
      const int cf = (nt * 160 + (nt & 1) * 32) >> 6, ch = (nt >> 1) * 320 + 128;
      auto g2_k = [&](int kc) { return kc == 0 ? 1536 + kh * 128 : (kc == 13 ? 1600 : kh * 768 + (kc - 1) * 64); };
      auto g2_load_b = [&](int kc) {
        const int s = kc & 3;
        const uint32_t fb = BAR(B_F2 + s);
        mbar_expect(fb, kc == 13 ? 8192 + 24576 : 16384 + 24576);
        tma3d(sb + g2_b(s), &M.w2, 0, g2_k(kc), cf, fb);
        tma2d(sb + g2_b(s) + 16384, &M.w2x, ch, g2_k(kc), fb);
      };
      auto g2_load_a = [&](int kc) {
        const int s = kc & 3, o = kc == 13 ? kh : 0;
        tma2d(sb + g2_a(s) + o * 8192, kc == 13 ? &M.hs : &M.ha, g2_k(kc), rb * 128 + o * 64, BAR(B_F2 + s));
      };
      bulk_wait_all();
      ONE(g2_load_b(0); g2_load_b(1));
      fence_release();
      ONE(signal_cnt(CNT_H + rb); TS(37));
      wait_cnt(CNT_H + rb, 8 * ep);
      ONE(TS(39); g2_load_a(0); g2_load_a(1); prefetch_map(&M.qf); prefetch_map(&M.y); prefetch_map(&M.out));
      mbar_wait(BAR(B_KD), 0);
      ONE(g2_load_b(3));
      mbar_wait(BAR(B_TD + 1), 0);
      ONE(g2_load_b(2); g2_load_a(2));
      mbar_wait(BAR(B_SD + 3), 0);
      ONE(mbar_expect(BAR(B_FINQ), 20480);
          for (int i = 0; i < 5; i++) tma2d(sb + FIN_Q + i * 4096, &M.qf, nt * 160 + ((gmap >> (4 * i)) & 7) * 32, rb * 128 + kh * 64, BAR(B_FINQ)));
      mbar_wait(BAR(B_RF + 2), 0);
      ONE(g2_load_a(3); TS(38));
#pragma unroll 1
      for (int kc = 4; kc < 14; kc++) {
        mbar_wait(BAR(B_E2 + (kc & 3)), ((kc >> 2) - 1) & 1);
                ONE(g2_load_a(kc); g2_load_b(kc); if (kc >= Y_KC && kc < Y_KC + 3) mbar_arrive(BAR(B_YSLOT + kc - Y_KC)));
      }
      if (lane == 0) g_launch[b * 8] = ep;
#pragma unroll 1
      for (int i = 0; i < 5; i++) {
        const int gi = (gmap >> (4 * i)) & 7;
        mbar_wait(BAR(B_OUT + i), 0);
        fence_async_smem();
        ONE(tma2d_st(&M.out, nt * 160 + gi * 32, rb * 128 + kh * 64, sb + FIN_Q + i * 4096));
      }
      ONE(bulk_commit());
      bulk_wait_read();
    } else {
      const int aw = warp - 9, at = tid - 288;
      if (aw == 0) {
        if (lane == 0) {
#pragma unroll
          for (int s = 0; s < 4; s++) { mbar_init(BAR(B_E1 + s), 8); mbar_init(BAR(B_FR + s), 8); mbar_init(BAR(B_F2 + s), 1); mbar_init(BAR(B_E2 + s), 8); }
          mbar_init(BAR(B_KRAW), 1); mbar_init(BAR(B_KRAW + 1), 1);
          mbar_init(BAR(B_RED), 8); mbar_init(BAR(B_BX), 1);
        }
      } else if (aw == 1) {
        if (lane == 0) {
#pragma unroll
          for (int c = 0; c < 5; c++) { if (c == 0) { mbar_init(BAR(B_SK), 1); mbar_init(BAR(B_KD), 2); } mbar_init(BAR(B_XL + c), 1); mbar_init(BAR(B_KT + c), 1); mbar_init(BAR(B_XF + c), 1); mbar_init(BAR(B_SD + c), 4); }
        }
      } else if (lane == 0) {
#pragma unroll
        for (int i = 0; i < 8; i++) mbar_init(BAR(B_HB + i), 4);
#pragma unroll
        for (int c = 0; c < 3; c++) mbar_init(BAR(B_RF + c), 3);
        for (int r = 0; r < 5; r++) { mbar_init(BAR(B_KIN + r), 1); mbar_init(BAR(B_KIN1 + r), 1); }
        for (int i = 0; i < 3; i++) { mbar_init(BAR(B_YSLOT + i), 1); mbar_init(BAR(B_YL + i), 1); } mbar_init(BAR(B_XR), 1);
        for (int i = 0; i < 5; i++) mbar_init(BAR(B_OUT + i), 4);
        mbar_init(BAR(B_XD), 1); mbar_expect(BAR(B_XD), 8192); mbar_init(BAR(B_XD + 1), 1); mbar_expect(BAR(B_XD + 1), 12288);
        asm volatile("fence.mbarrier_init.release.cluster;" ::: "memory");
        mbar_init(BAR(B_TD + 1), 8); mbar_init(BAR(B_FINQ), 1); mbar_init(BAR(B_FINY), 3);
      }
      __syncwarp();
      bar_arrive(NB_INIT, 384);
      if (aw == 1) ONE(prefetch_map(&M.k); prefetch_map(&M.v); mbar_expect(BAR(B_SK), 2560);
                       for (int r = 0; r < 5; r++) bulk_g2s(sb + M_SK + r * 512, P.shift_k + (128 * r + 64 * (b & 1)) * 4, 512, BAR(B_SK)));
      const uint32_t dv0 = ld_relaxed32(lane < 5 ? static_cast<const void*>(P.ssm_D + 128 * lane + (b & ~1)) : &g_launch[b * 8]);
      const uint32_t b2v = ldg32(reinterpret_cast<const uint32_t*>(P.b2 + nt * 160) + ((gmap >> (4 * (min(at, 79) >> 4))) & 7) * 16 + (at & 15));
      const int l27 = min(lane, 26), col = l27 < 24 ? 192 * j + 8 * l27 : 1536 + 24 * j + 8 * (l27 - 24);
      uint4 bb;
      if (aw == 2) bb = ldg128(P.b1 + col);
      bar_sync(NB_INIT2, 128);
      if (aw == 0) ONE(prefetch_map(&M.kvs));
      if (lane < 4) sts32(sb + M_ZERO + lane * 4, 0u);
      if (lane < 8) sts32(sb + M_AUX + aw * 32 + lane * 4, lane >= 5 ? dv0 + 1 : ((b & 1) ? dv0 >> 16 : dv0 & 0xFFFFu));
      if (at < 80) sts64f(sb + M_B2 + at * 8, 0.5f * bf_lo(b2v), 0.5f * bf_hi(b2v));
      __syncwarp();
      if (aw == 0) bar_arrive(NB_INIT3, 64);
      if (aw == 2) {
        const unsigned ep = lds32(sb + M_AUX + 64 + 20);
        const uint32_t ba = sb + M_BX + (l27 >> 2) * 512 + ((l27 & 3) << 4);
        mbar_wait(BAR(B_RED), 0);
        const uint32_t tg = ep & 15u;
        auto tagged = [&](float v) { return (__float_as_uint(v) & ~15u) | tg; };
        float c0 = 0.f, c1 = 0.f, s1 = 0.f, s2 = 0.f;
#pragma unroll
        for (int i = 0; i < 16; i += 2) { c0 += __uint_as_float(lds32(sb + M_RED1 + i * 128 + lane * 4)); c1 += __uint_as_float(lds32(sb + M_RED1 + i * 128 + 128 + lane * 4)); }
        st_relaxed32(&g_cs[(dir * 8 + j) * 256 + ci * 32 + lane], tagged(c0 + c1));
        float2 u[8];
#pragma unroll
        for (int i = 0; i < 8; i++) u[i] = lds64f(sb + M_RED0 + (lane & 15) * 128 + ((i + lane) & 7) * 16 + (lane >> 4) * 8);
        const float c = bf_round(u[0].x * (1.f / 40)), cc = 40.f * c * c;
#pragma unroll
        for (int i = 0; i < 8; i++) { s1 += fmaf(-40.f, c, u[i].x); s2 += fmaf(-2.f * c, u[i].x, u[i].y) + cc; }
        const float dm = s1 * (1.f / 320);
        st_relaxed64(&g_stat[dir * SL + rb * 128 + ri * 32 + lane], tagged(c + dm), tagged(fmaf(-dm, s1, s2)));
        __syncwarp();
        if (lane == 0) TS(30);
        sts128((ba + 128) ^ 16, 0u, 0u, 0u, 0u); sts128((ba + 192) ^ 16, bb.x, bb.y, bb.z, bb.w);
#pragma unroll
        for (int i = 4; i < 8; i++) sts128((ba + i * 64) ^ ((i >> 1) << 4), 0u, 0u, 0u, 0u);
        mbar_wait(BAR(B_FR), 0);
        auto raw_load = [&]() {
          ONE(mbar_expect(BAR(B_KRAW), 4096); mbar_expect(BAR(B_KRAW + 1), 4 * 4096);
              for (int c = 0; c < 5; c++) bulk_g2s(sb + cv_t(c) + KT_E, P.ssm_k + (size_t)(128 * c + b) * SL, 4096, BAR(B_KRAW + (c >= 1))));
        };
        uint32_t x[32], n = 0;
#pragma unroll 1
        while (true) {
#pragma unroll
          for (int i = 0; i < 8; i++) {
            const uint4 v = ld_relaxed128(i < 4 ? static_cast<const void*>(g_cs + ((i >> 1) * 8 + j) * 256 + l27 * 8 + (i & 1) * 4)
                                                : g_stat + ((i >> 1) & 1) * SL + rb * 128 + lane * 4 + (i & 1) * 2);
            x[4 * i] = v.x; x[4 * i + 1] = v.y; x[4 * i + 2] = v.z; x[4 * i + 3] = v.w;
          }
          if (!RAW_LATE && n == 0) raw_load();
          uint32_t bad = 0;
#pragma unroll
          for (int i = 0; i < 32; i++) { x[i] ^= tg; bad |= x[i]; }
          if (__all_sync(0xffffffffu, (bad & 15u) == 0) || spin_guard(n, 0x131)) break;
        }
        if (RAW_LATE) raw_load();
        uint32_t st[4];
#pragma unroll
        for (int i = 0; i < 4; i++) {
          const float ma = __uint_as_float(x[16 + 2 * i]), mb = __uint_as_float(x[24 + 2 * i]), dl = ma - mb;
          const float m2 = fmaf(dl * dl, 160.f, __uint_as_float(x[17 + 2 * i]) + __uint_as_float(x[25 + 2 * i]));
          const float vb = bf_round(fmaxf(m2, 0.f) * (1.f / DM));
          st[i] = pack_bf16(0.5f * (ma + mb), sqrt_fast(bf_round(vb + 1e-5f)));
        }
        sts128(sb + M_STAT + lane * 16, st[0], st[1], st[2], st[3]);
        uint32_t hi[4], lo[4];
#pragma unroll
        for (int i = 0; i < 4; i++) {
          const float x0 = __uint_as_float(x[2 * i]) + __uint_as_float(x[8 + 2 * i]), x1 = __uint_as_float(x[2 * i + 1]) + __uint_as_float(x[9 + 2 * i]);
          hi[i] = pack_bf16(x0, x1); lo[i] = pack_bf16(x0 - bf_lo(hi[i]), x1 - bf_hi(hi[i]));
        }
        sts128(ba, hi[0], hi[1], hi[2], hi[3]); sts128(ba + 64, lo[0], lo[1], lo[2], lo[3]);
        fence_async_smem();
        __syncwarp();
        ONE(mbar_arrive(BAR(B_BX)); TS(54));
      }
      if (aw < 2) {
        auto done = [&](int r) {
          bulk_wait_read();
          ONE(kv_load(r + 3, aw); TSKV);
        };
        const uint32_t par = lds32(sb + M_AUX + aw * 32 + 20) & 1u;
        bool pend = false;
        mbar_wait(BAR(B_SK), 0);
#pragma unroll 1
        for (int r = 0; r < 5; r++) {
          const int c0 = 128 * r + 64 * (b & 1);
          const uint32_t buf = sb + KVS + (r < 3 ? r : r - 3) * KV_BUF, stg = buf + aw * 2048, vb = stg + lane * 4, kb = buf + 4096 + aw * 2432 + lane * 4;
          const uint4 sk = lds128(sb + M_SK + r * 512 + lane * 16);
          const uint32_t w0 = __byte_perm(sk.x, sk.z, 0x5410), w1 = __byte_perm(sk.x, sk.z, 0x7632);
          const uint32_t w2 = __byte_perm(sk.y, sk.w, 0x5410), w3 = __byte_perm(sk.y, sk.w, 0x7632);
          mbar_wait(BAR((aw ? B_KIN1 : B_KIN) + r), 0);
          if (at == 0 && r == 0) TS(56);
          uint32_t kk[19], o[16];
#pragma unroll
          for (int i = 0; i < 19; i++) { kk[i] = lds32(kb + i * 128); if (i >= 3) o[i - 3] = lds32(vb + (i - 3) * 128); }
#pragma unroll
          for (int i = 0; i < 16; i++) o[i] = bmul2(bfma2(kk[i + 3], w0, bfma2(kk[i + 2], w1, bfma2(kk[i + 1], w2, bmul2(kk[i], w3)))), o[i]);
          __syncwarp();
          const uint32_t a0 = stg + lane * 64 + ((lane & 6) << 3);
          const uint32_t s0 = (lane & 4) ? 0x7632 : 0x5410, s1 = s0 ^ 0x2222;
#pragma unroll
          for (int hh = 0; hh < 2; hh++) {
            const uint32_t* u = o + 8 * hh;
            const uint32_t a = a0 ^ (hh << 4);
            auto nz = [&](uint32_t x) { return hh ? x : (x & ~1u) | par; };
            sts128(a, nz(__byte_perm(u[1], u[0], s0)), __byte_perm(u[3], u[2], s0), __byte_perm(u[5], u[4], s0), __byte_perm(u[7], u[6], s0));
            sts128(a ^ 32, nz(__byte_perm(u[1], u[0], s1)), __byte_perm(u[3], u[2], s1), __byte_perm(u[5], u[4], s1), __byte_perm(u[7], u[6], s1));
          }
          if (pend) done(r - 1);
          fence_async_smem();
          __syncwarp();
          ONE(tma2d_st(&M.kvs, 32 * (b >> 1) + 16 * aw, c0, stg); bulk_commit());
          pend = r < 2 && mbar_test(BAR((aw ? B_KIN1 : B_KIN) + r + 1), 0);
          if (!pend && r < 2) done(r);
        }
      }
      const unsigned ep = lds32(sb + M_AUX + aw * 32 + 20);
      auto x_load = [&](int c) { mbar_expect(BAR(B_XL + c), 4096); bulk_g2s(sb + cv_x(c) + XD, g_kvT + (size_t)(128 * c + b) * SL, 4096, BAR(B_XL + c)); };
      auto x_pad = [&](int c0, int c1) {
        if (lane < 17) for (int c = c0; c < c1; c++) sts128(sb + cv_x(c) + lane * 16, 0u, 0u, 0u, 0u);
        fence_async_smem();
        __syncwarp();
      };
      if (aw == 2) {
        mbar_wait(BAR(B_FR + 1), 0);
        ONE(for (int c = 0; c < X_A; c++) x_load(c));
        x_pad(0, 4);
      }
#pragma unroll 1
      for (int c = 2 - aw; c < 5; c += 2) {
        mbar_wait(BAR(B_KRAW + (c > 0)), 0);
        if (lane == 0 && c == 2) TS(35);
        table(c, aw);
        if (lane == 0 && c == 2) TS(55);
        if (c == 0) break;
        if (c < 3) { bulk_wait_read(); ONE(mbar_arrive(BAR(B_KD)); if (aw == 0) TS(34)); }
      }
      if (aw == 2) {
#pragma unroll 1
        for (int c = 0, n = 0; c < 5;) {
          mbar_wait(BAR(B_XL + c), n & 1);
          const uint32_t a = sb + cv_x(c) + XD + lane * 32;
          const uint32_t v = ((lds32(a) ^ ep) | (lds32(a + 1024) ^ ep) | (lds32(a + 2048) ^ ep) | (lds32(a + 3072) ^ ep)) & 1u;
          int nx = c;
          if (__all_sync(0xffffffffu, v == 0) || n > 100000) {
            ONE(mbar_arrive(BAR(B_XF + c)); if (c == 0) TS(36); if (c >= 3) TS(28 + c));
            nx = c + X_A; c++; n = 0;
            if (nx == 4) { mbar_wait(BAR(B_KD), 0); x_pad(4, 5); }
          } else {
            n++;
            if (lane == 0) TS(33);
          }
          if (nx < 5) ONE(x_load(nx));
        }
      }
      if (RED_GATE) mbar_wait(BAR(RED_GATE == 1 ? B_TD + 1 : B_SD + RED_GATE - 1), 0);
#pragma unroll 1
      for (int c = 0; c < 5; c++) {
        mbar_wait(BAR(B_SD + c), 0);
        conv_sum(c, aw * 96 + lane, aw < 2, ep);
        __syncwarp();
        if (c < 3 && lane == 0) mbar_arrive(BAR(B_RF + c));
        if (at == 0) TS(59 + c);
      }
      bar_sync(NB_AUX, 96);
      if (aw == 0) ONE(mbar_arrive_remote(mapa(BAR(B_XR), kh ^ 1)); TS(3));
      auto ytab = [](int a) { return (uint32_t)(fin_y(3 * a) >> 10 | fin_y(3 * a + 1) >> 10 << 8 | fin_y(3 * a + 2) >> 10 << 16 | fin_y(a == 2 ? 9 : 3 * a) >> 10 << 24); };
      const uint32_t yt = aw == 0 ? ytab(0) : (aw == 1 ? ytab(1) : ytab(2));
      mbar_wait(BAR(B_YSLOT + aw), 0);
#pragma unroll 1
      for (int n = 0;; n++) {
        ONE(mbar_expect(BAR(B_YL + aw), aw == 2 ? 8192 : 6144));
#pragma unroll 1
        for (int i = 0; i < (aw == 2 ? 4 : 3); i++) {
          const int np = 3 * aw + i;
          ONE(tma2d(sb + (((yt >> (8 * i)) & 255) << 10), &M.y, rb * 128 + kh * 64, nt * 160 + ((gmap >> (4 * (np >> 1))) & 7) * 32 + (np & 1) * 16, BAR(B_YL + aw)));
        }
        mbar_wait(BAR(B_YL + aw), n & 1);
        uint32_t bad = 0;
#pragma unroll
        for (int i = 0; i < 4; i++) {
          const uint32_t a = sb + (((yt >> (8 * i)) & 255) << 10) + (lane >> 2) * 128 + ((((lane & 3) * 2) ^ (lane >> 2)) << 4);
          bad |= (lds32(a) ^ ep) | (lds32(a + 1024) ^ ep);
        }
        if (__all_sync(0xffffffffu, (bad & 1u) == 0) || n > 100000) break;
        if (lane == 0) TS(33);
      }
      ONE(mbar_arrive(BAR(B_FINY)); if (aw == 2) TS(40));
    }
  } else {
    asm volatile("setmaxnreg.inc.sync.aligned.u32 " REG_CON ";");
    const int wg = warp >> 2, w = warp & 3, g = lane >> 2, q = lane & 3;
    constexpr bool elect = false;
    uint32_t ca[64];
    const uint32_t ab0 = sb + ((g & 1) ? KT_E : KT_O) + (8 * w + 4 + (g >> 1) - q) * 4;
    auto conv_lda = [&](int c, int k0, int k1) {
      const uint32_t ab = ab0 + cv_t(c);
#pragma unroll
      for (int ks = 15; ks >= 0; ks--) {
        if (ks >= k0 && ks < k1) {
          ca[4 * ks + 0] = lds32(ab + ks * 256);
          ca[4 * ks + 1] = lds32(ab + ks * 256 + 128);
          ca[4 * ks + 2] = lds32(ab + ks * 256 - 16);
          ca[4 * ks + 3] = lds32(ab + ks * 256 + 112);
        }
      }
    };
    {
      float d[108];
      auto g1_release = [&](int kc) { if (lane == 0) mbar_arrive(BAR(kc < 6 ? B_E1 + (kc & 3) : B_FR + kc - 6)); };
      auto g1_wait = [&](int kc) { mbar_wait(BAR(B_F1 + (kc & 3)), (kc >> 2) & 1); };
      auto g1_issue = [&](int kc) {
        const int s = kc & 3;
        if (kc == 0) { mbar_wait(BAR(B_F1), 0); if (wg == 1) bar_sync(NB_LEAD, 256); }
        if (tid == 0) TS(8 + kc);
        const uint32_t st = sc + s * G1_STAGE;
        const uint64_t da = mkdesc(st + wg * 8192, 16, 1024, 1), db = mkdesc(st + 16384, 8192, 1024, 1);
        wg_fence();
#pragma unroll
        for (int k = 0; k < 4; k++) {
          wg_ss_216(d, da + k * 2, db + k * 128, (kc | k) != 0);
          if (k == REL_K || k == 3) wg_commit();
          if (k == REL_K && kc > 0) { wg_wait<1>(); g1_release(kc - 1); }
        }
        if (kc == 0 && wg == 0) bar_arrive(NB_LEAD, 256);
      };
      const int t7 = tid & 127, wr = ((t7 >> 3) & 1) * 4 + (t7 >> 4) * 8, wc = 4 * min(ci, 6) + ((t7 >> 1) & 3);
      const uint32_t sa0 = sb + (wg ? 16384 + (wc >> 3) * 8192 + wr * 128 + (((wc ^ wr) & 7) << 4) + (t7 & 1) * 8 : ri * 4096 + t7 * 16);
      float t1 = 0.f, t2 = 0.f, t3 = 0.f, t4 = 0.f;
      auto piece = [&](int i) {
        if (wg == 0) {
          const uint4 x = lds128(sa0 + (i & 3) * G1_STAGE), y = lds128(sa0 + (i & 3) * G1_STAGE + 2048);
          const uint32_t xx[4] = {x.x, x.y, x.z, x.w}, yy[4] = {y.x, y.y, y.z, y.w};
#pragma unroll
          for (int e = 0; e < 4; e++) {
            const float u = bf_lo(xx[e]), v = bf_hi(xx[e]), r = bf_lo(yy[e]), z = bf_hi(yy[e]);
            t1 += u; t2 = fmaf(u, u, t2); t3 += r; t4 = fmaf(r, r, t4);
            t1 += v; t2 = fmaf(v, v, t2); t3 += z; t4 = fmaf(z, z, t4);
          }
        } else {
          float2 xx[4];
#pragma unroll
          for (int e = 0; e < 4; e++) xx[e] = lds64f((sa0 ^ (e * 144)) + (i & 3) * G1_STAGE);
#pragma unroll
          for (int e = 0; e < 4; e++) {
            const uint32_t u = __float_as_uint(xx[e].x), v = __float_as_uint(xx[e].y);
            t1 += bf_lo(u); t2 += bf_hi(u); t3 += bf_lo(v); t4 += bf_hi(v);
          }
        }
      };
      bar_sync(NB_INIT, 384);
#pragma unroll
      for (int kc = 0; kc < 10; kc++) {
        g1_issue(kc);
        if (kc < 5) { g1_wait(kc); piece(kc); }
        if (kc == 4) {
          sts128(sb + (wg ? M_RED1 : M_RED0) + t7 * 16, __float_as_uint(t1), __float_as_uint(t2), __float_as_uint(t3), __float_as_uint(t4));
          __syncwarp();
          if (lane == 0) mbar_arrive(BAR(B_RED));
        }
        if (kc < 9) g1_wait(kc + 1);
      }
      uint2 s0, s1;
      {
        mbar_wait(BAR(B_BX), 0);
        s0.x = lds32(sb + M_STAT + (wg * 64 + w * 16 + g) * 4); s1.x = lds32(sb + M_STAT + (wg * 64 + w * 16 + g + 8) * 4);
        if (tid == 0) TS(46);
        const uint32_t f0 = q == 0 ? ((s0.x & 0xFFFFu) * 0x10001u) ^ 0x80008000u : (q == 1 ? s0.x ^ 0x8000u : 0u);
        const uint32_t f1 = q == 0 ? ((s1.x & 0xFFFFu) * 0x10001u) ^ 0x80008000u : (q == 1 ? s1.x ^ 0x8000u : 0u);
        wg_fence();
        wg_rs_216(d, f0, f1, 0u, 0u, mkdesc(sc + M_BX, 512, 0, 2));
        wg_commit();
      }
      wg_wait<1>();
      if (lane == 0) mbar_arrive(BAR(B_FR + 3));
      const float r0 = rcp_fast(bf_hi(s0.x)), r1 = rcp_fast(bf_hi(s1.x));
      constexpr float C1 = 0.7978845608028654f, C2 = 0.7978845608028654f * 0.044715f;
      const float ga0 = C1 * r0, gb0 = C2 * r0 * r0 * r0, ga1 = C1 * r1, gb1 = C2 * r1 * r1 * r1;
      if (wg == 0) mbar_wait(BAR(B_FR + 2), 0);
      wg_wait<0>();
      if (elect) TS(1 + 47 * wg);
      if (wg == 1) bar_sync(NB_GELU, 256);
      sched_fence(sb);
      const int mi = lane >> 3, row = w * 16 + (mi & 1) * 8 + (lane & 7);
      const uint32_t hs = sb + wg * HST;
      float u[2][8];
#pragma unroll
      for (int st = -1; st < 15; st++) {
        const int nb = 2 * (st - 1);
        if (st >= 1) {
          uint32_t p[4];
#pragma unroll
          for (int e = 0; e < (nb < 26 ? 4 : 2); e++) {
            const float x = d[4 * nb + 2 * e], y = d[4 * nb + 2 * e + 1];
            p[e] = pack_bf16(fmaf(x, u[(st - 1) & 1][2 * e], x), fmaf(y, u[(st - 1) & 1][2 * e + 1], y));
          }
          const int nbm = nb + (mi >> 1);
          if (nb < 24) stsm4(hs + (nb >> 3) * 8192 + row * 128 + (((nbm & 7) ^ (row & 7)) << 4), p[0], p[1], p[2], p[3]);
          else if (nb == 24) stsm4(hs + 24576 + row * 48 + (mi >> 1) * 16, p[0], p[1], p[2], p[3]);
          else stsm2(hs + 24576 + row * 48 + 32, p[0], p[1]);
          if ((nb & 7) == 6 || nb == 26) {
            __syncwarp();
            if (lane == 0) mbar_arrive(BAR(B_HB + wg * 4 + (nb >> 3)));
          }
        }
        if (st >= 0 && st < 14) {
#pragma unroll
          for (int i = 0; i < (st < 13 ? 8 : 4); i++) u[st & 1][i] = tanh_fast(u[st & 1][i]);
        }
        if (st + 1 < 14) {
#pragma unroll
          for (int i = 0; i < (st + 1 < 13 ? 8 : 4); i++) {
            const float x = d[8 * (st + 1) + i];
            u[(st + 1) & 1][i] = x * fmaf(x * ((i & 2) ? gb1 : gb0), x, (i & 2) ? ga1 : ga0);
          }
        }
        constexpr int S0 = A_NB0 / 2;
        if (st >= S0 && st < 14) conv_lda(wg, 16 - (st + 1 - S0) * 16 / (S0 < 14 ? 14 - S0 : 1), 16 - (st - S0) * 16 / (S0 < 14 ? 14 - S0 : 1));
        if (2 * st == GELU_NB && wg == 0) bar_arrive(NB_GELU, 256);
        if (st + 1 == S0) mbar_wait(BAR(B_KT + wg), 0); else if (st < 14 && (st + 1) % SCH == 0) sched_fence(sb);
      }
      if (A_NB0 >= 28) { mbar_wait(BAR(B_KT + wg), 0); conv_lda(wg, 0, 16); }
      if (elect) TS(2 + 47 * wg);
    }
#pragma unroll 1
    for (int c = wg; c < 5; c += 2) {
      float d[128];
      mbar_wait(BAR(B_XF + c), 0);
      if (c < 3) mbar_wait(BAR(B_KT + c + 2), 0);
      const uint64_t db = mkdesc(sc + cv_x(c), 16, 128, 0);
      if (c > 0) { if (wg) bar_sync(NB_TURN + 1, 256); else bar_sync(NB_TURN, 256); }
      wg_fence();
      auto hand = [&]() { if (wg) bar_arrive(NB_TURN, 256); else bar_arrive(NB_TURN + 1, 256); };
      if (c < 3) conv_chain_1(d, ca, db, ab0 + cv_t(c + 2), hand); else conv_chain_0(d, ca, db, 0, hand);
      mbar_wait(BAR(c >= 3 ? B_RF + c - 3 : B_FR + 3), 0);
      wg_wait<0>();
      if (elect) TS(41 + c);
      const uint32_t wa = sb + cv_p(c) + w * 4096 + lane * 16;
#pragma unroll
      for (int n4 = 0; n4 < 32; n4 += 4) {
        uint32_t p[4];
#pragma unroll
        for (int e = 0; e < 4; e++) {
          const int nb = n4 + e;
          float x = d[4 * nb], y = d[4 * nb + 1];
          if (nb > 0) { x += d[4 * nb - 2]; y += d[4 * nb - 1]; }
          p[e] = pack_bf16(x, y);
        }
        stsm4t(wa + n4 * 128, p[0], p[1], p[2], p[3]);
      }
      __syncwarp();
      if (lane == 0) mbar_arrive(BAR(B_SD + c));
      if (c < 3) {
        conv_lda(c + 2, 0, CV_RELOADED);
        if (c > 0) {
          fence_async_smem();
          __syncwarp();
          if (lane == 0) mbar_arrive(BAR(B_TD + 1));
        }
      }
    }
    if (elect) TS(51 + wg);
    {
      float d[80];
      const uint32_t aoff = (wg ^ kh) * 8192;
      const uint64_t boff = (uint64_t)(nt & 1) << 51;
      const uint32_t s0 = lds32(sb + M_STAT + ((wg ^ kh) * 64 + w * 16 + g) * 4), s1 = lds32(sb + M_STAT + ((wg ^ kh) * 64 + w * 16 + g + 8) * 4);
      auto g2_release = [&](int kc) { if (lane == 0) mbar_arrive(BAR(B_E2 + (kc & 3))); };
      auto g2_mma = [&](int kc, int first, bool rel) {
        const int s = kc & 3;
        mbar_wait(BAR(B_F2 + s), (kc >> 2) & 1);
        const uint64_t da = mkdesc(sc + g2_a(s) + aoff, 16, 1024, 1), db = mkdesc(sc + g2_b(s), 8192, 1024, 1) | boff;
        wg_fence();
#pragma unroll
        for (int k = 0; k < 4; k++) {
          wg_ss_160(d, da + k * 2, db + k * 128, k ? 1 : first);
          if ((k == REL_K && rel) || k == 3) wg_commit();
          if (k == REL_K && rel) { wg_wait<1>(); g2_release(kc - 1); }
        }
      };
      if (wg == 1) bar_sync(NB_TURN + 1, 256);
      g2_mma(0, 0, false);
      if (wg == 1) bar_sync(NB_LEAD, 256); else bar_arrive(NB_LEAD, 256);
#pragma unroll
      for (int kc = 1; kc < XP_KC; kc++) {
        if (tid == 0) TS(17 + kc);
        g2_mma(kc, 1, true);
      }
      if (wg == 1) {
        float bi[40];
#pragma unroll
        for (int nb = 0; nb < 20; nb++) { const float2 v = lds64f(sb + M_B2 + nb * 32 + q * 8); bi[2 * nb] = v.x; bi[2 * nb + 1] = v.y; }
        const float c0 = 0.25f * rcp_fast(bf_hi(s0)), c1 = 0.25f * rcp_fast(bf_hi(s1));
#pragma unroll
        for (int kc = XP_KC; kc < 13; kc++) {
          g2_mma(kc, 1, kc < 11);
          if (kc == END_KC) bar_arrive(NB_END, 256);
        }
        mbar_wait(BAR(B_XR), 0);
        wg_wait<0>();
        if (elect) TS(53);
        const uint32_t ra = mapa(sb, kh ^ 1), rbar = ra + M_BAR + 8 * B_XD, dst = ra + (tid & 127) * 16;
#pragma unroll
        for (int i = 0; i < 10; i++) {
          const float *dd = d + 8 * i, *bb = bi + 4 * i;
          st_async128(dst + (i < 5 ? P0 + i * 2048 : P1 + (i - 5) * 2048), pack_bf16(fmaf(dd[0], c0, bb[0]), fmaf(dd[1], c0, bb[1])), pack_bf16(fmaf(dd[2], c1, bb[0]), fmaf(dd[3], c1, bb[1])),
                      pack_bf16(fmaf(dd[4], c0, bb[2]), fmaf(dd[5], c0, bb[3])), pack_bf16(fmaf(dd[6], c1, bb[2]), fmaf(dd[7], c1, bb[3])), rbar + 8 * (i >= 4));
        }
        if (elect) TS(7);
      } else {
        const int mi = lane >> 3, row = (mi & 1) * 8 + (lane & 7);
        const uint32_t qa = sb + FIN_Q + (w * 16 + row) * 64 + (((mi >> 1) ^ ((row >> 1) & 3)) << 4), qb = qa ^ 32;
        auto q_addr = [&](int np) { return ((np & 1) ? qb : qa) + (np >> 1) * 4096; };
        uint32_t sv[40];
        const uint32_t m0 = (s0 & 0xFFFFu) * 0x10001u, m1 = (s1 & 0xFFFFu) * 0x10001u;
        float rs0 = rcp_fast(bf_hi(s0)), rs1 = rcp_fast(bf_hi(s1));
#pragma unroll
        for (int kc = XP_KC; kc < 10; kc++) {
          if (tid == 0) TS(17 + kc);
          g2_mma(kc, 1, true);
          if (kc >= XP_KC && XP_KC < 10) {
            mbar_wait(BAR(B_FINQ), 0);
#pragma unroll
            for (int np = 10 * (kc - XP_KC) / (XP_KC < 10 ? 10 - XP_KC : 1); np < 10 * (kc + 1 - XP_KC) / (XP_KC < 10 ? 10 - XP_KC : 1); np++) {
              uint32_t xq[4];
              ldsm4(q_addr(np), xq[0], xq[1], xq[2], xq[3]);
#pragma unroll
              for (int e = 0; e < 4; e++) {
                const uint32_t dm = bsub2(xq[e], (e & 1) ? m1 : m0);
                const float rs = (e & 1) ? rs1 : rs0;
                sv[4 * np + e] = pack_bf16(bf_lo(dm) * rs, bf_hi(dm) * rs);
              }
            }
          }
        }
        const uint32_t ya = sb + (mi >> 1) * 1024 + (lane & 7) * 128 + (((2 * w + (mi & 1)) ^ (lane & 7)) << 4);
        auto y_prep = [&](int n0, int n1) {
          if (n1 > n0) mbar_wait(BAR(B_FINY), 0);
#pragma unroll
          for (int np = n0; np < n1; np++) {
            uint32_t y[4];
            ldsm4t(ya + fin_y(np), y[0], y[1], y[2], y[3]);
#pragma unroll
            for (int e = 0; e < 4; e++) sv[4 * np + e] = bmul2(sv[4 * np + e], y[e]);
          }
        };
        rs0 *= 0.25f; rs1 *= 0.25f;
        if (tid == 0) TS(27);
#pragma unroll
        for (int kc = 9; kc < 14; kc++) {
          if (kc > 9) g2_mma(kc, 1, kc == 10 && HOLD_KC > 9);
          else if (HOLD_KC == 9) { wg_wait<0>(); g2_release(9); }
          if (kc == HOLD_KC) {
            if (tid == 0) TS(28);
            y_prep(0, YP_H);
            bar_sync(NB_END, 256);
          }
          if (kc == 12) y_prep(YP_H, YP_N);
        }
        if (tid == 0) TS(29);
        y_prep(YP_N, 10);
        if (tid == 0) TS(47);
        mbar_wait(BAR(B_XD), 0);
        if (tid == 0) TS(5);
        uint4 v0 = lds128(sb + tid * 16 + P0), v1 = lds128(sb + tid * 16 + P0 + 2048);
        wg_wait<0>();
        if (tid == 0) TS(4);
#pragma unroll
        for (int np = 0; np < 10; np++) {
          const uint32_t pw[4] = {v0.x, v0.y, v0.z, v0.w};
          v0 = v1;
          if (np < 8) {
            if (np == 2) mbar_wait(BAR(B_XD + 1), 0);
            v1 = lds128(sb + tid * 16 + (np + 2 < 5 ? P0 + (np + 2) * 2048 : P1 + (np - 3) * 2048));
          }
          uint32_t o[4];
          ldsm4(q_addr(np), o[0], o[1], o[2], o[3]);
#pragma unroll
          for (int e = 0; e < 4; e++) {
            const float h0 = fmaf(d[8 * np + 2 * e], (e & 1) ? rs1 : rs0, bf_lo(pw[e])), h1 = fmaf(d[8 * np + 2 * e + 1], (e & 1) ? rs1 : rs0, bf_hi(pw[e]));
            o[e] = bfma2(sv[4 * np + e], pack_bf16(fmaf(h0, tanh_fast(h0), h0), fmaf(h1, tanh_fast(h1), h1)), o[e]);
          }
          stsm4(q_addr(np), o[0], o[1], o[2], o[3]);
          if (np & 1) {
            if (np == 9 && tid == 0) TS(50);
            __syncwarp();
            if (lane == 0) mbar_arrive(BAR(B_OUT + (np >> 1)));
          }
        }
      }
    }
  }
}

typedef CUresult (*EncFn)(CUtensorMap*, CUtensorMapDataType, cuuint32_t, void*, const cuuint64_t*, const cuuint64_t*, const cuuint32_t*, const cuuint32_t*,
                          CUtensorMapInterleave, CUtensorMapSwizzle, CUtensorMapL2promotion, CUtensorMapFloatOOBfill);

static void make_map(EncFn enc, CUtensorMap* tm, const void* ptr, int cols, int rows, int bc, int br, int grp, CUtensorMapSwizzle sw,
                     CUtensorMapL2promotion promo = CU_TENSOR_MAP_L2_PROMOTION_NONE) {
  cuuint64_t gd[3] = {(cuuint64_t)(grp ? bc : cols), (cuuint64_t)rows, (cuuint64_t)(cols / bc)};
  cuuint64_t gs[2] = {(cuuint64_t)cols * 2, (cuuint64_t)bc * 2};
  cuuint32_t bd[3] = {(cuuint32_t)bc, (cuuint32_t)br, (cuuint32_t)grp};
  cuuint32_t es[3] = {1, 1, 1};
  CUresult r = enc(tm, CU_TENSOR_MAP_DATA_TYPE_BFLOAT16, grp ? 3 : 2, const_cast<void*>(ptr), gd, gs, bd, es, CU_TENSOR_MAP_INTERLEAVE_NONE, sw,
                   promo, CU_TENSOR_MAP_FLOAT_OOB_FILL_NONE);
  (void)r;
}

}

extern "C" void kernel_launch(void* const* d_in, const int* in_sizes, int n_in, void* d_out, int out_size) {
  using namespace h3;
  (void)in_sizes; (void)n_in; (void)out_size;
  static EncFn enc = nullptr;
  static void *p_h = nullptr, *p_yT = nullptr, *p_kvT = nullptr;
  if (!enc) {
    void* fn = nullptr; cudaDriverEntryPointQueryResult qr;
    cudaGetDriverEntryPoint("cuTensorMapEncodeTiled", &fn, cudaEnableDefault, &qr);
    enc = (EncFn)fn;
    cudaGetSymbolAddress(&p_h, g_h);
    cudaGetSymbolAddress(&p_yT, g_yT);
    cudaGetSymbolAddress(&p_kvT, g_kvT);
    cudaFuncSetAttribute(h3_kernel, cudaFuncAttributeMaxDynamicSharedMemorySize, SMEM_BYTES);
  }
  Params P;
  P.q = (const __nv_bfloat16*)d_in[0]; P.k = (const __nv_bfloat16*)d_in[1]; P.v = (const __nv_bfloat16*)d_in[2];
  P.shift_k = (const __nv_bfloat16*)d_in[3]; P.ssm_k = (const __nv_bfloat16*)d_in[4]; P.ssm_D = (const __nv_bfloat16*)d_in[5];
  P.out = (__nv_bfloat16*)d_out;
  P.w1 = (const __nv_bfloat16*)d_in[7]; P.b1 = (const __nv_bfloat16*)d_in[8]; P.w2 = (const __nv_bfloat16*)d_in[9]; P.b2 = (const __nv_bfloat16*)d_in[10];
  const CUtensorMapSwizzle S128 = CU_TENSOR_MAP_SWIZZLE_128B, S64 = CU_TENSOR_MAP_SWIZZLE_64B, S0 = CU_TENSOR_MAP_SWIZZLE_NONE;
  Maps M;
  make_map(enc, &M.qa, P.q, DM, SL, 64, 128, 0, S128);
  make_map(enc, &M.w1, P.w1, FF, DM, 64, 64, 3, S128);
  make_map(enc, &M.w1x, P.w1, FF, DM, 24, 64, 0, S128, WS_PROMO);
  make_map(enc, &M.k, P.k, DM, SL, 64, 19, 0, S0);
  make_map(enc, &M.v, P.v, DM, SL, 64, 16, 0, S0);
  make_map(enc, &M.hs, p_h, FF, SL, 64, 64, 0, S128);
  make_map(enc, &M.hx, p_h, FF, SL, 24, 64, 0, S0);
  make_map(enc, &M.ha, p_h, FF, SL, 64, 128, 0, S128);
  make_map(enc, &M.w2, P.w2, DM, FF, 64, 64, 2, S128);
  make_map(enc, &M.w2x, P.w2, DM, FF, 64, 64, 0, S128);
  make_map(enc, &M.kvs, p_kvT, SL, DM, 16, 64, 0, CU_TENSOR_MAP_SWIZZLE_32B);
  make_map(enc, &M.qf, P.q, DM, SL, 32, 64, 0, S64);
  make_map(enc, &M.y, p_yT, SL, DM, 64, 16, 0, S128);
  make_map(enc, &M.out, d_out, DM, SL, 32, 64, 0, S64);
  h3_kernel<<<NCTA, 384, SMEM_BYTES>>>(M, P);
}
```

```cpp
#include <cuda_runtime.h>
#include <cuda_bf16.h>
#include <cuda.h>
#include <stdint.h>

namespace h3 {

constexpr int SL = 2048, DM = 640, FF = 1728;
constexpr int NCTA = 128;

__device__ __align__(1024) __nv_bfloat16 g_h[SL * FF];
__device__ __align__(1024) __nv_bfloat16 g_kvT[DM * SL];
__device__ __align__(1024) __nv_bfloat16 g_yT[DM * SL];
__device__ __align__(1024) uint2 g_stat[2 * SL];
__device__ __align__(1024) uint32_t g_cs[2 * 8 * 256];
__device__ __align__(1024) unsigned g_cnt[64 * 32];
__device__ __align__(1024) unsigned g_launch[NCTA * 8];
constexpr int CNT_H = 0;

constexpr int G1_STAGE = 49152, G1_TX = 16384 + 24576 + 3072;
constexpr int HST = 49152;
constexpr int P0 = 81920, P1 = 140288, P2 = 156672;
constexpr int XCH = 4368, XD = 272, X0 = 173056, X4 = 221184;
constexpr int KVS = 196608, KV_BUF = 8960;
constexpr int KT_CH = 8240, KT_O = 16, KT_E = 4144, KT0 = 98304;
constexpr int FIN_Q = X0;
constexpr int MISC = 226816;
constexpr int M_BX = MISC;
constexpr int M_RED0 = M_BX + 2048, M_RED1 = M_BX;
constexpr int M_SK = KVS + 3 * KV_BUF;
constexpr int M_STAT = M_BX + 3584;
constexpr int M_B2 = MISC - 640;
constexpr int M_AUX = M_STAT + 512;
constexpr int M_ZERO = M_AUX + 96;
constexpr int M_BAR = M_ZERO + 16;
constexpr int M_TS = M_BAR + 94 * 8;
constexpr int SMEM_BYTES = M_TS + 256;
__host__ __device__ constexpr int fin_y(int np) {
  return np < 3 ? P0 + 10240 + np * 2048 : (np < 6 ? P1 + 10240 + (np - 3) * 2048 : (np == 6 ? FIN_Q + 20480 : (np < 9 ? X4 + (np - 7) * 2048 : M_BX + 512)));
}
static_assert(fin_y(9) % 1024 == 0 && fin_y(6) % 1024 == 0 && fin_y(6) + 2048 <= KVS && fin_y(7) % 1024 == 0, "smem");
__host__ __device__ constexpr int cv_x(int c) { return c == 4 ? X4 : X0 + c * XCH; }
__host__ __device__ constexpr int cv_p(int c) { return c == 2 ? P2 : ((c == 0 || c == 3) ? P0 : P1); }
__host__ __device__ constexpr int cv_t(int c) { return KT0 + c * KT_CH; }
__host__ __device__ constexpr int g2_a(int s) { return s == 0 ? 0 : (s == 1 ? 40960 : (s == 2 ? 98304 : P2)); }
__host__ __device__ constexpr int g2_b(int s) { return s == 0 ? 16384 : (s == 1 ? 57344 : (s == 2 ? 114688 : KVS)); }
static_assert(M_SK + 2560 <= M_B2 && X4 + XCH <= M_B2 && KVS + 24576 <= X4 && X0 + 4 * XCH <= KVS && FIN_Q + 20480 <= KVS, "smem");
static_assert(KT0 + 5 * KT_CH <= P1 && P1 + 16384 <= P2 && P2 + 16384 <= X0 && SMEM_BYTES <= 232448 && MISC % 512 == 0 && M_BAR % 8 == 0, "smem");
constexpr int B_F1 = 0, B_E1 = 4, B_FR = 8, B_F2 = 12, B_E2 = 16, B_KRAW = 20, B_KT = 22, B_XF = 27, B_HB = 32, B_SD = 40, B_RF = 45,
              B_TD = 48, B_FINQ = 50, B_FINY = 51, B_RED = 52, B_BX = 53, B_KIN = 54, B_XR = 59, B_OUT = 61, B_SK = 66, B_YSLOT = 80, B_YL = 83, B_XD = 86, B_F0 = 89, B_LNI = 90, B_KIN1 = 70, B_XL = 75, B_KD = 60;
constexpr int NB_INIT = 1, NB_INIT2 = 2, NB_AUX = 3, NB_LEAD = 4, NB_GELU = 5, NB_TURN = 6  , NB_END = 8, NB_INIT3 = 9, NB_WG1 = 10;

#define STAG_KC 8
#define STAG_ALL 1
#define STAG_REL 0
#define INC_KC 6
#define KV_MAP 0x764
#define KV_LATE 1
#define PF_KV 0
#define PF_G1 0
#define WS_PROMO CU_TENSOR_MAP_L2_PROMOTION_L2_128B
#define RAW_LATE 0
#define PF_RAW 0x00007
#define SIDE_LD 4
#define SIDE_USE 0x554
#define REL_K 0
#define CS_WAIT 1
#define GELU_NB 8
#define H_ORD 0x73625410
#define W2_PF 7
#define H_FLY 8
#define TB2 2
#define X_A 2
#define FENCE_KIND 1
#define SCH2 0
#define SCH 1
#define A_NB0 14
#define HAND4 1
#define LEAD_KC 1
#define RED_GATE 3
#define XP_KC 4
#define NSH 12
#define NST (27 - NSH)
#define YP_KC 12
#define YFENCE 1
#define Y_KC 8
#define XD_N 6
#define XD_M 8
#define HOLD_KC 11
#define END_KC (NSH - 1)
#define REG_AUX "56"
#define REG_CON "224"
#define LDQ ".nc.L1::no_allocate"
#define LDP ""

__device__ __forceinline__ uint32_t s32(const void* p) { return (uint32_t)__cvta_generic_to_shared(p); }
__device__ __forceinline__ uint32_t clk() { uint32_t t; asm volatile("mov.u32 %0, %%clock;" : "=r"(t)); return t; }
__device__ __forceinline__ bool elect_one() {
  uint32_t p; asm volatile("{\n.reg .pred P;\nelect.sync _|P, 0xffffffff;\nselp.u32 %0, 1, 0, P;\n}" : "=r"(p)); return p;
}
#define ONE(...) do { if (elect_one()) { __VA_ARGS__; } __syncwarp(); } while (0)
__device__ __forceinline__ void mbar_init(uint32_t a, int c) { asm volatile("mbarrier.init.shared::cta.b64 [%0], %1;" ::"r"(a), "r"(c) : "memory"); }
__device__ __forceinline__ void mbar_expect(uint32_t a, int b) { asm volatile("mbarrier.arrive.expect_tx.shared::cta.b64 _, [%0], %1;" ::"r"(a), "r"(b) : "memory"); }
__device__ __forceinline__ void mbar_arrive(uint32_t a) { asm volatile("mbarrier.arrive.shared::cta.b64 _, [%0];" ::"r"(a) : "memory"); }
__device__ __forceinline__ bool spin_guard(uint32_t& n, uint32_t) {
  return ++n > (1u << 20);
}
__device__ __forceinline__ void mbar_wait(uint32_t a, int ph) {
  asm volatile("{\n.reg .pred p;\n.reg .u32 n;\nmov.u32 n, 0;\nW:\n.pragma \"nounroll\";\nmbarrier.try_wait.parity.shared::cta.b64 p, [%0], %1;\n"
               "add.u32 n, n, 1;\nsetp.ge.or.u32 p, n, 0x100000, p;\n@!p bra W;\n}" ::"r"(a), "r"(ph) : "memory");
}
__device__ __forceinline__ bool mbar_test(uint32_t a, int ph) {
  uint32_t ok;
  asm volatile("{\n.reg .pred p;\nmbarrier.test_wait.parity.shared::cta.b64 p, [%1], %2;\nselp.u32 %0, 1, 0, p;\n}" : "=r"(ok) : "r"(a), "r"(ph) : "memory");
  return __all_sync(0xffffffffu, ok);
}
__device__ __forceinline__ void sched_fence(uint32_t a) {
  asm volatile("{\n.reg .pred p;\nsetp.eq.u32 p, %0, 0;\n@p exit;\n}" ::"r"(a) : "memory");
}
__device__ __forceinline__ void tma2d(uint32_t dst, const CUtensorMap* tm, int c0, int c1, uint32_t bar) {
  asm volatile("cp.async.bulk.tensor.2d.shared::cluster.global.mbarrier::complete_tx::bytes [%0], [%1, {%3, %4}], [%2];"
               ::"r"(dst), "l"(tm), "r"(bar), "r"(c0), "r"(c1) : "memory");
}
__device__ __forceinline__ void tma3d(uint32_t dst, const CUtensorMap* tm, int c0, int c1, int c2, uint32_t bar) {
  asm volatile("cp.async.bulk.tensor.3d.shared::cluster.global.mbarrier::complete_tx::bytes [%0], [%1, {%3, %4, %5}], [%2];"
               ::"r"(dst), "l"(tm), "r"(bar), "r"(c0), "r"(c1), "r"(c2) : "memory");
}
__device__ __forceinline__ void tma2d_st(const CUtensorMap* tm, int c0, int c1, uint32_t src) {
  asm volatile("cp.async.bulk.tensor.2d.global.shared::cta.bulk_group [%0, {%2, %3}], [%1];" ::"l"(tm), "r"(src), "r"(c0), "r"(c1) : "memory");
}
__device__ __forceinline__ void tma3d_st(const CUtensorMap* tm, int c0, int c1, int c2, uint32_t src) {
  asm volatile("cp.async.bulk.tensor.3d.global.shared::cta.bulk_group [%0, {%2, %3, %4}], [%1];" ::"l"(tm), "r"(src), "r"(c0), "r"(c1), "r"(c2) : "memory");
}
__device__ __forceinline__ void bulk_g2s(uint32_t dst, const void* src, int bytes, uint32_t bar) {
  asm volatile("cp.async.bulk.shared::cluster.global.mbarrier::complete_tx::bytes [%0], [%1], %2, [%3];" ::"r"(dst), "l"(src), "r"(bytes), "r"(bar) : "memory");
}
__device__ __forceinline__ void bulk_commit() { asm volatile("cp.async.bulk.commit_group;" ::: "memory"); }
__device__ __forceinline__ void bulk_wait_read() { asm volatile("cp.async.bulk.wait_group.read 0;" ::: "memory"); }
__device__ __forceinline__ void bulk_wait_all() { asm volatile("cp.async.bulk.wait_group 0;" ::: "memory"); }
__device__ __forceinline__ void fence_async_smem() { asm volatile("fence.proxy.async.shared::cta;" ::: "memory"); }
__device__ __forceinline__ void fence_async_all() { asm volatile("fence.proxy.async;" ::: "memory"); }
__device__ __forceinline__ void fence_gpu() { asm volatile("fence.acq_rel.gpu;" ::: "memory"); }
#define bar_sync(id, n) asm volatile("bar.sync %0, %1;" ::"n"(id), "n"(n) : "memory")
#define bar_arrive(id, n) asm volatile("bar.arrive %0, %1;" ::"n"(id), "n"(n) : "memory")
__device__ __forceinline__ void wg_fence() { asm volatile("wgmma.fence.sync.aligned;" ::: "memory"); }
__device__ __forceinline__ void wg_commit() { asm volatile("wgmma.commit_group.sync.aligned;" ::: "memory"); }
template <int N> __device__ __forceinline__ void wg_wait() { asm volatile("wgmma.wait_group.sync.aligned %0;" ::"n"(N) : "memory"); }
__device__ __forceinline__ uint64_t mkdesc(uint32_t addr, uint32_t lbo, uint32_t sbo, int sw) {
  return (uint64_t)((addr & 0x3FFFF) >> 4) | ((uint64_t)(lbo >> 4) << 16) | ((uint64_t)(sbo >> 4) << 32) | ((uint64_t)sw << 62);
}
__device__ __forceinline__ uint32_t ldg32(const void* p) { uint32_t v; asm volatile("ld.global" LDQ ".b32 %0, [%1];" : "=r"(v) : "l"(p)); return v; }
template <int OFF> __device__ __forceinline__ uint32_t ldg32o(const void* p) { uint32_t v; asm volatile("ld.global" LDQ ".b32 %0, [%1+%2];" : "=r"(v) : "l"(p), "n"(OFF)); return v; }
template <int I> __device__ __forceinline__ void kv_loads(const void* kp, const void* vp, uint32_t (&kk)[16], uint32_t (&o)[16]) {
  kk[I] = ldg32o<I * DM * 2>(kp); o[I] = ldg32o<I * DM * 2>(vp);
  if constexpr (I < 15) kv_loads<I + 1>(kp, vp, kk, o);
}
__device__ __forceinline__ uint4 ldg128(const void* p) {
  uint4 v; asm volatile("ld.global" LDQ LDP ".v4.b32 {%0,%1,%2,%3}, [%4];" : "=r"(v.x), "=r"(v.y), "=r"(v.z), "=r"(v.w) : "l"(p)); return v;
}
__device__ __forceinline__ void stg128(void* p, uint32_t x, uint32_t y, uint32_t z, uint32_t w) {
  asm volatile("st.global.v4.b32 [%0], {%1,%2,%3,%4};" ::"l"(p), "r"(x), "r"(y), "r"(z), "r"(w) : "memory");
}
__device__ __forceinline__ uint4 ld_relaxed128(const void* p) {
  uint4 v; asm volatile("ld.relaxed.gpu.global.v4.b32 {%0,%1,%2,%3}, [%4];" : "=r"(v.x), "=r"(v.y), "=r"(v.z), "=r"(v.w) : "l"(p) : "memory"); return v;
}
__device__ __forceinline__ uint2 ld_relaxed64(const void* p) {
  uint2 v; asm volatile("ld.relaxed.gpu.global.v2.b32 {%0,%1}, [%2];" : "=r"(v.x), "=r"(v.y) : "l"(p) : "memory"); return v;
}
__device__ __forceinline__ uint4 ld_relaxed_b128(const void* p) {
  uint4 v; asm volatile("{\n.reg .b128 t;\nld.relaxed.gpu.global.b128 t, [%4];\nmov.b128 {%0,%1,%2,%3}, t;\n}" : "=r"(v.x), "=r"(v.y), "=r"(v.z), "=r"(v.w) : "l"(p) : "memory"); return v;
}
__device__ __forceinline__ void st_relaxed_b128(void* p, uint32_t x, uint32_t y, uint32_t z, uint32_t w) {
  asm volatile("{\n.reg .b128 t;\nmov.b128 t, {%1,%2,%3,%4};\nst.relaxed.gpu.global.b128 [%0], t;\n}" ::"l"(p), "r"(x), "r"(y), "r"(z), "r"(w) : "memory");
}
__device__ __forceinline__ void st_relaxed64(void* p, uint32_t x, uint32_t y) {
  asm volatile("{\n.reg .b64 t;\nmov.b64 t, {%1,%2};\nst.relaxed.gpu.global.b64 [%0], t;\n}" ::"l"(p), "r"(x), "r"(y) : "memory");
}
__device__ __forceinline__ void st_relaxed32(void* p, uint32_t x) { asm volatile("st.relaxed.gpu.global.b32 [%0], %1;" ::"l"(p), "r"(x) : "memory"); }
__device__ __forceinline__ uint32_t ld_relaxed32(const void* p) { uint32_t v; asm volatile("ld.relaxed.gpu.global.b32 %0, [%1];" : "=r"(v) : "l"(p) : "memory"); return v; }
__device__ __forceinline__ void st_relaxed128(void* p, uint32_t x, uint32_t y, uint32_t z, uint32_t w) {
  asm volatile("{\n.reg .b64 t, u;\nmov.b64 t, {%1,%2};\nmov.b64 u, {%3,%4};\nst.relaxed.gpu.global.v2.b64 [%0], {t, u};\n}" ::"l"(p), "r"(x), "r"(y), "r"(z), "r"(w) : "memory");
}
__device__ __forceinline__ void fence_release() { asm volatile("fence.proxy.async.global;\nfence.release.gpu;" ::: "memory"); }
__device__ __forceinline__ void fence_acquire() { asm volatile("fence.acquire.gpu;\nfence.proxy.async.global;" ::: "memory"); }
__device__ __forceinline__ void signal_cnt(int idx) { asm volatile("red.relaxed.gpu.global.add.u32 [%0], 1;" ::"l"(&g_cnt[idx * 32]) : "memory"); }
__device__ __forceinline__ void wait_cnt(int idx, unsigned target) {
  uint32_t n = 0;
#pragma unroll 1
  while (!__all_sync(0xffffffffu, (int)(ld_relaxed32(&g_cnt[idx * 32]) - target) >= 0)) {
    if (spin_guard(n, 0x100 + idx)) break;
  }
  fence_acquire();
}
__device__ __forceinline__ void bulk_s2g(void* dst, uint32_t src, int bytes) {
  asm volatile("cp.async.bulk.global.shared::cta.bulk_group [%0], [%1], %2;" ::"l"(dst), "r"(src), "r"(bytes) : "memory");
}
__device__ __forceinline__ void bulk_add_s2g(void* dst, uint32_t src, int bytes) {
  asm volatile("cp.reduce.async.bulk.global.shared::cta.bulk_group.add.noftz.bf16 [%0], [%1], %2;" ::"l"(dst), "r"(src), "r"(bytes) : "memory");
}
__device__ __forceinline__ void prefetch_l2(const void* p, int bytes) { asm volatile("cp.async.bulk.prefetch.L2.global [%0], %1;" ::"l"(p), "r"(bytes) : "memory"); }
__device__ __forceinline__ void prefetch_tile(const CUtensorMap* tm, int c0, int c1) {
  asm volatile("cp.async.bulk.prefetch.tensor.2d.L2.global.tile [%0, {%1, %2}];" ::"l"(tm), "r"(c0), "r"(c1) : "memory");
}
__device__ __forceinline__ void prefetch_map(const CUtensorMap* tm) { asm volatile("prefetch.tensormap [%0];" ::"l"(tm) : "memory"); }
__device__ __forceinline__ uint32_t pack_bf16(float lo, float hi) {
  uint32_t r; asm("cvt.rn.bf16x2.f32 %0, %1, %2;" : "=r"(r) : "f"(hi), "f"(lo)); return r;
}
__device__ __forceinline__ float bf_lo(uint32_t v) { return __uint_as_float(v << 16); }
__device__ __forceinline__ float bf_hi(uint32_t v) { return __uint_as_float(v & 0xFFFF0000u); }
__device__ __forceinline__ float bf_round(float x) { return __bfloat162float(__float2bfloat16_rn(x)); }
__device__ __forceinline__ uint32_t bmul2(uint32_t a, uint32_t b) { uint32_t r; asm("mul.rn.bf16x2 %0, %1, %2;" : "=r"(r) : "r"(a), "r"(b)); return r; }
__device__ __forceinline__ uint32_t bfma2(uint32_t a, uint32_t b, uint32_t c) { uint32_t r; asm("fma.rn.bf16x2 %0, %1, %2, %3;" : "=r"(r) : "r"(a), "r"(b), "r"(c)); return r; }
__device__ __forceinline__ uint32_t badd2(uint32_t a, uint32_t b) { uint32_t r; asm("add.rn.bf16x2 %0, %1, %2;" : "=r"(r) : "r"(a), "r"(b)); return r; }
__device__ __forceinline__ uint32_t bsub2(uint32_t a, uint32_t b) { uint32_t r; asm("sub.rn.bf16x2 %0, %1, %2;" : "=r"(r) : "r"(a), "r"(b)); return r; }
__device__ __forceinline__ float tanh_fast(float x) { float r; asm("tanh.approx.f32 %0, %1;" : "=f"(r) : "f"(x)); return r; }
__device__ __forceinline__ float rcp_fast(float x) { float r; asm("rcp.approx.ftz.f32 %0, %1;" : "=f"(r) : "f"(x)); return r; }
__device__ __forceinline__ float sqrt_fast(float x) { float r; asm("sqrt.approx.ftz.f32 %0, %1;" : "=f"(r) : "f"(x)); return r; }
__device__ __forceinline__ uint32_t lds32(uint32_t a) { uint32_t v; asm volatile("ld.shared.b32 %0, [%1];" : "=r"(v) : "r"(a)); return v; }
__device__ __forceinline__ uint4 lds128(uint32_t a) { uint4 v; asm volatile("ld.shared.v4.b32 {%0,%1,%2,%3}, [%4];" : "=r"(v.x), "=r"(v.y), "=r"(v.z), "=r"(v.w) : "r"(a)); return v; }
__device__ __forceinline__ float2 lds64f(uint32_t a) { float2 v; asm volatile("ld.shared.v2.f32 {%0,%1}, [%2];" : "=f"(v.x), "=f"(v.y) : "r"(a)); return v; }
__device__ __forceinline__ void sts64f(uint32_t a, float x, float y) { asm volatile("st.shared.v2.f32 [%0], {%1,%2};" ::"r"(a), "f"(x), "f"(y) : "memory"); }
__device__ __forceinline__ void sts32(uint32_t a, uint32_t x) { asm volatile("st.shared.b32 [%0], %1;" ::"r"(a), "r"(x) : "memory"); }
__device__ __forceinline__ void sts128(uint32_t a, uint32_t x, uint32_t y, uint32_t z, uint32_t w) { asm volatile("st.shared.v4.b32 [%0], {%1,%2,%3,%4};" ::"r"(a), "r"(x), "r"(y), "r"(z), "r"(w) : "memory"); }
__device__ __forceinline__ void stsm4(uint32_t a, uint32_t r0, uint32_t r1, uint32_t r2, uint32_t r3) {
  asm volatile("stmatrix.sync.aligned.m8n8.x4.shared.b16 [%0], {%1,%2,%3,%4};" ::"r"(a), "r"(r0), "r"(r1), "r"(r2), "r"(r3) : "memory");
}
__device__ __forceinline__ void stsm4t(uint32_t a, uint32_t r0, uint32_t r1, uint32_t r2, uint32_t r3) {
  asm volatile("stmatrix.sync.aligned.m8n8.x4.trans.shared.b16 [%0], {%1,%2,%3,%4};" ::"r"(a), "r"(r0), "r"(r1), "r"(r2), "r"(r3) : "memory");
}
__device__ __forceinline__ void stsm2(uint32_t a, uint32_t r0, uint32_t r1) {
  asm volatile("stmatrix.sync.aligned.m8n8.x2.shared.b16 [%0], {%1,%2};" ::"r"(a), "r"(r0), "r"(r1) : "memory");
}
__device__ __forceinline__ void ldsm4(uint32_t a, uint32_t& r0, uint32_t& r1, uint32_t& r2, uint32_t& r3) {
  asm volatile("ldmatrix.sync.aligned.m8n8.x4.shared.b16 {%0,%1,%2,%3}, [%4];" : "=r"(r0), "=r"(r1), "=r"(r2), "=r"(r3) : "r"(a) : "memory");
}
__device__ __forceinline__ void ldsm4t(uint32_t a, uint32_t& r0, uint32_t& r1, uint32_t& r2, uint32_t& r3) {
  asm volatile("ldmatrix.sync.aligned.m8n8.x4.trans.shared.b16 {%0,%1,%2,%3}, [%4];" : "=r"(r0), "=r"(r1), "=r"(r2), "=r"(r3) : "r"(a) : "memory");
}
__device__ __forceinline__ uint32_t mapa(uint32_t a, uint32_t rank) { uint32_t r; asm("mapa.shared::cluster.u32 %0, %1, %2;" : "=r"(r) : "r"(a), "r"(rank)); return r; }
__device__ __forceinline__ void mbar_arrive_remote(uint32_t a) { asm volatile("mbarrier.arrive.relaxed.cluster.shared::cluster.b64 _, [%0];" ::"r"(a) : "memory"); }
__device__ __forceinline__ void st_async128(uint32_t a, uint32_t x, uint32_t y, uint32_t z, uint32_t w, uint32_t bar) {
  asm volatile("st.async.weak.shared::cluster.mbarrier::complete_tx::bytes.v4.b32 [%0], {%1,%2,%3,%4}, [%5];" ::"r"(a), "r"(x), "r"(y), "r"(z), "r"(w), "r"(bar) : "memory");
}
#define TS(i)

#define TSKV
__device__ __forceinline__ void wg_ss_216(float (&d)[108], uint64_t da, uint64_t db, int sd) {
  asm volatile("{\n.reg .pred p;\nsetp.ne.b32 p, %110, 0;\n"
    "wgmma.mma_async.sync.aligned.m64n216k16.f32.bf16.bf16 {%0,%1,%2,%3,%4,%5,%6,%7,%8,%9,%10,%11,%12,%13,%14,%15,%16,%17,%18,%19,%20,%21,%22,%23,%24,%25,%26,%27,%28,%29,%30,%31,%32,%33,%34,%35,%36,%37,%38,%39,%40,%41,%42,%43,%44,%45,%46,%47,%48,%49,%50,%51,%52,%53,%54,%55,%56,%57,%58,%59,%60,%61,%62,%63,%64,%65,%66,%67,%68,%69,%70,%71,%72,%73,%74,%75,%76,%77,%78,%79,%80,%81,%82,%83,%84,%85,%86,%87,%88,%89,%90,%91,%92,%93,%94,%95,%96,%97,%98,%99,%100,%101,%102,%103,%104,%105,%106,%107}, %108, %109, p, 1, 1, 0, 1;\n}\n"
    : "+f"(d[0]),"+f"(d[1]),"+f"(d[2]),"+f"(d[3]),"+f"(d[4]),"+f"(d[5]),"+f"(d[6]),"+f"(d[7]),"+f"(d[8]),"+f"(d[9]),"+f"(d[10]),"+f"(d[11]),"+f"(d[12]),"+f"(d[13]),"+f"(d[14]),"+f"(d[15]),"+f"(d[16]),"+f"(d[17]),"+f"(d[18]),"+f"(d[19]),"+f"(d[20]),"+f"(d[21]),"+f"(d[22]),"+f"(d[23]),"+f"(d[24]),"+f"(d[25]),"+f"(d[26]),"+f"(d[27]),"+f"(d[28]),"+f"(d[29]),"+f"(d[30]),"+f"(d[31]),"+f"(d[32]),"+f"(d[33]),"+f"(d[34]),"+f"(d[35]),"+f"(d[36]),"+f"(d[37]),"+f"(d[38]),"+f"(d[39]),"+f"(d[40]),"+f"(d[41]),"+f"(d[42]),"+f"(d[43]),"+f"(d[44]),"+f"(d[45]),"+f"(d[46]),"+f"(d[47]),"+f"(d[48]),"+f"(d[49]),"+f"(d[50]),"+f"(d[51]),"+f"(d[52]),"+f"(d[53]),"+f"(d[54]),"+f"(d[55]),"+f"(d[56]),"+f"(d[57]),"+f"(d[58]),"+f"(d[59]),"+f"(d[60]),"+f"(d[61]),"+f"(d[62]),"+f"(d[63]),"+f"(d[64]),"+f"(d[65]),"+f"(d[66]),"+f"(d[67]),"+f"(d[68]),"+f"(d[69]),"+f"(d[70]),"+f"(d[71]),"+f"(d[72]),"+f"(d[73]),"+f"(d[74]),"+f"(d[75]),"+f"(d[76]),"+f"(d[77]),"+f"(d[78]),"+f"(d[79]),"+f"(d[80]),"+f"(d[81]),"+f"(d[82]),"+f"(d[83]),"+f"(d[84]),"+f"(d[85]),"+f"(d[86]),"+f"(d[87]),"+f"(d[88]),"+f"(d[89]),"+f"(d[90]),"+f"(d[91]),"+f"(d[92]),"+f"(d[93]),"+f"(d[94]),"+f"(d[95]),"+f"(d[96]),"+f"(d[97]),"+f"(d[98]),"+f"(d[99]),"+f"(d[100]),"+f"(d[101]),"+f"(d[102]),"+f"(d[103]),"+f"(d[104]),"+f"(d[105]),"+f"(d[106]),"+f"(d[107]) : "l"(da), "l"(db), "r"(sd));
}
__device__ __forceinline__ void wg_ss_160(float (&d)[80], uint64_t da, uint64_t db, int sd) {
  asm volatile("{\n.reg .pred p;\nsetp.ne.b32 p, %82, 0;\n"
    "wgmma.mma_async.sync.aligned.m64n160k16.f32.bf16.bf16 {%0,%1,%2,%3,%4,%5,%6,%7,%8,%9,%10,%11,%12,%13,%14,%15,%16,%17,%18,%19,%20,%21,%22,%23,%24,%25,%26,%27,%28,%29,%30,%31,%32,%33,%34,%35,%36,%37,%38,%39,%40,%41,%42,%43,%44,%45,%46,%47,%48,%49,%50,%51,%52,%53,%54,%55,%56,%57,%58,%59,%60,%61,%62,%63,%64,%65,%66,%67,%68,%69,%70,%71,%72,%73,%74,%75,%76,%77,%78,%79}, %80, %81, p, 1, 1, 0, 1;\n}\n"
    : "+f"(d[0]),"+f"(d[1]),"+f"(d[2]),"+f"(d[3]),"+f"(d[4]),"+f"(d[5]),"+f"(d[6]),"+f"(d[7]),"+f"(d[8]),"+f"(d[9]),"+f"(d[10]),"+f"(d[11]),"+f"(d[12]),"+f"(d[13]),"+f"(d[14]),"+f"(d[15]),"+f"(d[16]),"+f"(d[17]),"+f"(d[18]),"+f"(d[19]),"+f"(d[20]),"+f"(d[21]),"+f"(d[22]),"+f"(d[23]),"+f"(d[24]),"+f"(d[25]),"+f"(d[26]),"+f"(d[27]),"+f"(d[28]),"+f"(d[29]),"+f"(d[30]),"+f"(d[31]),"+f"(d[32]),"+f"(d[33]),"+f"(d[34]),"+f"(d[35]),"+f"(d[36]),"+f"(d[37]),"+f"(d[38]),"+f"(d[39]),"+f"(d[40]),"+f"(d[41]),"+f"(d[42]),"+f"(d[43]),"+f"(d[44]),"+f"(d[45]),"+f"(d[46]),"+f"(d[47]),"+f"(d[48]),"+f"(d[49]),"+f"(d[50]),"+f"(d[51]),"+f"(d[52]),"+f"(d[53]),"+f"(d[54]),"+f"(d[55]),"+f"(d[56]),"+f"(d[57]),"+f"(d[58]),"+f"(d[59]),"+f"(d[60]),"+f"(d[61]),"+f"(d[62]),"+f"(d[63]),"+f"(d[64]),"+f"(d[65]),"+f"(d[66]),"+f"(d[67]),"+f"(d[68]),"+f"(d[69]),"+f"(d[70]),"+f"(d[71]),"+f"(d[72]),"+f"(d[73]),"+f"(d[74]),"+f"(d[75]),"+f"(d[76]),"+f"(d[77]),"+f"(d[78]),"+f"(d[79]) : "l"(da), "l"(db), "r"(sd));
}
__device__ __forceinline__ void wg_rs_216(float (&d)[108], uint32_t a0, uint32_t a1, uint32_t a2, uint32_t a3, uint64_t db) {
  asm volatile("{\n.reg .pred p;\nsetp.ne.b32 p, 1, 0;\n"
    "wgmma.mma_async.sync.aligned.m64n216k16.f32.bf16.bf16 {%0,%1,%2,%3,%4,%5,%6,%7,%8,%9,%10,%11,%12,%13,%14,%15,%16,%17,%18,%19,%20,%21,%22,%23,%24,%25,%26,%27,%28,%29,%30,%31,%32,%33,%34,%35,%36,%37,%38,%39,%40,%41,%42,%43,%44,%45,%46,%47,%48,%49,%50,%51,%52,%53,%54,%55,%56,%57,%58,%59,%60,%61,%62,%63,%64,%65,%66,%67,%68,%69,%70,%71,%72,%73,%74,%75,%76,%77,%78,%79,%80,%81,%82,%83,%84,%85,%86,%87,%88,%89,%90,%91,%92,%93,%94,%95,%96,%97,%98,%99,%100,%101,%102,%103,%104,%105,%106,%107}, {%108,%109,%110,%111}, %112, p, 1, 1, 1;\n}\n"
    : "+f"(d[0]),"+f"(d[1]),"+f"(d[2]),"+f"(d[3]),"+f"(d[4]),"+f"(d[5]),"+f"(d[6]),"+f"(d[7]),"+f"(d[8]),"+f"(d[9]),"+f"(d[10]),"+f"(d[11]),"+f"(d[12]),"+f"(d[13]),"+f"(d[14]),"+f"(d[15]),"+f"(d[16]),"+f"(d[17]),"+f"(d[18]),"+f"(d[19]),"+f"(d[20]),"+f"(d[21]),"+f"(d[22]),"+f"(d[23]),"+f"(d[24]),"+f"(d[25]),"+f"(d[26]),"+f"(d[27]),"+f"(d[28]),"+f"(d[29]),"+f"(d[30]),"+f"(d[31]),"+f"(d[32]),"+f"(d[33]),"+f"(d[34]),"+f"(d[35]),"+f"(d[36]),"+f"(d[37]),"+f"(d[38]),"+f"(d[39]),"+f"(d[40]),"+f"(d[41]),"+f"(d[42]),"+f"(d[43]),"+f"(d[44]),"+f"(d[45]),"+f"(d[46]),"+f"(d[47]),"+f"(d[48]),"+f"(d[49]),"+f"(d[50]),"+f"(d[51]),"+f"(d[52]),"+f"(d[53]),"+f"(d[54]),"+f"(d[55]),"+f"(d[56]),"+f"(d[57]),"+f"(d[58]),"+f"(d[59]),"+f"(d[60]),"+f"(d[61]),"+f"(d[62]),"+f"(d[63]),"+f"(d[64]),"+f"(d[65]),"+f"(d[66]),"+f"(d[67]),"+f"(d[68]),"+f"(d[69]),"+f"(d[70]),"+f"(d[71]),"+f"(d[72]),"+f"(d[73]),"+f"(d[74]),"+f"(d[75]),"+f"(d[76]),"+f"(d[77]),"+f"(d[78]),"+f"(d[79]),"+f"(d[80]),"+f"(d[81]),"+f"(d[82]),"+f"(d[83]),"+f"(d[84]),"+f"(d[85]),"+f"(d[86]),"+f"(d[87]),"+f"(d[88]),"+f"(d[89]),"+f"(d[90]),"+f"(d[91]),"+f"(d[92]),"+f"(d[93]),"+f"(d[94]),"+f"(d[95]),"+f"(d[96]),"+f"(d[97]),"+f"(d[98]),"+f"(d[99]),"+f"(d[100]),"+f"(d[101]),"+f"(d[102]),"+f"(d[103]),"+f"(d[104]),"+f"(d[105]),"+f"(d[106]),"+f"(d[107]) : "r"(a0), "r"(a1), "r"(a2), "r"(a3), "l"(db));
}
__device__ __forceinline__ void wg_cv_0_0(float (&d)[128], uint32_t a0, uint32_t a1, uint32_t a2, uint32_t a3, uint32_t db) {
  asm volatile("{\n.reg .pred p;\n.reg .b64 t;\nsetp.ne.b32 p, 0, 0;\nmov.b64 t, {%20, 8};\n"
    "wgmma.mma_async.sync.aligned.m64n32k16.f32.bf16.bf16 {%0,%1,%2,%3,%4,%5,%6,%7,%8,%9,%10,%11,%12,%13,%14,%15}, {%16,%17,%18,%19}, t, p, 1, 1, 0;\n}\n"
    : "+f"(d[0]),"+f"(d[1]),"+f"(d[2]),"+f"(d[3]),"+f"(d[4]),"+f"(d[5]),"+f"(d[6]),"+f"(d[7]),"+f"(d[8]),"+f"(d[9]),"+f"(d[10]),"+f"(d[11]),"+f"(d[12]),"+f"(d[13]),"+f"(d[14]),"+f"(d[15]) : "r"(a0), "r"(a1), "r"(a2), "r"(a3), "r"(db));
}
__device__ __forceinline__ void wg_cv_0_1(float (&d)[128], uint32_t a0, uint32_t a1, uint32_t a2, uint32_t a3, uint32_t db) {
  asm volatile("{\n.reg .pred p;\n.reg .b64 t;\nsetp.ne.b32 p, 1, 0;\nmov.b64 t, {%20, 8};\n"
    "wgmma.mma_async.sync.aligned.m64n32k16.f32.bf16.bf16 {%0,%1,%2,%3,%4,%5,%6,%7,%8,%9,%10,%11,%12,%13,%14,%15}, {%16,%17,%18,%19}, t, p, 1, 1, 0;\n}\n"
    : "+f"(d[0]),"+f"(d[1]),"+f"(d[2]),"+f"(d[3]),"+f"(d[4]),"+f"(d[5]),"+f"(d[6]),"+f"(d[7]),"+f"(d[8]),"+f"(d[9]),"+f"(d[10]),"+f"(d[11]),"+f"(d[12]),"+f"(d[13]),"+f"(d[14]),"+f"(d[15]) : "r"(a0), "r"(a1), "r"(a2), "r"(a3), "r"(db));
}
__device__ __forceinline__ void wg_cv_1_0(float (&d)[128], uint32_t a0, uint32_t a1, uint32_t a2, uint32_t a3, uint32_t db) {
  asm volatile("{\n.reg .pred p;\n.reg .b64 t;\nsetp.ne.b32 p, 0, 0;\nmov.b64 t, {%20, 8};\n"
    "wgmma.mma_async.sync.aligned.m64n32k16.f32.bf16.bf16 {%0,%1,%2,%3,%4,%5,%6,%7,%8,%9,%10,%11,%12,%13,%14,%15}, {%16,%17,%18,%19}, t, p, 1, 1, 0;\n}\n"
    : "+f"(d[16]),"+f"(d[17]),"+f"(d[18]),"+f"(d[19]),"+f"(d[20]),"+f"(d[21]),"+f"(d[22]),"+f"(d[23]),"+f"(d[24]),"+f"(d[25]),"+f"(d[26]),"+f"(d[27]),"+f"(d[28]),"+f"(d[29]),"+f"(d[30]),"+f"(d[31]) : "r"(a0), "r"(a1), "r"(a2), "r"(a3), "r"(db));
}
__device__ __forceinline__ void wg_cv_1_1(float (&d)[128], uint32_t a0, uint32_t a1, uint32_t a2, uint32_t a3, uint32_t db) {
  asm volatile("{\n.reg .pred p;\n.reg .b64 t;\nsetp.ne.b32 p, 1, 0;\nmov.b64 t, {%20, 8};\n"
    "wgmma.mma_async.sync.aligned.m64n32k16.f32.bf16.bf16 {%0,%1,%2,%3,%4,%5,%6,%7,%8,%9,%10,%11,%12,%13,%14,%15}, {%16,%17,%18,%19}, t, p, 1, 1, 0;\n}\n"
    : "+f"(d[16]),"+f"(d[17]),"+f"(d[18]),"+f"(d[19]),"+f"(d[20]),"+f"(d[21]),"+f"(d[22]),"+f"(d[23]),"+f"(d[24]),"+f"(d[25]),"+f"(d[26]),"+f"(d[27]),"+f"(d[28]),"+f"(d[29]),"+f"(d[30]),"+f"(d[31]) : "r"(a0), "r"(a1), "r"(a2), "r"(a3), "r"(db));
}
__device__ __forceinline__ void wg_cv_2_0(float (&d)[128], uint32_t a0, uint32_t a1, uint32_t a2, uint32_t a3, uint32_t db) {
  asm volatile("{\n.reg .pred p;\n.reg .b64 t;\nsetp.ne.b32 p, 0, 0;\nmov.b64 t, {%20, 8};\n"
    "wgmma.mma_async.sync.aligned.m64n32k16.f32.bf16.bf16 {%0,%1,%2,%3,%4,%5,%6,%7,%8,%9,%10,%11,%12,%13,%14,%15}, {%16,%17,%18,%19}, t, p, 1, 1, 0;\n}\n"
    : "+f"(d[32]),"+f"(d[33]),"+f"(d[34]),"+f"(d[35]),"+f"(d[36]),"+f"(d[37]),"+f"(d[38]),"+f"(d[39]),"+f"(d[40]),"+f"(d[41]),"+f"(d[42]),"+f"(d[43]),"+f"(d[44]),"+f"(d[45]),"+f"(d[46]),"+f"(d[47]) : "r"(a0), "r"(a1), "r"(a2), "r"(a3), "r"(db));
}
__device__ __forceinline__ void wg_cv_2_1(float (&d)[128], uint32_t a0, uint32_t a1, uint32_t a2, uint32_t a3, uint32_t db) {
  asm volatile("{\n.reg .pred p;\n.reg .b64 t;\nsetp.ne.b32 p, 1, 0;\nmov.b64 t, {%20, 8};\n"
    "wgmma.mma_async.sync.aligned.m64n32k16.f32.bf16.bf16 {%0,%1,%2,%3,%4,%5,%6,%7,%8,%9,%10,%11,%12,%13,%14,%15}, {%16,%17,%18,%19}, t, p, 1, 1, 0;\n}\n"
    : "+f"(d[32]),"+f"(d[33]),"+f"(d[34]),"+f"(d[35]),"+f"(d[36]),"+f"(d[37]),"+f"(d[38]),"+f"(d[39]),"+f"(d[40]),"+f"(d[41]),"+f"(d[42]),"+f"(d[43]),"+f"(d[44]),"+f"(d[45]),"+f"(d[46]),"+f"(d[47]) : "r"(a0), "r"(a1), "r"(a2), "r"(a3), "r"(db));
}
__device__ __forceinline__ void wg_cv_3_0(float (&d)[128], uint32_t a0, uint32_t a1, uint32_t a2, uint32_t a3, uint32_t db) {
  asm volatile("{\n.reg .pred p;\n.reg .b64 t;\nsetp.ne.b32 p, 0, 0;\nmov.b64 t, {%20, 8};\n"
    "wgmma.mma_async.sync.aligned.m64n32k16.f32.bf16.bf16 {%0,%1,%2,%3,%4,%5,%6,%7,%8,%9,%10,%11,%12,%13,%14,%15}, {%16,%17,%18,%19}, t, p, 1, 1, 0;\n}\n"
    : "+f"(d[48]),"+f"(d[49]),"+f"(d[50]),"+f"(d[51]),"+f"(d[52]),"+f"(d[53]),"+f"(d[54]),"+f"(d[55]),"+f"(d[56]),"+f"(d[57]),"+f"(d[58]),"+f"(d[59]),"+f"(d[60]),"+f"(d[61]),"+f"(d[62]),"+f"(d[63]) : "r"(a0), "r"(a1), "r"(a2), "r"(a3), "r"(db));
}
__device__ __forceinline__ void wg_cv_3_1(float (&d)[128], uint32_t a0, uint32_t a1, uint32_t a2, uint32_t a3, uint32_t db) {
  asm volatile("{\n.reg .pred p;\n.reg .b64 t;\nsetp.ne.b32 p, 1, 0;\nmov.b64 t, {%20, 8};\n"
    "wgmma.mma_async.sync.aligned.m64n32k16.f32.bf16.bf16 {%0,%1,%2,%3,%4,%5,%6,%7,%8,%9,%10,%11,%12,%13,%14,%15}, {%16,%17,%18,%19}, t, p, 1, 1, 0;\n}\n"
    : "+f"(d[48]),"+f"(d[49]),"+f"(d[50]),"+f"(d[51]),"+f"(d[52]),"+f"(d[53]),"+f"(d[54]),"+f"(d[55]),"+f"(d[56]),"+f"(d[57]),"+f"(d[58]),"+f"(d[59]),"+f"(d[60]),"+f"(d[61]),"+f"(d[62]),"+f"(d[63]) : "r"(a0), "r"(a1), "r"(a2), "r"(a3), "r"(db));
}
__device__ __forceinline__ void wg_cv_4_0(float (&d)[128], uint32_t a0, uint32_t a1, uint32_t a2, uint32_t a3, uint32_t db) {
  asm volatile("{\n.reg .pred p;\n.reg .b64 t;\nsetp.ne.b32 p, 0, 0;\nmov.b64 t, {%20, 8};\n"
    "wgmma.mma_async.sync.aligned.m64n32k16.f32.bf16.bf16 {%0,%1,%2,%3,%4,%5,%6,%7,%8,%9,%10,%11,%12,%13,%14,%15}, {%16,%17,%18,%19}, t, p, 1, 1, 0;\n}\n"
    : "+f"(d[64]),"+f"(d[65]),"+f"(d[66]),"+f"(d[67]),"+f"(d[68]),"+f"(d[69]),"+f"(d[70]),"+f"(d[71]),"+f"(d[72]),"+f"(d[73]),"+f"(d[74]),"+f"(d[75]),"+f"(d[76]),"+f"(d[77]),"+f"(d[78]),"+f"(d[79]) : "r"(a0), "r"(a1), "r"(a2), "r"(a3), "r"(db));
}
__device__ __forceinline__ void wg_cv_4_1(float (&d)[128], uint32_t a0, uint32_t a1, uint32_t a2, uint32_t a3, uint32_t db) {
  asm volatile("{\n.reg .pred p;\n.reg .b64 t;\nsetp.ne.b32 p, 1, 0;\nmov.b64 t, {%20, 8};\n"
    "wgmma.mma_async.sync.aligned.m64n32k16.f32.bf16.bf16 {%0,%1,%2,%3,%4,%5,%6,%7,%8,%9,%10,%11,%12,%13,%14,%15}, {%16,%17,%18,%19}, t, p, 1, 1, 0;\n}\n"
    : "+f"(d[64]),"+f"(d[65]),"+f"(d[66]),"+f"(d[67]),"+f"(d[68]),"+f"(d[69]),"+f"(d[70]),"+f"(d[71]),"+f"(d[72]),"+f"(d[73]),"+f"(d[74]),"+f"(d[75]),"+f"(d[76]),"+f"(d[77]),"+f"(d[78]),"+f"(d[79]) : "r"(a0), "r"(a1), "r"(a2), "r"(a3), "r"(db));
}
__device__ __forceinline__ void wg_cv_5_0(float (&d)[128], uint32_t a0, uint32_t a1, uint32_t a2, uint32_t a3, uint32_t db) {
  asm volatile("{\n.reg .pred p;\n.reg .b64 t;\nsetp.ne.b32 p, 0, 0;\nmov.b64 t, {%20, 8};\n"
    "wgmma.mma_async.sync.aligned.m64n32k16.f32.bf16.bf16 {%0,%1,%2,%3,%4,%5,%6,%7,%8,%9,%10,%11,%12,%13,%14,%15}, {%16,%17,%18,%19}, t, p, 1, 1, 0;\n}\n"
    : "+f"(d[80]),"+f"(d[81]),"+f"(d[82]),"+f"(d[83]),"+f"(d[84]),"+f"(d[85]),"+f"(d[86]),"+f"(d[87]),"+f"(d[88]),"+f"(d[89]),"+f"(d[90]),"+f"(d[91]),"+f"(d[92]),"+f"(d[93]),"+f"(d[94]),"+f"(d[95]) : "r"(a0), "r"(a1), "r"(a2), "r"(a3), "r"(db));
}
__device__ __forceinline__ void wg_cv_5_1(float (&d)[128], uint32_t a0, uint32_t a1, uint32_t a2, uint32_t a3, uint32_t db) {
  asm volatile("{\n.reg .pred p;\n.reg .b64 t;\nsetp.ne.b32 p, 1, 0;\nmov.b64 t, {%20, 8};\n"
    "wgmma.mma_async.sync.aligned.m64n32k16.f32.bf16.bf16 {%0,%1,%2,%3,%4,%5,%6,%7,%8,%9,%10,%11,%12,%13,%14,%15}, {%16,%17,%18,%19}, t, p, 1, 1, 0;\n}\n"
    : "+f"(d[80]),"+f"(d[81]),"+f"(d[82]),"+f"(d[83]),"+f"(d[84]),"+f"(d[85]),"+f"(d[86]),"+f"(d[87]),"+f"(d[88]),"+f"(d[89]),"+f"(d[90]),"+f"(d[91]),"+f"(d[92]),"+f"(d[93]),"+f"(d[94]),"+f"(d[95]) : "r"(a0), "r"(a1), "r"(a2), "r"(a3), "r"(db));
}
__device__ __forceinline__ void wg_cv_6_0(float (&d)[128], uint32_t a0, uint32_t a1, uint32_t a2, uint32_t a3, uint32_t db) {
  asm volatile("{\n.reg .pred p;\n.reg .b64 t;\nsetp.ne.b32 p, 0, 0;\nmov.b64 t, {%20, 8};\n"
    "wgmma.mma_async.sync.aligned.m64n32k16.f32.bf16.bf16 {%0,%1,%2,%3,%4,%5,%6,%7,%8,%9,%10,%11,%12,%13,%14,%15}, {%16,%17,%18,%19}, t, p, 1, 1, 0;\n}\n"
    : "+f"(d[96]),"+f"(d[97]),"+f"(d[98]),"+f"(d[99]),"+f"(d[100]),"+f"(d[101]),"+f"(d[102]),"+f"(d[103]),"+f"(d[104]),"+f"(d[105]),"+f"(d[106]),"+f"(d[107]),"+f"(d[108]),"+f"(d[109]),"+f"(d[110]),"+f"(d[111]) : "r"(a0), "r"(a1), "r"(a2), "r"(a3), "r"(db));
}
__device__ __forceinline__ void wg_cv_6_1(float (&d)[128], uint32_t a0, uint32_t a1, uint32_t a2, uint32_t a3, uint32_t db) {
  asm volatile("{\n.reg .pred p;\n.reg .b64 t;\nsetp.ne.b32 p, 1, 0;\nmov.b64 t, {%20, 8};\n"
    "wgmma.mma_async.sync.aligned.m64n32k16.f32.bf16.bf16 {%0,%1,%2,%3,%4,%5,%6,%7,%8,%9,%10,%11,%12,%13,%14,%15}, {%16,%17,%18,%19}, t, p, 1, 1, 0;\n}\n"
    : "+f"(d[96]),"+f"(d[97]),"+f"(d[98]),"+f"(d[99]),"+f"(d[100]),"+f"(d[101]),"+f"(d[102]),"+f"(d[103]),"+f"(d[104]),"+f"(d[105]),"+f"(d[106]),"+f"(d[107]),"+f"(d[108]),"+f"(d[109]),"+f"(d[110]),"+f"(d[111]) : "r"(a0), "r"(a1), "r"(a2), "r"(a3), "r"(db));
}
__device__ __forceinline__ void wg_cv_7_0(float (&d)[128], uint32_t a0, uint32_t a1, uint32_t a2, uint32_t a3, uint32_t db) {
  asm volatile("{\n.reg .pred p;\n.reg .b64 t;\nsetp.ne.b32 p, 0, 0;\nmov.b64 t, {%20, 8};\n"
    "wgmma.mma_async.sync.aligned.m64n32k16.f32.bf16.bf16 {%0,%1,%2,%3,%4,%5,%6,%7,%8,%9,%10,%11,%12,%13,%14,%15}, {%16,%17,%18,%19}, t, p, 1, 1, 0;\n}\n"
    : "+f"(d[112]),"+f"(d[113]),"+f"(d[114]),"+f"(d[115]),"+f"(d[116]),"+f"(d[117]),"+f"(d[118]),"+f"(d[119]),"+f"(d[120]),"+f"(d[121]),"+f"(d[122]),"+f"(d[123]),"+f"(d[124]),"+f"(d[125]),"+f"(d[126]),"+f"(d[127]) : "r"(a0), "r"(a1), "r"(a2), "r"(a3), "r"(db));
}
__device__ __forceinline__ void wg_cv_7_1(float (&d)[128], uint32_t a0, uint32_t a1, uint32_t a2, uint32_t a3, uint32_t db) {
  asm volatile("{\n.reg .pred p;\n.reg .b64 t;\nsetp.ne.b32 p, 1, 0;\nmov.b64 t, {%20, 8};\n"
    "wgmma.mma_async.sync.aligned.m64n32k16.f32.bf16.bf16 {%0,%1,%2,%3,%4,%5,%6,%7,%8,%9,%10,%11,%12,%13,%14,%15}, {%16,%17,%18,%19}, t, p, 1, 1, 0;\n}\n"
    : "+f"(d[112]),"+f"(d[113]),"+f"(d[114]),"+f"(d[115]),"+f"(d[116]),"+f"(d[117]),"+f"(d[118]),"+f"(d[119]),"+f"(d[120]),"+f"(d[121]),"+f"(d[122]),"+f"(d[123]),"+f"(d[124]),"+f"(d[125]),"+f"(d[126]),"+f"(d[127]) : "r"(a0), "r"(a1), "r"(a2), "r"(a3), "r"(db));
}
template <class F, class T> __device__ __forceinline__ void conv_chain_1(float (&d)[128], uint32_t (&a)[64], uint32_t db, uint32_t ao, uint32_t ab, F hand, T dead) {
  wg_cv_7_0(d, a[60], a[61], a[62], a[63], db + 0);
  wg_cv_6_0(d, a[52], a[53], a[54], a[55], db + 0);
  dead();
  wg_cv_7_1(d, a[56], a[57], a[58], a[59], db + 16);
  wg_cv_5_0(d, a[44], a[45], a[46], a[47], db + 0);
  wg_cv_6_1(d, a[48], a[49], a[50], a[51], db + 16);
  wg_cv_7_1(d, a[52], a[53], a[54], a[55], db + 32);
  wg_cv_5_1(d, a[40], a[41], a[42], a[43], db + 16);
  wg_cv_6_1(d, a[44], a[45], a[46], a[47], db + 32);
  wg_cv_7_1(d, a[48], a[49], a[50], a[51], db + 48);
  wg_cv_6_1(d, a[40], a[41], a[42], a[43], db + 48);
  wg_cv_7_1(d, a[44], a[45], a[46], a[47], db + 64);
  wg_cv_7_1(d, a[40], a[41], a[42], a[43], db + 80);
  wg_commit();
  wg_cv_7_1(d, a[36], a[37], a[38], a[39], db + 96);
  wg_cv_6_1(d, a[36], a[37], a[38], a[39], db + 64);
  wg_cv_5_1(d, a[36], a[37], a[38], a[39], db + 32);
  wg_cv_4_0(d, a[36], a[37], a[38], a[39], db + 0);
  wg_commit(); wg_wait<1>();
  wg_cv_7_1(d, a[32], a[33], a[34], a[35], db + 112);
  wg_cv_6_1(d, a[32], a[33], a[34], a[35], db + 80);
  wg_cv_5_1(d, a[32], a[33], a[34], a[35], db + 48);
  a[60] = lds32(ab + (3840));
  a[61] = lds32(ab + (3968));
  a[62] = lds32(ab + (3824));
  a[63] = lds32(ab + (3952));
  wg_cv_4_1(d, a[32], a[33], a[34], a[35], db + 16);
  wg_cv_7_1(d, a[28], a[29], a[30], a[31], db + 128);
  wg_cv_6_1(d, a[28], a[29], a[30], a[31], db + 96);
  wg_cv_5_1(d, a[28], a[29], a[30], a[31], db + 64);
  a[56] = lds32(ab + (3584));
  a[57] = lds32(ab + (3712));
  a[58] = lds32(ab + (3568));
  a[59] = lds32(ab + (3696));
  wg_cv_4_1(d, a[28], a[29], a[30], a[31], db + 32);
  wg_cv_3_0(d, a[28], a[29], a[30], a[31], db + 0);
  wg_cv_7_1(d, a[24], a[25], a[26], a[27], db + 144);
  wg_cv_6_1(d, a[24], a[25], a[26], a[27], db + 112);
  a[52] = lds32(ab + (3328));
  a[53] = lds32(ab + (3456));
  a[54] = lds32(ab + (3312));
  a[55] = lds32(ab + (3440));
  wg_cv_5_1(d, a[24], a[25], a[26], a[27], db + 80);
  wg_cv_4_1(d, a[24], a[25], a[26], a[27], db + 48);
  wg_cv_3_1(d, a[24], a[25], a[26], a[27], db + 16);
  wg_commit();
  wg_cv_7_1(d, a[20], a[21], a[22], a[23], db + 160);
  wg_cv_6_1(d, a[20], a[21], a[22], a[23], db + 128);
  wg_cv_5_1(d, a[20], a[21], a[22], a[23], db + 96);
  wg_cv_4_1(d, a[20], a[21], a[22], a[23], db + 64);
  wg_commit(); wg_wait<1>();
  a[48] = lds32(ab + (3072));
  a[49] = lds32(ab + (3200));
  a[50] = lds32(ab + (3056));
  a[51] = lds32(ab + (3184));
  wg_cv_3_1(d, a[20], a[21], a[22], a[23], db + 32);
  wg_cv_2_0(d, a[20], a[21], a[22], a[23], db + 0);
  wg_cv_7_1(d, a[16], a[17], a[18], a[19], db + 176);
  wg_cv_6_1(d, a[16], a[17], a[18], a[19], db + 144);
  a[44] = lds32(ab + (2816));
  a[45] = lds32(ab + (2944));
  a[46] = lds32(ab + (2800));
  a[47] = lds32(ab + (2928));
  wg_cv_5_1(d, a[16], a[17], a[18], a[19], db + 112);
  wg_cv_4_1(d, a[16], a[17], a[18], a[19], db + 80);
  wg_cv_3_1(d, a[16], a[17], a[18], a[19], db + 48);
  wg_cv_2_1(d, a[16], a[17], a[18], a[19], db + 16);
  a[40] = lds32(ab + (2560));
  a[41] = lds32(ab + (2688));
  a[42] = lds32(ab + (2544));
  a[43] = lds32(ab + (2672));
  wg_cv_7_1(d, a[12], a[13], a[14], a[15], db + 192);
  wg_cv_6_1(d, a[12], a[13], a[14], a[15], db + 160);
  wg_cv_5_1(d, a[12], a[13], a[14], a[15], db + 128);
  wg_cv_4_1(d, a[12], a[13], a[14], a[15], db + 96);
  a[36] = lds32(ab + (2304));
  a[37] = lds32(ab + (2432));
  a[38] = lds32(ab + (2288));
  a[39] = lds32(ab + (2416));
  wg_cv_3_1(d, a[12], a[13], a[14], a[15], db + 64);
  wg_cv_2_1(d, a[12], a[13], a[14], a[15], db + 32);
  wg_cv_1_0(d, a[12], a[13], a[14], a[15], db + 0);
  wg_cv_7_1(d, a[8], a[9], a[10], a[11], db + 208);
  a[32] = lds32(ab + (2048));
  a[33] = lds32(ab + (2176));
  a[34] = lds32(ab + (2032));
  a[35] = lds32(ab + (2160));
  wg_cv_6_1(d, a[8], a[9], a[10], a[11], db + 176);
  wg_cv_5_1(d, a[8], a[9], a[10], a[11], db + 144);
  wg_cv_4_1(d, a[8], a[9], a[10], a[11], db + 112);
  wg_cv_3_1(d, a[8], a[9], a[10], a[11], db + 80);
  a[28] = lds32(ab + (1792));
  a[29] = lds32(ab + (1920));
  a[30] = lds32(ab + (1776));
  a[31] = lds32(ab + (1904));
  wg_cv_2_1(d, a[8], a[9], a[10], a[11], db + 48);
  wg_cv_1_1(d, a[8], a[9], a[10], a[11], db + 16);
  wg_commit();
  wg_cv_7_1(d, a[4], a[5], a[6], a[7], db + 224);
  wg_cv_6_1(d, a[4], a[5], a[6], a[7], db + 192);
  wg_cv_5_1(d, a[4], a[5], a[6], a[7], db + 160);
  wg_cv_4_1(d, a[4], a[5], a[6], a[7], db + 128);
  wg_commit(); wg_wait<1>();
  a[24] = lds32(ab + (1536));
  a[25] = lds32(ab + (1664));
  a[26] = lds32(ab + (1520));
  a[27] = lds32(ab + (1648));
  hand();
  wg_cv_3_1(d, a[4], a[5], a[6], a[7], db + 96);
  wg_cv_2_1(d, a[4], a[5], a[6], a[7], db + 64);
  wg_cv_1_1(d, a[4], a[5], a[6], a[7], db + 32);
  wg_cv_0_0(d, a[4], a[5], a[6], a[7], db + 0);
  a[20] = lds32(ab + (1280));
  a[21] = lds32(ab + (1408));
  a[22] = lds32(ab + (1264));
  a[23] = lds32(ab + (1392));
  wg_cv_7_1(d, a[0], a[1], a[2], a[3], db + 240);
  wg_cv_6_1(d, a[0], a[1], a[2], a[3], db + 208);
  wg_cv_5_1(d, a[0], a[1], a[2], a[3], db + 176);
  wg_cv_4_1(d, a[0], a[1], a[2], a[3], db + 144);
  a[16] = lds32(ab + (1024));
  a[17] = lds32(ab + (1152));
  a[18] = lds32(ab + (1008));
  a[19] = lds32(ab + (1136));
  wg_cv_3_1(d, a[0], a[1], a[2], a[3], db + 112);
  wg_cv_2_1(d, a[0], a[1], a[2], a[3], db + 80);
  wg_cv_1_1(d, a[0], a[1], a[2], a[3], db + 48);
  wg_cv_0_1(d, a[0], a[1], a[2], a[3], db + 16);
  wg_commit();
  a[12] = lds32(ab + (768));
  a[13] = lds32(ab + (896));
  a[14] = lds32(ab + (752));
  a[15] = lds32(ab + (880));
  a[8] = lds32(ab + (512));
  a[9] = lds32(ab + (640));
  a[10] = lds32(ab + (496));
  a[11] = lds32(ab + (624));
}
template <class F, class T> __device__ __forceinline__ void conv_chain_0(float (&d)[128], uint32_t (&a)[64], uint32_t db, uint32_t ao, uint32_t ab, F hand, T dead) {
  wg_cv_7_0(d, a[60], a[61], a[62], a[63], db + 0);
  wg_cv_6_0(d, a[52], a[53], a[54], a[55], db + 0);
  dead();
  wg_cv_7_1(d, a[56], a[57], a[58], a[59], db + 16);
  wg_cv_5_0(d, a[44], a[45], a[46], a[47], db + 0);
  wg_cv_6_1(d, a[48], a[49], a[50], a[51], db + 16);
  wg_cv_7_1(d, a[52], a[53], a[54], a[55], db + 32);
  wg_cv_5_1(d, a[40], a[41], a[42], a[43], db + 16);
  wg_cv_6_1(d, a[44], a[45], a[46], a[47], db + 32);
  wg_cv_7_1(d, a[48], a[49], a[50], a[51], db + 48);
  wg_cv_6_1(d, a[40], a[41], a[42], a[43], db + 48);
  wg_cv_7_1(d, a[44], a[45], a[46], a[47], db + 64);
  wg_cv_7_1(d, a[40], a[41], a[42], a[43], db + 80);
  wg_commit();
  wg_cv_7_1(d, a[36], a[37], a[38], a[39], db + 96);
  wg_cv_6_1(d, a[36], a[37], a[38], a[39], db + 64);
  wg_cv_5_1(d, a[36], a[37], a[38], a[39], db + 32);
  wg_cv_4_0(d, a[36], a[37], a[38], a[39], db + 0);
  wg_cv_7_1(d, a[32], a[33], a[34], a[35], db + 112);
  wg_cv_6_1(d, a[32], a[33], a[34], a[35], db + 80);
  wg_cv_5_1(d, a[32], a[33], a[34], a[35], db + 48);
  wg_cv_4_1(d, a[32], a[33], a[34], a[35], db + 16);
  wg_cv_7_1(d, a[28], a[29], a[30], a[31], db + 128);
  wg_cv_6_1(d, a[28], a[29], a[30], a[31], db + 96);
  wg_cv_5_1(d, a[28], a[29], a[30], a[31], db + 64);
  wg_cv_4_1(d, a[28], a[29], a[30], a[31], db + 32);
  wg_cv_3_0(d, a[28], a[29], a[30], a[31], db + 0);
  wg_cv_7_1(d, a[24], a[25], a[26], a[27], db + 144);
  wg_cv_6_1(d, a[24], a[25], a[26], a[27], db + 112);
  wg_cv_5_1(d, a[24], a[25], a[26], a[27], db + 80);
  wg_cv_4_1(d, a[24], a[25], a[26], a[27], db + 48);
  wg_cv_3_1(d, a[24], a[25], a[26], a[27], db + 16);
  wg_commit();
  wg_cv_7_1(d, a[20], a[21], a[22], a[23], db + 160);
  wg_cv_6_1(d, a[20], a[21], a[22], a[23], db + 128);
  wg_cv_5_1(d, a[20], a[21], a[22], a[23], db + 96);
  wg_cv_4_1(d, a[20], a[21], a[22], a[23], db + 64);
  wg_cv_3_1(d, a[20], a[21], a[22], a[23], db + 32);
  wg_cv_2_0(d, a[20], a[21], a[22], a[23], db + 0);
  wg_cv_7_1(d, a[16], a[17], a[18], a[19], db + 176);
  wg_cv_6_1(d, a[16], a[17], a[18], a[19], db + 144);
  wg_cv_5_1(d, a[16], a[17], a[18], a[19], db + 112);
  wg_cv_4_1(d, a[16], a[17], a[18], a[19], db + 80);
  wg_cv_3_1(d, a[16], a[17], a[18], a[19], db + 48);
  wg_cv_2_1(d, a[16], a[17], a[18], a[19], db + 16);
  wg_cv_7_1(d, a[12], a[13], a[14], a[15], db + 192);
  wg_cv_6_1(d, a[12], a[13], a[14], a[15], db + 160);
  wg_cv_5_1(d, a[12], a[13], a[14], a[15], db + 128);
  wg_cv_4_1(d, a[12], a[13], a[14], a[15], db + 96);
  wg_cv_3_1(d, a[12], a[13], a[14], a[15], db + 64);
  wg_cv_2_1(d, a[12], a[13], a[14], a[15], db + 32);
  wg_cv_1_0(d, a[12], a[13], a[14], a[15], db + 0);
  wg_cv_7_1(d, a[8], a[9], a[10], a[11], db + 208);
  wg_cv_6_1(d, a[8], a[9], a[10], a[11], db + 176);
  wg_cv_5_1(d, a[8], a[9], a[10], a[11], db + 144);
  wg_cv_4_1(d, a[8], a[9], a[10], a[11], db + 112);
  wg_cv_3_1(d, a[8], a[9], a[10], a[11], db + 80);
  wg_cv_2_1(d, a[8], a[9], a[10], a[11], db + 48);
  wg_cv_1_1(d, a[8], a[9], a[10], a[11], db + 16);
  wg_commit();
  wg_cv_7_1(d, a[4], a[5], a[6], a[7], db + 224);
  wg_cv_6_1(d, a[4], a[5], a[6], a[7], db + 192);
  wg_cv_5_1(d, a[4], a[5], a[6], a[7], db + 160);
  wg_cv_4_1(d, a[4], a[5], a[6], a[7], db + 128);
  hand();
  wg_cv_3_1(d, a[4], a[5], a[6], a[7], db + 96);
  wg_cv_2_1(d, a[4], a[5], a[6], a[7], db + 64);
  wg_cv_1_1(d, a[4], a[5], a[6], a[7], db + 32);
  wg_cv_0_0(d, a[4], a[5], a[6], a[7], db + 0);
  wg_cv_7_1(d, a[0], a[1], a[2], a[3], db + 240);
  wg_cv_6_1(d, a[0], a[1], a[2], a[3], db + 208);
  wg_cv_5_1(d, a[0], a[1], a[2], a[3], db + 176);
  wg_cv_4_1(d, a[0], a[1], a[2], a[3], db + 144);
  wg_cv_3_1(d, a[0], a[1], a[2], a[3], db + 112);
  wg_cv_2_1(d, a[0], a[1], a[2], a[3], db + 80);
  wg_cv_1_1(d, a[0], a[1], a[2], a[3], db + 48);
  wg_cv_0_1(d, a[0], a[1], a[2], a[3], db + 16);
  wg_commit();
}
constexpr bool CV_OWN = false;
constexpr int CV_RELOADED = 2;

struct Params {
  const __nv_bfloat16 *q, *k, *v, *shift_k, *ssm_k, *ssm_D, *w1, *b1, *w2, *b2;
  __nv_bfloat16* out;
};
struct Maps { CUtensorMap q0, qa, w1, w1x, k, v, hs, hx, ha, w2, w2x, kvs, qf, y, out; };

__global__ void __cluster_dims__(2, 1, 1) __launch_bounds__(384, 1) h3_kernel(const __grid_constant__ Maps M, const Params P) {
  extern __shared__ __align__(1024) uint8_t smem_raw[];
  constexpr uint32_t sc = 1024;
  const int tid = threadIdx.x, lane = tid & 31;
  if (tid == 0) { prefetch_map(&M.q0); prefetch_map(&M.w1); prefetch_map(&M.w1x); }
  const int warp = __shfl_sync(0xffffffffu, tid >> 5, 0);
  const uint32_t sb = __shfl_sync(0xffffffffu, s32(smem_raw), 0);
  const int b = blockIdx.x, pr = b >> 1;
  const int t7q = ((pr - 36) * 37) >> 8;
  const int G = pr < 4 ? 0 : (pr < 36 ? (pr - 4) & 7 : pr - 35 - 7 * t7q), gi = pr < 4 ? 4 + pr : (pr < 36 ? (pr - 4) >> 3 : 4 + t7q);
  const int kh = b & 1, nt = (G & 1) * 2 + (gi & 1), rb = (G >> 1) * 4 + (gi >> 1);
  const int dir = (G ^ (G >> 1)) & 1, ri = (gi & 1) * 2 + kh, ci = (G >> 2) * 4 + (gi >> 1);
  const uint32_t gmap = (nt & 1) ? 0x03412u : 0x43210u;
  const int j = kh * 4 + nt;
  const uint32_t bar = sb + M_BAR;
  auto BAR = [&](int i) { return bar + 8 * i; };
  auto g1_load = [&](int kc) {
    const uint32_t st = sb + (kc & 3) * G1_STAGE, fb = BAR(B_F1 + (kc & 3));
    const int k0 = dir ? 640 - kc * 64 : kc * 64;
    mbar_expect(fb, G1_TX);
    tma2d(st, &M.qa, k0, rb * 128, fb);
    tma3d(st + 16384, &M.w1, 0, k0, 3 * j, fb);
    tma2d(st + 40960, &M.w1x, 1536 + 24 * j, k0, fb);
  };
  auto kv_load = [&](int r, int hf) {
    const uint32_t st = sb + KVS + (r < 3 ? r : r - 3) * KV_BUF, fb = BAR((hf ? B_KIN1 : B_KIN) + r);
    mbar_expect(fb, KV_BUF / 2);
    tma2d(st + 4096 + hf * 2432, &M.k, 128 * r + 64 * (b & 1), 32 * (b >> 1) + 16 * hf - 3, fb);
    tma2d(st + hf * 2048, &M.v, 128 * r + 64 * (b & 1), 32 * (b >> 1) + 16 * hf, fb);
  };
  auto conv_sum = [&](int c, int ck, bool third, uint32_t ep) {
    const uint32_t ra = sb + cv_p(c) + ck * 16;
    __nv_bfloat16* yp = g_yT + (size_t)(128 * c + b) * SL + ck * 8;
    uint4 p[2][4];
    auto ld = [&](int u) {
#pragma unroll
      for (int w = 0; w < 4; w++) p[u & 1][w] = lds128((u == 0 && ck < 2 * w) ? sb + M_ZERO : ra + u * 512 + w * (4096 - 32));
    };
    auto st = [&](int u) {
      auto sum = [&](uint32_t a0, uint32_t a1, uint32_t a2, uint32_t a3) { return badd2(badd2(badd2(a3, a2), a1), a0); };
      const uint4* r = p[u & 1];
      const uint32_t m = ~ck & 1u;
      stg128(yp + u * 256, (sum(r[0].x, r[1].x, r[2].x, r[3].x) & ~m) | (ep & m), sum(r[0].y, r[1].y, r[2].y, r[3].y), sum(r[0].z, r[1].z, r[2].z, r[3].z), sum(r[0].w, r[1].w, r[2].w, r[3].w));
    };
    ld(0); ld(1); st(0);
    if (third) ld(2);
    st(1);
    if (third) st(2);
  };
  if (warp == 8) {
    if (lane == 0) {
      TS(0);
      mbar_init(BAR(B_F0), 1); mbar_init(BAR(B_F1), 1);
    }
    __syncwarp();
    ONE(mbar_expect(BAR(B_F0), G1_TX - 8192);
        tma2d(sb, &M.q0, 0, rb * 128, BAR(B_F0));
        tma3d(sb + 16384, &M.w1, 0, 0, 3 * j, BAR(B_F0));
        tma2d(sb + 40960, &M.w1x, 1536 + 24 * j, 0, BAR(B_F0));
        mbar_expect(BAR(B_F1), 8192);
        tma2d(sb + 8192, &M.q0, 0, rb * 128 + 64, BAR(B_F1));
        for (int s = 1; s < 4; s++) mbar_init(BAR(B_F1 + s), 1));
    bar_arrive(NB_INIT, 384);
  } else if (warp == 9) ONE(prefetch_map(&M.qa));
  if ((sb & 0xFFFFFFu) != sc) { if (warp == 8) { mbar_wait(BAR(B_F0), 0); mbar_wait(BAR(B_F1), 0); } return; }

  if (warp >= 8) {
    asm volatile("setmaxnreg.dec.sync.aligned.u32 " REG_AUX ";");
    auto table = [&](int c, int aw) {
      const uint32_t kb = sb + cv_t(c);
      const uint32_t dd = lds32(sb + M_AUX + aw * 32 + c * 4);
      if (lane < 2) sts128(kb + lane * (KT_E - 16), 0u, 0u, 0u, 0u);
      uint4 r[8];
#pragma unroll
      for (int it = 0; it < 8; it++) r[it] = lds128(kb + KT_E + (it * 32 + lane) * 16);
      if (lane == 0) { r[0].x = __byte_perm(badd2(r[0].x, dd), r[0].x, 0x7610); sts32(kb + KT_E, r[0].x); }
#pragma unroll
      for (int it = 0; it < 8; it++) {
        const uint32_t pv = __shfl_sync(0xffffffffu, lane == 31 ? (it ? r[it ? it - 1 : 0].w : 0u) : r[it].w, lane - 1);
        sts128(kb + KT_O + (it * 32 + lane) * 16, __byte_perm(pv, r[it].x, 0x5432), __byte_perm(r[it].x, r[it].y, 0x5432),
               __byte_perm(r[it].y, r[it].z, 0x5432), __byte_perm(r[it].z, r[it].w, 0x5432));
      }
      __syncwarp();
      if (lane == 0) mbar_arrive(BAR(B_KT + c));
    };
    if (warp == 8) {
      ONE(g1_load(1); g1_load(2); g1_load(3));
      bar_sync(NB_INIT2, 128);
#pragma unroll
      for (int kc = 3; kc < 10; kc++) {
        if (kc > 3) mbar_wait(BAR(B_E1 + (kc & 3)), (kc >> 3) & 1);
        ONE(if (kc > 3) g1_load(kc);
            for (int r = 0; r < 3; r++) if (kc == ((KV_MAP >> (4 * r)) & 15)) { kv_load(r, 0); kv_load(r, 1); }
            for (int c = 0; c < 5; c++) if (kc == ((PF_RAW >> (4 * c)) & 15)) prefetch_l2(P.ssm_k + (size_t)(128 * c + b) * SL, 4096));
      }
      ONE(prefetch_map(&M.hs); prefetch_map(&M.hx); prefetch_map(&M.ha); prefetch_map(&M.w2); prefetch_map(&M.w2x));
      bar_sync(NB_INIT3, 64);
      const unsigned ep = lds32(sb + M_AUX + 20);
      const int hc = j * 192, hx = 1536 + j * 24;
#pragma unroll 1
      for (int n = 0; n < 32; n += 4) {
        const int i = (H_ORD >> n) & 7, hw = i >> 2, blk = i & 3;
        if (n == 4 * W2_PF) ONE(prefetch_l2(P.w2 + (size_t)b * (FF * DM / NCTA), FF * DM / NCTA * 2));
        mbar_wait(BAR(B_HB + i), 0);
        fence_async_smem();
        asm volatile("cp.async.bulk.wait_group %0;" ::"n"(H_FLY - 1) : "memory");
        ONE(tma2d_st(blk < 3 ? &M.hs : &M.hx, blk < 3 ? hc + blk * 64 : hx, rb * 128 + hw * 64, sb + hw * HST + blk * 8192); bulk_commit());
      }
      const int cf = (nt * 160 + (nt & 1) * 32) >> 6, ch = (nt >> 1) * 320 + 128;
      auto g2_k = [&](int kc) { return (kc < NSH ? kh * NSH + kc : NSH + kc) * 64; };
      auto g2_load_b = [&](int kc) {
        const int s = kc & 3;
        const uint32_t fb = BAR(B_F2 + s);
        mbar_expect(fb, kc >= NSH ? 8192 + 24576 : 16384 + 24576);
        tma3d(sb + g2_b(s), &M.w2, 0, g2_k(kc), cf, fb);
        tma2d(sb + g2_b(s) + 16384, &M.w2x, ch, g2_k(kc), fb);
      };
      auto g2_load_a = [&](int kc) {
        const int s = kc & 3, o = kc >= NSH ? kh : 0;
        tma2d(sb + g2_a(s) + o * 8192, kc >= NSH ? &M.hs : &M.ha, g2_k(kc), rb * 128 + o * 64, BAR(B_F2 + s));
      };
      bulk_wait_all();
      ONE(g2_load_b(0); g2_load_b(1));
      fence_release();
      ONE(signal_cnt(CNT_H + rb); TS(37));
      wait_cnt(CNT_H + rb, 8 * ep);
      ONE(TS(39); g2_load_a(0); g2_load_a(1); prefetch_map(&M.qf); prefetch_map(&M.y); prefetch_map(&M.out));
      mbar_wait(BAR(B_KD), 0);
      ONE(g2_load_b(3));
      mbar_wait(BAR(B_TD + 1), 0);
      fence_async_smem();
      ONE(g2_load_b(2); g2_load_a(2));
      mbar_wait(BAR(B_SD + 3), 0);
      ONE(mbar_expect(BAR(B_FINQ), 20480);
          for (int i = 0; i < 5; i++) tma2d(sb + FIN_Q + i * 4096, &M.qf, nt * 160 + ((gmap >> (4 * i)) & 7) * 32, rb * 128 + kh * 64, BAR(B_FINQ)));
      mbar_wait(BAR(B_RF + 2), 0);
      ONE(g2_load_a(3); TS(38));
#pragma unroll 1
      for (int kc = 4; kc < NST; kc++) {
        mbar_wait(BAR(B_E2 + (kc & 3)), ((kc >> 2) - 1) & 1);
                ONE(g2_load_a(kc); g2_load_b(kc); if (kc >= Y_KC && kc < Y_KC + 3) mbar_arrive(BAR(B_YSLOT + kc - Y_KC)));
      }
      if (lane == 0) g_launch[b * 8] = ep;
#pragma unroll 1
      for (int i = 0; i < 5; i++) {
        const int gi = (gmap >> (4 * i)) & 7;
        mbar_wait(BAR(B_OUT + i), 0);
        fence_async_smem();
        ONE(tma2d_st(&M.out, nt * 160 + gi * 32, rb * 128 + kh * 64, sb + FIN_Q + i * 4096));
      }
      ONE(bulk_commit());
      bulk_wait_read();
    } else {
      const int aw = warp - 9, at = tid - 288;
      if (aw == 0) {
        if (lane == 0) {
#pragma unroll
          for (int s = 0; s < 4; s++) { mbar_init(BAR(B_E1 + s), 8); mbar_init(BAR(B_FR + s), 8); mbar_init(BAR(B_F2 + s), 1); mbar_init(BAR(B_E2 + s), 8); }
          mbar_init(BAR(B_KRAW), 1); mbar_init(BAR(B_KRAW + 1), 1);
          mbar_init(BAR(B_LNI), 4); mbar_init(BAR(B_RED), 8); mbar_init(BAR(B_BX), 1);
        }
      } else if (aw == 1) {
        if (lane == 0) {
#pragma unroll
          for (int c = 0; c < 5; c++) { if (c == 0) { mbar_init(BAR(B_SK), 1); mbar_init(BAR(B_KD), 2); } mbar_init(BAR(B_XL + c), 1); mbar_init(BAR(B_KT + c), 1); mbar_init(BAR(B_XF + c), 1); mbar_init(BAR(B_SD + c), 4); }
        }
      } else if (lane == 0) {
#pragma unroll
        for (int i = 0; i < 8; i++) mbar_init(BAR(B_HB + i), 4);
#pragma unroll
        for (int c = 0; c < 3; c++) mbar_init(BAR(B_RF + c), 3);
        for (int r = 0; r < 5; r++) { mbar_init(BAR(B_KIN + r), 1); mbar_init(BAR(B_KIN1 + r), 1); }
        for (int i = 0; i < 3; i++) { mbar_init(BAR(B_YSLOT + i), 1); mbar_init(BAR(B_YL + i), 1); } mbar_init(BAR(B_XR), 1);
        for (int i = 0; i < 5; i++) mbar_init(BAR(B_OUT + i), 4);
        mbar_init(BAR(B_XD), 1); mbar_expect(BAR(B_XD), XD_N * 2048); mbar_init(BAR(B_XD + 1), 1); mbar_expect(BAR(B_XD + 1), (XD_M - XD_N) * 2048);
        mbar_init(BAR(B_XD + 2), 1); mbar_expect(BAR(B_XD + 2), (10 - XD_M) * 2048);
        asm volatile("fence.mbarrier_init.release.cluster;" ::: "memory");
        mbar_init(BAR(B_TD + 1), 8); mbar_init(BAR(B_FINQ), 1); mbar_init(BAR(B_FINY), 3);
      }
      __syncwarp();
      bar_arrive(NB_INIT, 384);
      if (aw == 1) ONE(prefetch_map(&M.k); prefetch_map(&M.v); mbar_expect(BAR(B_SK), 2560);
                       for (int r = 0; r < 5; r++) bulk_g2s(sb + M_SK + r * 512, P.shift_k + (128 * r + 64 * (b & 1)) * 4, 512, BAR(B_SK)));
      const uint32_t dv0 = ld_relaxed32(lane < 5 ? static_cast<const void*>(P.ssm_D + 128 * lane + (b & ~1)) : &g_launch[b * 8]);
      const uint32_t b2v = ldg32(reinterpret_cast<const uint32_t*>(P.b2 + nt * 160) + ((gmap >> (4 * (min(at, 79) >> 4))) & 7) * 16 + (at & 15));
      const int l27 = min(lane, 26), col = l27 < 24 ? 192 * j + 8 * l27 : 1536 + 24 * j + 8 * (l27 - 24);
      uint4 bb;
      if (aw == 2) bb = ldg128(P.b1 + col);
      bar_sync(NB_INIT2, 128);
      if (aw == 0) ONE(prefetch_map(&M.kvs));
      if (lane < 4) sts32(sb + M_ZERO + lane * 4, 0u);
      if (lane < 8) sts32(sb + M_AUX + aw * 32 + lane * 4, lane >= 5 ? dv0 + 1 : ((b & 1) ? dv0 >> 16 : dv0 & 0xFFFFu));
      if (at < 80) sts64f(sb + M_B2 + at * 8, 0.5f * bf_lo(b2v), 0.5f * bf_hi(b2v));
      __syncwarp();
      if (aw == 0) bar_arrive(NB_INIT3, 64);
      if (aw == 2) {
        const unsigned ep = lds32(sb + M_AUX + 64 + 20);
        const uint32_t ba = sb + M_BX + (l27 >> 2) * 512 + ((l27 & 3) << 4);
        mbar_wait(BAR(B_RED), 0);
        const uint32_t tg = ep & 15u;
        auto tagged = [&](float v) { return (__float_as_uint(v) & ~15u) | tg; };
        float c0 = 0.f, c1 = 0.f, s1 = 0.f, s2 = 0.f;
#pragma unroll
        for (int i = 0; i < 16; i += 2) { c0 += __uint_as_float(lds32(sb + M_RED1 + i * 128 + lane * 4)); c1 += __uint_as_float(lds32(sb + M_RED1 + i * 128 + 128 + lane * 4)); }
        st_relaxed32(&g_cs[(dir * 8 + j) * 256 + ci * 32 + lane], tagged(c0 + c1));
        float2 u[8];
#pragma unroll
        for (int i = 0; i < 8; i++) u[i] = lds64f(sb + M_RED0 + (lane & 15) * 128 + ((i + lane) & 7) * 16 + (lane >> 4) * 8);
        const float c = bf_round(u[0].x * (1.f / 40)), cc = 40.f * c * c;
#pragma unroll
        for (int i = 0; i < 8; i++) { s1 += fmaf(-40.f, c, u[i].x); s2 += fmaf(-2.f * c, u[i].x, u[i].y) + cc; }
        const float dm = s1 * (1.f / 320);
        st_relaxed64(&g_stat[dir * SL + rb * 128 + ri * 32 + lane], tagged(c + dm), tagged(fmaf(-dm, s1, s2)));
        __syncwarp();
        if (lane == 0) TS(30);
        sts128((ba + 128) ^ 16, 0u, 0u, 0u, 0u); sts128((ba + 192) ^ 16, bb.x, bb.y, bb.z, bb.w);
#pragma unroll
        for (int i = 4; i < 8; i++) sts128((ba + i * 64) ^ ((i >> 1) << 4), 0u, 0u, 0u, 0u);
        mbar_wait(BAR(B_FR), 0);
        auto raw_load = [&]() {
          ONE(mbar_expect(BAR(B_KRAW), 4096); mbar_expect(BAR(B_KRAW + 1), 4 * 4096);
              for (int c = 0; c < 5; c++) bulk_g2s(sb + cv_t(c) + KT_E, P.ssm_k + (size_t)(128 * c + b) * SL, 4096, BAR(B_KRAW + (c >= 1))));
        };
        uint32_t x[32], n = 0;
#pragma unroll 1
        while (true) {
#pragma unroll
          for (int i = 0; i < 8; i++) {
            const uint4 v = ld_relaxed128(i < 4 ? static_cast<const void*>(g_cs + ((i >> 1) * 8 + j) * 256 + l27 * 8 + (i & 1) * 4)
                                                : g_stat + ((i >> 1) & 1) * SL + rb * 128 + lane * 4 + (i & 1) * 2);
            x[4 * i] = v.x; x[4 * i + 1] = v.y; x[4 * i + 2] = v.z; x[4 * i + 3] = v.w;
          }
          if (!RAW_LATE && n == 0) raw_load();
          uint32_t bad = 0;
#pragma unroll
          for (int i = 0; i < 32; i++) { x[i] ^= tg; bad |= x[i]; }
          if (__all_sync(0xffffffffu, (bad & 15u) == 0) || spin_guard(n, 0x131)) break;
        }
        if (RAW_LATE) raw_load();
        uint32_t st[4];
#pragma unroll
        for (int i = 0; i < 4; i++) {
          const float ma = __uint_as_float(x[16 + 2 * i]), mb = __uint_as_float(x[24 + 2 * i]), dl = ma - mb;
          const float m2 = fmaf(dl * dl, 160.f, __uint_as_float(x[17 + 2 * i]) + __uint_as_float(x[25 + 2 * i]));
          const float vb = bf_round(fmaxf(m2, 0.f) * (1.f / DM));
          st[i] = pack_bf16(0.5f * (ma + mb), sqrt_fast(bf_round(vb + 1e-5f)));
        }
        sts128(sb + M_STAT + lane * 16, st[0], st[1], st[2], st[3]);
        uint32_t hi[4], lo[4];
#pragma unroll
        for (int i = 0; i < 4; i++) {
          const float x0 = __uint_as_float(x[2 * i]) + __uint_as_float(x[8 + 2 * i]), x1 = __uint_as_float(x[2 * i + 1]) + __uint_as_float(x[9 + 2 * i]);
          hi[i] = pack_bf16(x0, x1); lo[i] = pack_bf16(x0 - bf_lo(hi[i]), x1 - bf_hi(hi[i]));
        }
        sts128(ba, hi[0], hi[1], hi[2], hi[3]); sts128(ba + 64, lo[0], lo[1], lo[2], lo[3]);
        fence_async_smem();
        __syncwarp();
        ONE(mbar_arrive(BAR(B_BX)); TS(54));
      }
      if (aw < 2) {
        auto done = [&](int r) {
          bulk_wait_read();
          ONE(kv_load(r + 3, aw); TSKV);
        };
        const uint32_t par = lds32(sb + M_AUX + aw * 32 + 20) & 1u;
        bool pend = false;
        mbar_wait(BAR(B_SK), 0);
#pragma unroll 1
        for (int r = 0; r < 5; r++) {
          const int c0 = 128 * r + 64 * (b & 1);
          const uint32_t buf = sb + KVS + (r < 3 ? r : r - 3) * KV_BUF, stg = buf + aw * 2048, vb = stg + lane * 4, kb = buf + 4096 + aw * 2432 + lane * 4;
          const uint4 sk = lds128(sb + M_SK + r * 512 + lane * 16);
          const uint32_t w0 = __byte_perm(sk.x, sk.z, 0x5410), w1 = __byte_perm(sk.x, sk.z, 0x7632);
          const uint32_t w2 = __byte_perm(sk.y, sk.w, 0x5410), w3 = __byte_perm(sk.y, sk.w, 0x7632);
          mbar_wait(BAR((aw ? B_KIN1 : B_KIN) + r), 0);
          if (at == 0 && r == 0) TS(56);
          uint32_t kk[19], o[16];
#pragma unroll
          for (int i = 0; i < 19; i++) { kk[i] = lds32(kb + i * 128); if (i >= 3) o[i - 3] = lds32(vb + (i - 3) * 128); }
#pragma unroll
          for (int i = 0; i < 16; i++) o[i] = bmul2(bfma2(kk[i + 3], w0, bfma2(kk[i + 2], w1, bfma2(kk[i + 1], w2, bmul2(kk[i], w3)))), o[i]);
          __syncwarp();
          const uint32_t a0 = stg + lane * 64 + ((lane & 6) << 3);
          const uint32_t s0 = (lane & 4) ? 0x7632 : 0x5410, s1 = s0 ^ 0x2222;
#pragma unroll
          for (int hh = 0; hh < 2; hh++) {
            const uint32_t* u = o + 8 * hh;
            const uint32_t a = a0 ^ (hh << 4);
            auto nz = [&](uint32_t x) { return hh ? x : (x & ~1u) | par; };
            sts128(a, nz(__byte_perm(u[1], u[0], s0)), __byte_perm(u[3], u[2], s0), __byte_perm(u[5], u[4], s0), __byte_perm(u[7], u[6], s0));
            sts128(a ^ 32, nz(__byte_perm(u[1], u[0], s1)), __byte_perm(u[3], u[2], s1), __byte_perm(u[5], u[4], s1), __byte_perm(u[7], u[6], s1));
          }
          if (pend) done(r - 1);
          fence_async_smem();
          __syncwarp();
          ONE(tma2d_st(&M.kvs, 32 * (b >> 1) + 16 * aw, c0, stg); bulk_commit());
          pend = r < 2 && mbar_test(BAR((aw ? B_KIN1 : B_KIN) + r + 1), 0);
          if (!pend && r < 2) done(r);
        }
      }
      const unsigned ep = lds32(sb + M_AUX + aw * 32 + 20);
      auto x_load = [&](int c) { mbar_expect(BAR(B_XL + c), 4096); bulk_g2s(sb + cv_x(c) + XD, g_kvT + (size_t)(128 * c + b) * SL, 4096, BAR(B_XL + c)); };
      auto x_pad = [&](int c0, int c1) {
        if (lane < 17) for (int c = c0; c < c1; c++) sts128(sb + cv_x(c) + lane * 16, 0u, 0u, 0u, 0u);
        fence_async_smem();
        __syncwarp();
      };
      if (aw == 2) {
        mbar_wait(BAR(B_FR + 1), 0);
        ONE(for (int c = 0; c < X_A; c++) x_load(c));
        x_pad(0, 4);
      }
#pragma unroll 1
      for (int c = 2 - aw; c < 5; c += 2) {
        mbar_wait(BAR(B_KRAW + (c > 0)), 0);
        if (lane == 0 && c == 2) TS(35);
        table(c, aw);
        if (lane == 0 && c == 2) TS(55);
        if (c == 0) break;
        if (c < 3) { bulk_wait_read(); ONE(mbar_arrive(BAR(B_KD)); if (aw == 0) TS(34)); }
      }
      if (aw == 2) {
#pragma unroll 1
        for (int c = 0, n = 0; c < 5;) {
          mbar_wait(BAR(B_XL + c), n & 1);
          const uint32_t a = sb + cv_x(c) + XD + lane * 32;
          const uint32_t v = ((lds32(a) ^ ep) | (lds32(a + 1024) ^ ep) | (lds32(a + 2048) ^ ep) | (lds32(a + 3072) ^ ep)) & 1u;
          int nx = c;
          if (__all_sync(0xffffffffu, v == 0) || n > 100000) {
            ONE(mbar_arrive(BAR(B_XF + c)); if (c == 0) TS(36); if (c >= 3) TS(28 + c));
            nx = c + X_A; c++; n = 0;
            if (nx == 4) { mbar_wait(BAR(B_KD), 0); x_pad(4, 5); }
          } else {
            n++;
            if (lane == 0) TS(33);
          }
          if (nx < 5) ONE(x_load(nx));
        }
      }
      if (RED_GATE) mbar_wait(BAR(RED_GATE == 1 ? B_TD + 1 : B_SD + RED_GATE - 1), 0);
#pragma unroll 1
      for (int c = 0; c < 5; c++) {
        mbar_wait(BAR(B_SD + c), 0);
        conv_sum(c, aw * 96 + lane, aw < 2, ep);
        __syncwarp();
        if (c < 3 && lane == 0) mbar_arrive(BAR(B_RF + c));
        if (at == 0) TS(59 + c);
      }
      bar_sync(NB_AUX, 96);
      if (aw == 0) ONE(mbar_arrive_remote(mapa(BAR(B_XR), kh ^ 1)); TS(3));
      auto ytab = [](int a) { return (uint32_t)(fin_y(3 * a) >> 10 | fin_y(3 * a + 1) >> 10 << 8 | fin_y(3 * a + 2) >> 10 << 16 | fin_y(a == 2 ? 9 : 3 * a) >> 10 << 24); };
      const uint32_t yt = aw == 0 ? ytab(0) : (aw == 1 ? ytab(1) : ytab(2));
      mbar_wait(BAR(B_YSLOT + aw), 0);
#pragma unroll 1
      for (int n = 0;; n++) {
        ONE(mbar_expect(BAR(B_YL + aw), aw == 2 ? 8192 : 6144));
#pragma unroll 1
        for (int i = 0; i < (aw == 2 ? 4 : 3); i++) {
          const int np = 3 * aw + i;
          ONE(tma2d(sb + (((yt >> (8 * i)) & 255) << 10), &M.y, rb * 128 + kh * 64, nt * 160 + ((gmap >> (4 * (np >> 1))) & 7) * 32 + (np & 1) * 16, BAR(B_YL + aw)));
        }
        mbar_wait(BAR(B_YL + aw), n & 1);
        uint32_t bad = 0;
#pragma unroll
        for (int i = 0; i < 4; i++) {
          const uint32_t a = sb + (((yt >> (8 * i)) & 255) << 10) + (lane >> 2) * 128 + ((((lane & 3) * 2) ^ (lane >> 2)) << 4);
          bad |= (lds32(a) ^ ep) | (lds32(a + 1024) ^ ep);
        }
        if (__all_sync(0xffffffffu, (bad & 1u) == 0) || n > 100000) break;
        if (lane == 0) TS(33);
      }
      ONE(mbar_arrive(BAR(B_FINY)); if (aw == 2) TS(40));
    }
  } else {
    if (INC_KC < 0) asm volatile("setmaxnreg.inc.sync.aligned.u32 " REG_CON ";");
    const int wg = warp >> 2, w = warp & 3, g = lane >> 2, q = lane & 3;
    constexpr bool elect = false;
    uint32_t ca[64];
    const uint32_t ab0 = sb + ((g & 1) ? KT_E : KT_O) + (8 * w + 4 + (g >> 1) - q) * 4;
    auto conv_lda = [&](int c, int k0, int k1) {
      const uint32_t ab = ab0 + cv_t(c);
#pragma unroll
      for (int ks = 15; ks >= 0; ks--) {
        if (ks >= k0 && ks < k1) {
          ca[4 * ks + 0] = lds32(ab + ks * 256);
          ca[4 * ks + 1] = lds32(ab + ks * 256 + 128);
          ca[4 * ks + 2] = lds32(ab + ks * 256 - 16);
          ca[4 * ks + 3] = lds32(ab + ks * 256 + 112);
        }
      }
    };
    {
      float d[108];
      bool stag = false;
      auto g1_release = [&](int kc) { if (lane == 0) mbar_arrive(BAR(kc < 6 ? B_E1 + (kc & 3) : B_FR + kc - 6)); };
      auto g1_wait = [&](int kc) { mbar_wait(BAR(B_F1 + (kc & 3)), (kc >> 2) & 1); };
      auto g1_issue = [&](int kc) {
        const int s = kc & 3;
        if (kc == 0) { if (wg == 1) { mbar_wait(BAR(B_F1), 0); bar_sync(NB_LEAD, 256); } mbar_wait(BAR(B_F0), 0); }
        if (tid == 0) TS(8 + kc);
        const uint32_t st = sc + s * G1_STAGE;
        const uint64_t da = mkdesc(st + wg * 8192, 16, 1024, 1), db = mkdesc(st + 16384, 8192, 1024, 1);
        wg_fence();
#pragma unroll
        for (int k = 0; k < 4; k++) {
          wg_ss_216(d, da + k * 2, db + k * 128, (kc | k) != 0);
          if (k == REL_K || k == 3) wg_commit();
          if (k == REL_K && kc > 0) { wg_wait<1>(); if (kc != STAG_KC + 1 || !stag) g1_release(kc - 1); }
        }
        if (kc == 0 && wg == 0) bar_arrive(NB_LEAD, 256);
      };
      const int t7 = tid & 127, wr = ((t7 >> 3) & 1) * 4 + (t7 >> 4) * 8, wc = 4 * min(ci, 6) + ((t7 >> 1) & 3);
      const uint32_t sa0 = sb + (wg ? 16384 + (wc >> 3) * 8192 + wr * 128 + (((wc ^ wr) & 7) << 4) + (t7 & 1) * 8 : ri * 4096 + t7 * 16);
      float t1 = 0.f, t2 = 0.f, t3 = 0.f, t4 = 0.f;
      auto piece = [&](int i) {
        const uint32_t so = (i & 3) * G1_STAGE;
        if (wg == 0) {
          const uint4 x = lds128(sa0 + so), y = lds128(sa0 + so + 2048);
          const uint32_t xx[4] = {x.x, x.y, x.z, x.w}, yy[4] = {y.x, y.y, y.z, y.w};
#pragma unroll
          for (int e = 0; e < 4; e++) {
            const float u = bf_lo(xx[e]), v = bf_hi(xx[e]), r = bf_lo(yy[e]), z = bf_hi(yy[e]);
            t1 += u; t2 = fmaf(u, u, t2); t3 += r; t4 = fmaf(r, r, t4);
            t1 += v; t2 = fmaf(v, v, t2); t3 += z; t4 = fmaf(z, z, t4);
          }
        } else {
          float2 xx[4];
#pragma unroll
          for (int e = 0; e < 4; e++) xx[e] = lds64f((sa0 ^ (e * 144)) + so);
#pragma unroll
          for (int e = 0; e < 4; e++) {
            const uint32_t u = __float_as_uint(xx[e].x), v = __float_as_uint(xx[e].y);
            t1 += bf_lo(u); t2 += bf_hi(u); t3 += bf_lo(v); t4 += bf_hi(v);
          }
        }
      };
      bar_sync(NB_INIT, 384);
#pragma unroll
      for (int kc = 0; kc < 10; kc++) {
        g1_issue(kc);
        if (kc < 5 && (kc || !dir)) { g1_wait(kc); piece(kc); }
        if (kc == 4) {
          if (dir) { g1_wait(5); piece(5); }
          sts128(sb + (wg ? M_RED1 : M_RED0) + t7 * 16, __float_as_uint(t1), __float_as_uint(t2), __float_as_uint(t3), __float_as_uint(t4));
          __syncwarp();
          if (lane == 0) mbar_arrive(BAR(B_RED));
        }
        if (kc == INC_KC) asm volatile("setmaxnreg.inc.sync.aligned.u32 " REG_CON ";");
        if (kc < 9) g1_wait(kc + 1);
        if (kc == STAG_KC && wg == 1 && (STAG_ALL || mbar_test(BAR(B_BX), 0))) {
          if (STAG_REL) { wg_wait<0>(); g1_release(kc); stag = true; }
          mbar_wait(BAR(B_LNI), 0);
        }
      }
      uint2 s0, s1;
      {
        mbar_wait(BAR(B_BX), 0);
        s0.x = lds32(sb + M_STAT + (wg * 64 + w * 16 + g) * 4); s1.x = lds32(sb + M_STAT + (wg * 64 + w * 16 + g + 8) * 4);
        if (tid == 0) TS(46);
        const uint32_t f0 = q == 0 ? ((s0.x & 0xFFFFu) * 0x10001u) ^ 0x80008000u : (q == 1 ? s0.x ^ 0x8000u : 0u);
        const uint32_t f1 = q == 0 ? ((s1.x & 0xFFFFu) * 0x10001u) ^ 0x80008000u : (q == 1 ? s1.x ^ 0x8000u : 0u);
        wg_fence();
        wg_rs_216(d, f0, f1, 0u, 0u, mkdesc(sc + M_BX, 512, 0, 2));
        wg_commit();
        if (wg == 0 && lane == 0) mbar_arrive(BAR(B_LNI));
      }
      wg_wait<1>();
      if (lane == 0) mbar_arrive(BAR(B_FR + 3));
      const float r0 = rcp_fast(bf_hi(s0.x)), r1 = rcp_fast(bf_hi(s1.x));
      constexpr float C1 = 0.7978845608028654f, C2 = 0.7978845608028654f * 0.044715f;
      const float ga0 = C1 * r0, gb0 = C2 * r0 * r0 * r0, ga1 = C1 * r1, gb1 = C2 * r1 * r1 * r1;
      if (wg == 0) mbar_wait(BAR(B_FR + 2), 0);
      wg_wait<0>();
      if (elect) TS(1 + 47 * wg);
      if (wg == 1) bar_sync(NB_GELU, 256);
      sched_fence(sb);
      const int mi = lane >> 3, row = w * 16 + (mi & 1) * 8 + (lane & 7);
      const uint32_t hs = sb + wg * HST;
      float u[2][8];
#pragma unroll
      for (int st = -1; st < 15; st++) {
        const int nb = 2 * (st - 1);
        if (st >= 1) {
          uint32_t p[4];
#pragma unroll
          for (int e = 0; e < (nb < 26 ? 4 : 2); e++) {
            const float x = d[4 * nb + 2 * e], y = d[4 * nb + 2 * e + 1];
            p[e] = pack_bf16(fmaf(x, u[(st - 1) & 1][2 * e], x), fmaf(y, u[(st - 1) & 1][2 * e + 1], y));
          }
          const int nbm = nb + (mi >> 1);
          if (nb < 24) stsm4(hs + (nb >> 3) * 8192 + row * 128 + (((nbm & 7) ^ (row & 7)) << 4), p[0], p[1], p[2], p[3]);
          else if (nb == 24) stsm4(hs + 24576 + row * 48 + (mi >> 1) * 16, p[0], p[1], p[2], p[3]);
          else stsm2(hs + 24576 + row * 48 + 32, p[0], p[1]);
          if ((nb & 7) == 6 || nb == 26) {
            __syncwarp();
            if (lane == 0) mbar_arrive(BAR(B_HB + wg * 4 + (nb >> 3)));
          }
        }
        if (st >= 0 && st < 14) {
#pragma unroll
          for (int i = 0; i < (st < 13 ? 8 : 4); i++) u[st & 1][i] = tanh_fast(u[st & 1][i]);
        }
        if (st + 1 < 14) {
#pragma unroll
          for (int i = 0; i < (st + 1 < 13 ? 8 : 4); i++) {
            const float x = d[8 * (st + 1) + i];
            u[(st + 1) & 1][i] = x * fmaf(x * ((i & 2) ? gb1 : gb0), x, (i & 2) ? ga1 : ga0);
          }
        }
        constexpr int S0 = A_NB0 / 2, NK = CV_OWN ? 16 - CV_RELOADED : 16;
        if (st >= S0 && st < 14) conv_lda(wg, 16 - (st + 1 - S0) * NK / (14 - S0), 16 - (st - S0) * NK / (14 - S0));
        if (2 * st == GELU_NB && wg == 0) bar_arrive(NB_GELU, 256);
        if (st + 1 == S0) mbar_wait(BAR(B_KT + wg), 0); else if (st < 14 && (st + 1) % SCH == 0) sched_fence(sb);
      }
      if (elect) TS(2 + 47 * wg);
    }
#pragma unroll 1
    for (int c = wg; c < 5; c += 2) {
      float d[128];
      mbar_wait(BAR(B_XF + c), 0);
      if (c < 3) mbar_wait(BAR(B_KT + c + 2), 0);
      const uint64_t db = mkdesc(sc + cv_x(c), 16, 128, 0);
      if (c > 0) { if (wg) bar_sync(NB_TURN + 1, 256); else bar_sync(NB_TURN, 256); }
      wg_fence();
      auto hand = [&]() { if (wg) bar_arrive(NB_TURN, 256); else if (c < 4 || !HAND4) bar_arrive(NB_TURN + 1, 256); };
      const uint32_t ao = ab0 + cv_t(c);
      if (c < 3) conv_chain_1(d, ca, db, ao, ao + 2 * KT_CH, hand, []() {});
      else conv_chain_0(d, ca, db, ao, 0, hand, [&]() { if (lane == 0) mbar_arrive(BAR(B_TD + 1)); });
      if (c == 4 && HAND4) bar_arrive(NB_TURN + 1, 256);
      mbar_wait(BAR(c >= 3 ? B_RF + c - 3 : B_FR + 3), 0);
      wg_wait<0>();
      if (elect) TS(41 + c);
      if (c < 3 && !CV_OWN) conv_lda(c + 2, 0, CV_RELOADED);
      const uint32_t wa = sb + cv_p(c) + w * 4096 + lane * 16;
#pragma unroll
      for (int n4 = 0; n4 < 32; n4 += 4) {
        uint32_t p[4];
#pragma unroll
        for (int e = 0; e < 4; e++) {
          const int nb = n4 + e;
          float x = d[4 * nb], y = d[4 * nb + 1];
          if (nb > 0) { x += d[4 * nb - 2]; y += d[4 * nb - 1]; }
          p[e] = pack_bf16(x, y);
        }
        stsm4t(wa + n4 * 128, p[0], p[1], p[2], p[3]);
      }
      __syncwarp();
      if (lane == 0) mbar_arrive(BAR(B_SD + c));
    }
    if (elect) TS(51 + wg);
    {
      float d[80];
      const uint32_t aoff = (wg ^ kh) * 8192;
      const uint64_t boff = (uint64_t)(nt & 1) << 51;
      const uint32_t s0 = lds32(sb + M_STAT + ((wg ^ kh) * 64 + w * 16 + g) * 4), s1 = lds32(sb + M_STAT + ((wg ^ kh) * 64 + w * 16 + g + 8) * 4);
      auto g2_release = [&](int kc) { if (lane == 0) mbar_arrive(BAR(B_E2 + (kc & 3))); };
      auto g2_mma_w = [&](int kc, int first, bool rel, auto side) {
        const int s = kc & 3;
        mbar_wait(BAR(B_F2 + s), (kc >> 2) & 1);
        const uint64_t da = mkdesc(sc + g2_a(s) + aoff, 16, 1024, 1), db = mkdesc(sc + g2_b(s), 8192, 1024, 1) | boff;
        wg_fence();
#pragma unroll
        for (int k = 0; k < 4; k++) {
          wg_ss_160(d, da + k * 2, db + k * 128, k ? 1 : first);
          if ((k == REL_K && rel) || k == 3) wg_commit();
          if (k == REL_K && rel) { wg_wait<1>(); g2_release(kc - 1); }
          side(k);
        }
      };
      auto g2_mma = [&](int kc, int first, bool rel) { g2_mma_w(kc, first, rel, [](int) {}); };
      sched_fence(sb);
      if (wg == 1) bar_sync(NB_TURN + 1, 256);
      g2_mma(0, 0, false);
      if (wg == 0) bar_arrive(NB_LEAD, 256);
#pragma unroll
      for (int kc = 1; kc < XP_KC; kc++) {
        if (tid == 0) TS(17 + kc);
        if (kc == LEAD_KC && wg == 1) bar_sync(NB_LEAD, 256);
        g2_mma(kc, 1, true);
      }
      if (wg == 1) {
        float bi[40];
#pragma unroll
        for (int nb = 0; nb < 20; nb++) { const float2 v = lds64f(sb + M_B2 + nb * 32 + q * 8); bi[2 * nb] = v.x; bi[2 * nb + 1] = v.y; }
        const float c0 = 0.25f * rcp_fast(bf_hi(s0)), c1 = 0.25f * rcp_fast(bf_hi(s1));
#pragma unroll
        for (int kc = XP_KC; kc < NSH; kc++) {
          g2_mma(kc, 1, kc < NST - 3);
          if (kc == END_KC) bar_arrive(NB_END, 256);
        }
        mbar_wait(BAR(B_XR), 0);
        wg_wait<0>();
#pragma unroll
        for (int kc = NSH - 1; kc < NST - 4; kc++) g2_release(kc);
        if (elect) TS(53);
        const uint32_t ra = mapa(sb, kh ^ 1), rbar = ra + M_BAR + 8 * B_XD, dst = ra + (tid & 127) * 16;
#pragma unroll
        for (int i = 0; i < 10; i++) {
          const float *dd = d + 8 * i, *bb = bi + 4 * i;
          st_async128(dst + (i < 5 ? P0 + i * 2048 : P1 + (i - 5) * 2048), pack_bf16(fmaf(dd[0], c0, bb[0]), fmaf(dd[1], c0, bb[1])), pack_bf16(fmaf(dd[2], c1, bb[0]), fmaf(dd[3], c1, bb[1])),
                      pack_bf16(fmaf(dd[4], c0, bb[2]), fmaf(dd[5], c0, bb[3])), pack_bf16(fmaf(dd[6], c1, bb[2]), fmaf(dd[7], c1, bb[3])), rbar + 8 * ((i >= XD_N) + (i >= XD_M)));
          sched_fence(sb);
        }
        if (elect) TS(7);
      } else {
        const int mi = lane >> 3, row = (mi & 1) * 8 + (lane & 7);
        const uint32_t qa = sb + FIN_Q + (w * 16 + row) * 64 + (((mi >> 1) ^ ((row >> 1) & 3)) << 4), qb = qa ^ 32;
        auto q_addr = [&](int np) { return ((np & 1) ? qb : qa) + (np >> 1) * 4096; };
        uint32_t sv[40], xq[40];
        const uint32_t m0 = (s0 & 0xFFFFu) * 0x10001u, m1 = (s1 & 0xFFFFu) * 0x10001u;
        float rs0 = rcp_fast(bf_hi(s0)), rs1 = rcp_fast(bf_hi(s1));
#pragma unroll
        for (int kc = XP_KC; kc < 10; kc++) {
          if (tid == 0) TS(17 + kc);
          g2_mma(kc, 1, true);
          if (kc >= XP_KC && XP_KC < 10) {
            mbar_wait(BAR(B_FINQ), 0);
#pragma unroll
            for (int np = 10 * (kc - XP_KC) / (XP_KC < 10 ? 10 - XP_KC : 1); np < 10 * (kc + 1 - XP_KC) / (XP_KC < 10 ? 10 - XP_KC : 1); np++) {
              ldsm4(q_addr(np), xq[4 * np], xq[4 * np + 1], xq[4 * np + 2], xq[4 * np + 3]);
#pragma unroll
              for (int e = 0; e < 4; e++) {
                const uint32_t dm = bsub2(xq[4 * np + e], (e & 1) ? m1 : m0);
                const float rs = (e & 1) ? rs1 : rs0;
                sv[4 * np + e] = pack_bf16(bf_lo(dm) * rs, bf_hi(dm) * rs);
              }
            }
          }
        }
        const uint32_t ya = sb + (mi >> 1) * 1024 + (lane & 7) * 128 + (((2 * w + (mi & 1)) ^ (lane & 7)) << 4);
        uint32_t y[3][4];
        auto y_step = [&](int i) {
          if (i < 0 || i >= 12) return;
          if (i >= 2) {
#pragma unroll
            for (int e = 0; e < 4; e++) asm volatile("mul.rn.bf16x2 %0, %0, %1;" : "+r"(sv[4 * (i - 2) + e]) : "r"(y[(i - 2) % 3][e]));
          }
          if (i < 10) ldsm4t(ya + fin_y(i), y[i % 3][0], y[i % 3][1], y[i % 3][2], y[i % 3][3]);
          if (YFENCE) sched_fence(sb);
        };
        rs0 *= 0.25f; rs1 *= 0.25f;
        if (tid == 0) TS(27);
#pragma unroll
        for (int kc = 9; kc < NST; kc++) {
          if (kc == YP_KC) mbar_wait(BAR(B_FINY), 0);
          if (kc > 9) g2_mma_w(kc, 1, kc < NST - 3 && kc != HOLD_KC + 1, [&](int k) { y_step(4 * (kc - YP_KC) + k); });
          if (kc == HOLD_KC) {
            if (kc < NST - 4) { wg_wait<0>(); g2_release(kc); }
            if (tid == 0) TS(28);
            bar_sync(NB_END, 256);
          }
        }
        if (tid == 0) TS(29);
        if (tid == 0) TS(47);
        mbar_wait(BAR(B_XD), 0);
        if (tid == 0) TS(5);
        uint4 v[10];
        auto ld_v = [&](int n0, int n1) {
#pragma unroll
          for (int i = n0; i < n1; i++) v[i] = lds128(sb + tid * 16 + (i < 5 ? P0 + i * 2048 : P1 + (i - 5) * 2048));
        };
        ld_v(0, XD_N);
        wg_wait<0>();
        if (tid == 0) TS(4);
        float t[2][8];
#pragma unroll
        for (int st = -1; st < 11; st++) {
          if (st == XD_N - 3) { mbar_wait(BAR(B_XD + 1), 0); ld_v(XD_N, XD_M); }
          if (st == XD_M - 3) { mbar_wait(BAR(B_XD + 2), 0); ld_v(XD_M, 10); }
          if (st >= 1) {
            const int np = st - 1;
            uint32_t o[4];
#pragma unroll
            for (int e = 0; e < 4; e++) {
              const float h0 = d[8 * np + 2 * e], h1 = d[8 * np + 2 * e + 1];
              o[e] = bfma2(sv[4 * np + e], pack_bf16(fmaf(h0, t[np & 1][2 * e], h0), fmaf(h1, t[np & 1][2 * e + 1], h1)), xq[4 * np + e]);
            }
            stsm4(q_addr(np), o[0], o[1], o[2], o[3]);
            if (np & 1) {
              if (np == 9 && tid == 0) TS(50);
              __syncwarp();
              if (lane == 0) mbar_arrive(BAR(B_OUT + (np >> 1)));
            }
          }
          if (st >= 0 && st < 10) {
#pragma unroll
            for (int i = 0; i < 8; i++) t[st & 1][i] = tanh_fast(d[8 * st + i]);
          }
          if (st + 1 < 10) {
            const int np = st + 1;
            const uint32_t pw[4] = {v[np].x, v[np].y, v[np].z, v[np].w};
#pragma unroll
            for (int e = 0; e < 4; e++) {
              d[8 * np + 2 * e] = fmaf(d[8 * np + 2 * e], (e & 1) ? rs1 : rs0, bf_lo(pw[e]));
              d[8 * np + 2 * e + 1] = fmaf(d[8 * np + 2 * e + 1], (e & 1) ? rs1 : rs0, bf_hi(pw[e]));
            }
          }
          if (SCH2 && (st + 1) % (SCH2 ? SCH2 : 1) == 0) sched_fence(sb);
        }
      }
    }
  }
}

typedef CUresult (*EncFn)(CUtensorMap*, CUtensorMapDataType, cuuint32_t, void*, const cuuint64_t*, const cuuint64_t*, const cuuint32_t*, const cuuint32_t*,
                          CUtensorMapInterleave, CUtensorMapSwizzle, CUtensorMapL2promotion, CUtensorMapFloatOOBfill);

static void make_map(EncFn enc, CUtensorMap* tm, const void* ptr, int cols, int rows, int bc, int br, int grp, CUtensorMapSwizzle sw,
                     CUtensorMapL2promotion promo = CU_TENSOR_MAP_L2_PROMOTION_NONE) {
  cuuint64_t gd[3] = {(cuuint64_t)(grp ? bc : cols), (cuuint64_t)rows, (cuuint64_t)(cols / bc)};
  cuuint64_t gs[2] = {(cuuint64_t)cols * 2, (cuuint64_t)bc * 2};
  cuuint32_t bd[3] = {(cuuint32_t)bc, (cuuint32_t)br, (cuuint32_t)grp};
  cuuint32_t es[3] = {1, 1, 1};
  CUresult r = enc(tm, CU_TENSOR_MAP_DATA_TYPE_BFLOAT16, grp ? 3 : 2, const_cast<void*>(ptr), gd, gs, bd, es, CU_TENSOR_MAP_INTERLEAVE_NONE, sw,
                   promo, CU_TENSOR_MAP_FLOAT_OOB_FILL_NONE);
  (void)r;
}

}

extern "C" void kernel_launch(void* const* d_in, const int* in_sizes, int n_in, void* d_out, int out_size) {
  using namespace h3;
  (void)in_sizes; (void)n_in; (void)out_size;
  static EncFn enc = nullptr;
  static void *p_h = nullptr, *p_yT = nullptr, *p_kvT = nullptr;
  if (!enc) {
    void* fn = nullptr; cudaDriverEntryPointQueryResult qr;
    cudaGetDriverEntryPoint("cuTensorMapEncodeTiled", &fn, cudaEnableDefault, &qr);
    enc = (EncFn)fn;
    cudaGetSymbolAddress(&p_h, g_h);
    cudaGetSymbolAddress(&p_yT, g_yT);
    cudaGetSymbolAddress(&p_kvT, g_kvT);
    cudaFuncSetAttribute(h3_kernel, cudaFuncAttributeMaxDynamicSharedMemorySize, SMEM_BYTES);
  }
  Params P;
  P.q = (const __nv_bfloat16*)d_in[0]; P.k = (const __nv_bfloat16*)d_in[1]; P.v = (const __nv_bfloat16*)d_in[2];
  P.shift_k = (const __nv_bfloat16*)d_in[3]; P.ssm_k = (const __nv_bfloat16*)d_in[4]; P.ssm_D = (const __nv_bfloat16*)d_in[5];
  P.out = (__nv_bfloat16*)d_out;
  P.w1 = (const __nv_bfloat16*)d_in[7]; P.b1 = (const __nv_bfloat16*)d_in[8]; P.w2 = (const __nv_bfloat16*)d_in[9]; P.b2 = (const __nv_bfloat16*)d_in[10];
  const CUtensorMapSwizzle S128 = CU_TENSOR_MAP_SWIZZLE_128B, S64 = CU_TENSOR_MAP_SWIZZLE_64B, S0 = CU_TENSOR_MAP_SWIZZLE_NONE;
  Maps M;
  make_map(enc, &M.q0, P.q, DM, SL, 64, 64, 0, S128);
  make_map(enc, &M.qa, P.q, DM, SL, 64, 128, 0, S128);
  make_map(enc, &M.w1, P.w1, FF, DM, 64, 64, 3, S128);
  make_map(enc, &M.w1x, P.w1, FF, DM, 24, 64, 0, S128, WS_PROMO);
  make_map(enc, &M.k, P.k, DM, SL, 64, 19, 0, S0);
  make_map(enc, &M.v, P.v, DM, SL, 64, 16, 0, S0);
  make_map(enc, &M.hs, p_h, FF, SL, 64, 64, 0, S128);
  make_map(enc, &M.hx, p_h, FF, SL, 24, 64, 0, S0);
  make_map(enc, &M.ha, p_h, FF, SL, 64, 128, 0, S128);
  make_map(enc, &M.w2, P.w2, DM, FF, 64, 64, 2, S128);
  make_map(enc, &M.w2x, P.w2, DM, FF, 64, 64, 0, S128);
  make_map(enc, &M.kvs, p_kvT, SL, DM, 16, 64, 0, CU_TENSOR_MAP_SWIZZLE_32B);
  make_map(enc, &M.qf, P.q, DM, SL, 32, 64, 0, S64);
  make_map(enc, &M.y, p_yT, SL, DM, 64, 16, 0, S128);
  make_map(enc, &M.out, d_out, DM, SL, 32, 64, 0, S64);
  h3_kernel<<<NCTA, 384, SMEM_BYTES>>>(M, P);
}
```

```cpp
#include <cuda_runtime.h>
#include <cuda_bf16.h>
#include <cuda.h>
#include <stdint.h>

namespace h3 {

constexpr int SL = 2048, DM = 640, FF = 1728;
constexpr int NCTA = 128;

__device__ __align__(1024) __nv_bfloat16 g_h[SL * FF];
__device__ __align__(1024) __nv_bfloat16 g_kvT[DM * SL];
__device__ __align__(1024) __nv_bfloat16 g_yT[DM * SL];
__device__ __align__(1024) uint2 g_stat[2 * SL];
__device__ __align__(1024) uint32_t g_cs[2 * 8 * 256];
__device__ __align__(1024) unsigned g_cnt[64 * 32];
__device__ __align__(1024) unsigned g_launch[NCTA * 8];
#define RETRY(i)
constexpr int CNT_H = 0;

constexpr int G1_STAGE = 49152, G1_TX = 16384 + 24576 + 3072;
constexpr int HST = 49152;
constexpr int P0 = 81920, P1 = 140288, P2 = 156672;
constexpr int XCH = 4368, XD = 272, X0 = 173056, X4 = 221184;
constexpr int KVS = 196608, KV_BUF = 8960;
constexpr int KT_CH = 8240, KT_O = 16, KT_E = 4144, KT0 = 98304;
constexpr int FIN_Q = X0;
constexpr int MISC = 226816;
constexpr int M_BX = MISC;
constexpr int M_RED0 = M_BX + 2048, M_RED1 = M_BX;
constexpr int M_SK = KVS + 3 * KV_BUF;
constexpr int M_STAT = M_BX + 3584;
constexpr int M_B2 = MISC - 640;
constexpr int M_AUX = M_STAT + 512;
constexpr int M_ZERO = M_AUX + 96;
constexpr int M_BAR = M_ZERO + 16;
constexpr int M_TS = M_BAR + 94 * 8;
constexpr int SMEM_BYTES = M_TS + 256;
__host__ __device__ constexpr int fin_y(int np) {
  return np < 3 ? P0 + 10240 + np * 2048 : (np < 6 ? P1 + 10240 + (np - 3) * 2048 : (np == 6 ? FIN_Q + 20480 : (np < 9 ? X4 + (np - 7) * 2048 : M_BX + 512)));
}
static_assert(fin_y(9) % 1024 == 0 && fin_y(6) % 1024 == 0 && fin_y(6) + 2048 <= KVS && fin_y(7) % 1024 == 0, "smem");
__host__ __device__ constexpr int cv_x(int c) { return c == 4 ? X4 : X0 + c * XCH; }
__host__ __device__ constexpr int cv_p(int c) { return c == 2 ? P2 : ((c == 0 || c == 3) ? P0 : P1); }
__host__ __device__ constexpr int cv_t(int c) { return KT0 + c * KT_CH; }
__host__ __device__ constexpr int g2_a(int s) { return s == 0 ? 0 : (s == 1 ? 40960 : (s == 2 ? 98304 : P2)); }
__host__ __device__ constexpr int g2_b(int s) { return s == 0 ? 16384 : (s == 1 ? 57344 : (s == 2 ? 114688 : KVS)); }
static_assert(M_SK + 2560 <= M_B2 && X4 + XCH <= M_B2 && KVS + 24576 <= X4 && X0 + 4 * XCH <= KVS && FIN_Q + 20480 <= KVS, "smem");
static_assert(KT0 + 5 * KT_CH <= P1 && P1 + 16384 <= P2 && P2 + 16384 <= X0 && SMEM_BYTES <= 232448 && MISC % 512 == 0 && M_BAR % 8 == 0, "smem");
constexpr int B_F1 = 0, B_E1 = 4, B_FR = 8, B_F2 = 12, B_E2 = 16, B_KRAW = 20, B_KT = 22, B_XF = 27, B_HB = 32, B_SD = 40, B_RF = 45,
              B_TD = 48, B_FINQ = 50, B_FINY = 51, B_RED = 52, B_BX = 53, B_KIN = 54, B_XR = 59, B_OUT = 61, B_SK = 66, B_YSLOT = 80, B_YL = 83, B_XD = 86, B_F0 = 89, B_LNI = 90, B_RED1 = 91, B_RD = 92, B_KIN1 = 70, B_XL = 75, B_KD = 60;
constexpr int NB_INIT = 1, NB_INIT2 = 2, NB_AUX = 3, NB_LEAD = 4, NB_GELU = 5, NB_TURN = 6  , NB_END = 8, NB_INIT3 = 9, NB_WG1 = 10;

#define STAG_KC 8
#define STAG_ALL 1
#define STAG_REL 0
#define COM 2
#define PEEK 0
#define INC_KC 6
#define KV_MAP 0x764
#define KV_LATE 1
#define PF_KV 0
#define PF_G1 0
#define WS_PROMO CU_TENSOR_MAP_L2_PROMOTION_L2_128B
#define RAW_LATE 0
#define PF_RAW 0x00007
#define SIDE_LD 4
#define SIDE_USE 0x554
#define REL_K 0
#define CS_WAIT 1
#define GELU_NB 8
#define H_ORD 0x73625410
#define W2_PF 7
#define H_FLY 8
#define TB_MAP 0x01040532u
#define KRAW_N 2
#define XT1 (B_FR + 3)
#define XT2 (B_HB + 1)
#define XT3 (B_HB + 3)
#define XT4 (B_HB + 7)
#define X_TRIG ((XT1) | (XT2) << 8 | (XT3) << 16 | (XT4) << 24)
#define FENCE_KIND 1
#define SCH2 0
#define SCH 1
#define A_NB0 14
#define HAND4 1
#define LEAD_KC 1
#define RED_GATE 3
#define XP_KC 4
#define NSH 12
#define NST (27 - NSH)
#define YP_KC 12
#define YFENCE 1
#define Y_KC 9
#define XD_N 6
#define XD_M 8
#define HOLD_KC 11
#define END_KC (NSH - 1)
#define REG_AUX "56"
#define REG_CON "224"
#define LDQ ".nc.L1::no_allocate"
#define LDP ""

__device__ __forceinline__ uint32_t s32(const void* p) { return (uint32_t)__cvta_generic_to_shared(p); }
__device__ __forceinline__ uint32_t clk() { uint32_t t; asm volatile("mov.u32 %0, %%clock;" : "=r"(t)); return t; }
__device__ __forceinline__ bool elect_one() {
  uint32_t p; asm volatile("{\n.reg .pred P;\nelect.sync _|P, 0xffffffff;\nselp.u32 %0, 1, 0, P;\n}" : "=r"(p)); return p;
}
#define ONE(...) do { if (elect_one()) { __VA_ARGS__; } __syncwarp(); } while (0)
__device__ __forceinline__ void mbar_init(uint32_t a, int c) { asm volatile("mbarrier.init.shared::cta.b64 [%0], %1;" ::"r"(a), "r"(c) : "memory"); }
__device__ __forceinline__ void mbar_expect(uint32_t a, int b) { asm volatile("mbarrier.arrive.expect_tx.shared::cta.b64 _, [%0], %1;" ::"r"(a), "r"(b) : "memory"); }
__device__ __forceinline__ void mbar_arrive(uint32_t a) { asm volatile("mbarrier.arrive.shared::cta.b64 _, [%0];" ::"r"(a) : "memory"); }
__device__ __forceinline__ bool spin_guard(uint32_t& n, uint32_t) {
  return ++n > (1u << 20);
}
__device__ __forceinline__ void mbar_wait(uint32_t a, int ph) {
  asm volatile("{\n.reg .pred p;\n.reg .u32 n;\nmov.u32 n, 0;\nW:\n.pragma \"nounroll\";\nmbarrier.try_wait.parity.shared::cta.b64 p, [%0], %1;\n"
               "add.u32 n, n, 1;\nsetp.ge.or.u32 p, n, 0x100000, p;\n@!p bra W;\n}" ::"r"(a), "r"(ph) : "memory");
}
__device__ __forceinline__ bool mbar_test(uint32_t a, int ph) {
  uint32_t ok;
  asm volatile("{\n.reg .pred p;\nmbarrier.test_wait.parity.shared::cta.b64 p, [%1], %2;\nselp.u32 %0, 1, 0, p;\n}" : "=r"(ok) : "r"(a), "r"(ph) : "memory");
  return __all_sync(0xffffffffu, ok);
}
__device__ __forceinline__ void sched_fence(uint32_t a) {
  asm volatile("{\n.reg .pred p;\nsetp.eq.u32 p, %0, 0;\n@p exit;\n}" ::"r"(a) : "memory");
}
__device__ __forceinline__ void tma2d(uint32_t dst, const CUtensorMap* tm, int c0, int c1, uint32_t bar) {
  asm volatile("cp.async.bulk.tensor.2d.shared::cluster.global.mbarrier::complete_tx::bytes [%0], [%1, {%3, %4}], [%2];"
               ::"r"(dst), "l"(tm), "r"(bar), "r"(c0), "r"(c1) : "memory");
}
__device__ __forceinline__ void tma3d(uint32_t dst, const CUtensorMap* tm, int c0, int c1, int c2, uint32_t bar) {
  asm volatile("cp.async.bulk.tensor.3d.shared::cluster.global.mbarrier::complete_tx::bytes [%0], [%1, {%3, %4, %5}], [%2];"
               ::"r"(dst), "l"(tm), "r"(bar), "r"(c0), "r"(c1), "r"(c2) : "memory");
}
__device__ __forceinline__ void tma2d_st(const CUtensorMap* tm, int c0, int c1, uint32_t src) {
  asm volatile("cp.async.bulk.tensor.2d.global.shared::cta.bulk_group [%0, {%2, %3}], [%1];" ::"l"(tm), "r"(src), "r"(c0), "r"(c1) : "memory");
}
__device__ __forceinline__ void tma3d_st(const CUtensorMap* tm, int c0, int c1, int c2, uint32_t src) {
  asm volatile("cp.async.bulk.tensor.3d.global.shared::cta.bulk_group [%0, {%2, %3, %4}], [%1];" ::"l"(tm), "r"(src), "r"(c0), "r"(c1), "r"(c2) : "memory");
}
__device__ __forceinline__ void bulk_g2s(uint32_t dst, const void* src, int bytes, uint32_t bar) {
  asm volatile("cp.async.bulk.shared::cluster.global.mbarrier::complete_tx::bytes [%0], [%1], %2, [%3];" ::"r"(dst), "l"(src), "r"(bytes), "r"(bar) : "memory");
}
__device__ __forceinline__ void bulk_commit() { asm volatile("cp.async.bulk.commit_group;" ::: "memory"); }
__device__ __forceinline__ void bulk_wait_read() { asm volatile("cp.async.bulk.wait_group.read 0;" ::: "memory"); }
__device__ __forceinline__ void bulk_wait_all() { asm volatile("cp.async.bulk.wait_group 0;" ::: "memory"); }
__device__ __forceinline__ void fence_async_smem() { asm volatile("fence.proxy.async.shared::cta;" ::: "memory"); }
__device__ __forceinline__ void fence_async_all() { asm volatile("fence.proxy.async;" ::: "memory"); }
__device__ __forceinline__ void fence_gpu() { asm volatile("fence.acq_rel.gpu;" ::: "memory"); }
#define bar_sync(id, n) asm volatile("bar.sync %0, %1;" ::"n"(id), "n"(n) : "memory")
#define bar_arrive(id, n) asm volatile("bar.arrive %0, %1;" ::"n"(id), "n"(n) : "memory")
__device__ __forceinline__ void wg_fence() { asm volatile("wgmma.fence.sync.aligned;" ::: "memory"); }
__device__ __forceinline__ void wg_commit() { asm volatile("wgmma.commit_group.sync.aligned;" ::: "memory"); }
template <int N> __device__ __forceinline__ void wg_wait() { asm volatile("wgmma.wait_group.sync.aligned %0;" ::"n"(N) : "memory"); }
__device__ __forceinline__ uint64_t mkdesc(uint32_t addr, uint32_t lbo, uint32_t sbo, int sw) {
  return (uint64_t)((addr & 0x3FFFF) >> 4) | ((uint64_t)(lbo >> 4) << 16) | ((uint64_t)(sbo >> 4) << 32) | ((uint64_t)sw << 62);
}
__device__ __forceinline__ uint32_t ldg32(const void* p) { uint32_t v; asm volatile("ld.global" LDQ ".b32 %0, [%1];" : "=r"(v) : "l"(p)); return v; }
template <int OFF> __device__ __forceinline__ uint32_t ldg32o(const void* p) { uint32_t v; asm volatile("ld.global" LDQ ".b32 %0, [%1+%2];" : "=r"(v) : "l"(p), "n"(OFF)); return v; }
template <int I> __device__ __forceinline__ void kv_loads(const void* kp, const void* vp, uint32_t (&kk)[16], uint32_t (&o)[16]) {
  kk[I] = ldg32o<I * DM * 2>(kp); o[I] = ldg32o<I * DM * 2>(vp);
  if constexpr (I < 15) kv_loads<I + 1>(kp, vp, kk, o);
}
__device__ __forceinline__ uint4 ldg128(const void* p) {
  uint4 v; asm volatile("ld.global" LDQ LDP ".v4.b32 {%0,%1,%2,%3}, [%4];" : "=r"(v.x), "=r"(v.y), "=r"(v.z), "=r"(v.w) : "l"(p)); return v;
}
__device__ __forceinline__ void stg128(void* p, uint32_t x, uint32_t y, uint32_t z, uint32_t w) {
  asm volatile("st.global.v4.b32 [%0], {%1,%2,%3,%4};" ::"l"(p), "r"(x), "r"(y), "r"(z), "r"(w) : "memory");
}
__device__ __forceinline__ uint4 ld_relaxed128(const void* p) {
  uint4 v; asm volatile("ld.relaxed.gpu.global.v4.b32 {%0,%1,%2,%3}, [%4];" : "=r"(v.x), "=r"(v.y), "=r"(v.z), "=r"(v.w) : "l"(p) : "memory"); return v;
}
__device__ __forceinline__ uint2 ld_relaxed64(const void* p) {
  uint2 v; asm volatile("ld.relaxed.gpu.global.v2.b32 {%0,%1}, [%2];" : "=r"(v.x), "=r"(v.y) : "l"(p) : "memory"); return v;
}
__device__ __forceinline__ uint4 ld_relaxed_b128(const void* p) {
  uint4 v; asm volatile("{\n.reg .b128 t;\nld.relaxed.gpu.global.b128 t, [%4];\nmov.b128 {%0,%1,%2,%3}, t;\n}" : "=r"(v.x), "=r"(v.y), "=r"(v.z), "=r"(v.w) : "l"(p) : "memory"); return v;
}
__device__ __forceinline__ void st_relaxed_b128(void* p, uint32_t x, uint32_t y, uint32_t z, uint32_t w) {
  asm volatile("{\n.reg .b128 t;\nmov.b128 t, {%1,%2,%3,%4};\nst.relaxed.gpu.global.b128 [%0], t;\n}" ::"l"(p), "r"(x), "r"(y), "r"(z), "r"(w) : "memory");
}
__device__ __forceinline__ void st_relaxed64(void* p, uint32_t x, uint32_t y) {
  asm volatile("{\n.reg .b64 t;\nmov.b64 t, {%1,%2};\nst.relaxed.gpu.global.b64 [%0], t;\n}" ::"l"(p), "r"(x), "r"(y) : "memory");
}
__device__ __forceinline__ void st_relaxed32(void* p, uint32_t x) { asm volatile("st.relaxed.gpu.global.b32 [%0], %1;" ::"l"(p), "r"(x) : "memory"); }
__device__ __forceinline__ uint32_t ld_relaxed32(const void* p) { uint32_t v; asm volatile("ld.relaxed.gpu.global.b32 %0, [%1];" : "=r"(v) : "l"(p) : "memory"); return v; }
__device__ __forceinline__ void st_relaxed128(void* p, uint32_t x, uint32_t y, uint32_t z, uint32_t w) {
  asm volatile("{\n.reg .b64 t, u;\nmov.b64 t, {%1,%2};\nmov.b64 u, {%3,%4};\nst.relaxed.gpu.global.v2.b64 [%0], {t, u};\n}" ::"l"(p), "r"(x), "r"(y), "r"(z), "r"(w) : "memory");
}
__device__ __forceinline__ void fence_release() { asm volatile("fence.proxy.async.global;\nfence.release.gpu;" ::: "memory"); }
__device__ __forceinline__ void fence_acquire() { asm volatile("fence.acquire.gpu;\nfence.proxy.async.global;" ::: "memory"); }
__device__ __forceinline__ void signal_cnt(int idx) { asm volatile("red.relaxed.gpu.global.add.u32 [%0], 1;" ::"l"(&g_cnt[idx * 32]) : "memory"); }
__device__ __forceinline__ void wait_cnt(int idx, unsigned target) {
  uint32_t n = 0;
#pragma unroll 1
  while (!__all_sync(0xffffffffu, (int)(ld_relaxed32(&g_cnt[idx * 32]) - target) >= 0)) {
    if (spin_guard(n, 0x100 + idx)) break;
  }
  fence_acquire();
}
__device__ __forceinline__ void bulk_s2g(void* dst, uint32_t src, int bytes) {
  asm volatile("cp.async.bulk.global.shared::cta.bulk_group [%0], [%1], %2;" ::"l"(dst), "r"(src), "r"(bytes) : "memory");
}
__device__ __forceinline__ void bulk_add_s2g(void* dst, uint32_t src, int bytes) {
  asm volatile("cp.reduce.async.bulk.global.shared::cta.bulk_group.add.noftz.bf16 [%0], [%1], %2;" ::"l"(dst), "r"(src), "r"(bytes) : "memory");
}
__device__ __forceinline__ void prefetch_l2(const void* p, int bytes) { asm volatile("cp.async.bulk.prefetch.L2.global [%0], %1;" ::"l"(p), "r"(bytes) : "memory"); }
__device__ __forceinline__ void prefetch_tile(const CUtensorMap* tm, int c0, int c1) {
  asm volatile("cp.async.bulk.prefetch.tensor.2d.L2.global.tile [%0, {%1, %2}];" ::"l"(tm), "r"(c0), "r"(c1) : "memory");
}
__device__ __forceinline__ void prefetch_map(const CUtensorMap* tm) { asm volatile("prefetch.tensormap [%0];" ::"l"(tm) : "memory"); }
__device__ __forceinline__ uint32_t pack_bf16(float lo, float hi) {
  uint32_t r; asm("cvt.rn.bf16x2.f32 %0, %1, %2;" : "=r"(r) : "f"(hi), "f"(lo)); return r;
}
__device__ __forceinline__ float bf_lo(uint32_t v) { return __uint_as_float(v << 16); }
__device__ __forceinline__ float bf_hi(uint32_t v) { return __uint_as_float(v & 0xFFFF0000u); }
__device__ __forceinline__ float bf_round(float x) { return __bfloat162float(__float2bfloat16_rn(x)); }
__device__ __forceinline__ uint32_t bmul2(uint32_t a, uint32_t b) { uint32_t r; asm("mul.rn.bf16x2 %0, %1, %2;" : "=r"(r) : "r"(a), "r"(b)); return r; }
__device__ __forceinline__ uint32_t bfma2(uint32_t a, uint32_t b, uint32_t c) { uint32_t r; asm("fma.rn.bf16x2 %0, %1, %2, %3;" : "=r"(r) : "r"(a), "r"(b), "r"(c)); return r; }
__device__ __forceinline__ uint32_t badd2(uint32_t a, uint32_t b) { uint32_t r; asm("add.rn.bf16x2 %0, %1, %2;" : "=r"(r) : "r"(a), "r"(b)); return r; }
__device__ __forceinline__ uint32_t bsub2(uint32_t a, uint32_t b) { uint32_t r; asm("sub.rn.bf16x2 %0, %1, %2;" : "=r"(r) : "r"(a), "r"(b)); return r; }
__device__ __forceinline__ uint32_t tagged(float v, uint32_t ep) { return (__float_as_uint(v) & ~15u) | (ep & 15u); }
__device__ __forceinline__ float tanh_fast(float x) { float r; asm("tanh.approx.f32 %0, %1;" : "=f"(r) : "f"(x)); return r; }
__device__ __forceinline__ float rcp_fast(float x) { float r; asm("rcp.approx.ftz.f32 %0, %1;" : "=f"(r) : "f"(x)); return r; }
__device__ __forceinline__ float sqrt_fast(float x) { float r; asm("sqrt.approx.ftz.f32 %0, %1;" : "=f"(r) : "f"(x)); return r; }
__device__ __forceinline__ uint32_t lds32(uint32_t a) { uint32_t v; asm volatile("ld.shared.b32 %0, [%1];" : "=r"(v) : "r"(a)); return v; }
__device__ __forceinline__ uint4 lds128(uint32_t a) { uint4 v; asm volatile("ld.shared.v4.b32 {%0,%1,%2,%3}, [%4];" : "=r"(v.x), "=r"(v.y), "=r"(v.z), "=r"(v.w) : "r"(a)); return v; }
__device__ __forceinline__ float2 lds64f(uint32_t a) { float2 v; asm volatile("ld.shared.v2.f32 {%0,%1}, [%2];" : "=f"(v.x), "=f"(v.y) : "r"(a)); return v; }
__device__ __forceinline__ void sts64f(uint32_t a, float x, float y) { asm volatile("st.shared.v2.f32 [%0], {%1,%2};" ::"r"(a), "f"(x), "f"(y) : "memory"); }
__device__ __forceinline__ void sts32(uint32_t a, uint32_t x) { asm volatile("st.shared.b32 [%0], %1;" ::"r"(a), "r"(x) : "memory"); }
__device__ __forceinline__ void sts128(uint32_t a, uint32_t x, uint32_t y, uint32_t z, uint32_t w) { asm volatile("st.shared.v4.b32 [%0], {%1,%2,%3,%4};" ::"r"(a), "r"(x), "r"(y), "r"(z), "r"(w) : "memory"); }
__device__ __forceinline__ void stsm4(uint32_t a, uint32_t r0, uint32_t r1, uint32_t r2, uint32_t r3) {
  asm volatile("stmatrix.sync.aligned.m8n8.x4.shared.b16 [%0], {%1,%2,%3,%4};" ::"r"(a), "r"(r0), "r"(r1), "r"(r2), "r"(r3) : "memory");
}
__device__ __forceinline__ void stsm4t(uint32_t a, uint32_t r0, uint32_t r1, uint32_t r2, uint32_t r3) {
  asm volatile("stmatrix.sync.aligned.m8n8.x4.trans.shared.b16 [%0], {%1,%2,%3,%4};" ::"r"(a), "r"(r0), "r"(r1), "r"(r2), "r"(r3) : "memory");
}
__device__ __forceinline__ void stsm2(uint32_t a, uint32_t r0, uint32_t r1) {
  asm volatile("stmatrix.sync.aligned.m8n8.x2.shared.b16 [%0], {%1,%2};" ::"r"(a), "r"(r0), "r"(r1) : "memory");
}
__device__ __forceinline__ void ldsm4(uint32_t a, uint32_t& r0, uint32_t& r1, uint32_t& r2, uint32_t& r3) {
  asm volatile("ldmatrix.sync.aligned.m8n8.x4.shared.b16 {%0,%1,%2,%3}, [%4];" : "=r"(r0), "=r"(r1), "=r"(r2), "=r"(r3) : "r"(a) : "memory");
}
__device__ __forceinline__ void ldsm4t(uint32_t a, uint32_t& r0, uint32_t& r1, uint32_t& r2, uint32_t& r3) {
  asm volatile("ldmatrix.sync.aligned.m8n8.x4.trans.shared.b16 {%0,%1,%2,%3}, [%4];" : "=r"(r0), "=r"(r1), "=r"(r2), "=r"(r3) : "r"(a) : "memory");
}
__device__ __forceinline__ uint32_t mapa(uint32_t a, uint32_t rank) { uint32_t r; asm("mapa.shared::cluster.u32 %0, %1, %2;" : "=r"(r) : "r"(a), "r"(rank)); return r; }
__device__ __forceinline__ void mbar_arrive_remote(uint32_t a) { asm volatile("mbarrier.arrive.relaxed.cluster.shared::cluster.b64 _, [%0];" ::"r"(a) : "memory"); }
__device__ __forceinline__ void st_async128(uint32_t a, uint32_t x, uint32_t y, uint32_t z, uint32_t w, uint32_t bar) {
  asm volatile("st.async.weak.shared::cluster.mbarrier::complete_tx::bytes.v4.b32 [%0], {%1,%2,%3,%4}, [%5];" ::"r"(a), "r"(x), "r"(y), "r"(z), "r"(w), "r"(bar) : "memory");
}
#define TS(i)

#define TSKV
__device__ __forceinline__ void wg_ss_216(float (&d)[108], uint64_t da, uint64_t db, int sd) {
  asm volatile("{\n.reg .pred p;\nsetp.ne.b32 p, %110, 0;\n"
    "wgmma.mma_async.sync.aligned.m64n216k16.f32.bf16.bf16 {%0,%1,%2,%3,%4,%5,%6,%7,%8,%9,%10,%11,%12,%13,%14,%15,%16,%17,%18,%19,%20,%21,%22,%23,%24,%25,%26,%27,%28,%29,%30,%31,%32,%33,%34,%35,%36,%37,%38,%39,%40,%41,%42,%43,%44,%45,%46,%47,%48,%49,%50,%51,%52,%53,%54,%55,%56,%57,%58,%59,%60,%61,%62,%63,%64,%65,%66,%67,%68,%69,%70,%71,%72,%73,%74,%75,%76,%77,%78,%79,%80,%81,%82,%83,%84,%85,%86,%87,%88,%89,%90,%91,%92,%93,%94,%95,%96,%97,%98,%99,%100,%101,%102,%103,%104,%105,%106,%107}, %108, %109, p, 1, 1, 0, 1;\n}\n"
    : "+f"(d[0]),"+f"(d[1]),"+f"(d[2]),"+f"(d[3]),"+f"(d[4]),"+f"(d[5]),"+f"(d[6]),"+f"(d[7]),"+f"(d[8]),"+f"(d[9]),"+f"(d[10]),"+f"(d[11]),"+f"(d[12]),"+f"(d[13]),"+f"(d[14]),"+f"(d[15]),"+f"(d[16]),"+f"(d[17]),"+f"(d[18]),"+f"(d[19]),"+f"(d[20]),"+f"(d[21]),"+f"(d[22]),"+f"(d[23]),"+f"(d[24]),"+f"(d[25]),"+f"(d[26]),"+f"(d[27]),"+f"(d[28]),"+f"(d[29]),"+f"(d[30]),"+f"(d[31]),"+f"(d[32]),"+f"(d[33]),"+f"(d[34]),"+f"(d[35]),"+f"(d[36]),"+f"(d[37]),"+f"(d[38]),"+f"(d[39]),"+f"(d[40]),"+f"(d[41]),"+f"(d[42]),"+f"(d[43]),"+f"(d[44]),"+f"(d[45]),"+f"(d[46]),"+f"(d[47]),"+f"(d[48]),"+f"(d[49]),"+f"(d[50]),"+f"(d[51]),"+f"(d[52]),"+f"(d[53]),"+f"(d[54]),"+f"(d[55]),"+f"(d[56]),"+f"(d[57]),"+f"(d[58]),"+f"(d[59]),"+f"(d[60]),"+f"(d[61]),"+f"(d[62]),"+f"(d[63]),"+f"(d[64]),"+f"(d[65]),"+f"(d[66]),"+f"(d[67]),"+f"(d[68]),"+f"(d[69]),"+f"(d[70]),"+f"(d[71]),"+f"(d[72]),"+f"(d[73]),"+f"(d[74]),"+f"(d[75]),"+f"(d[76]),"+f"(d[77]),"+f"(d[78]),"+f"(d[79]),"+f"(d[80]),"+f"(d[81]),"+f"(d[82]),"+f"(d[83]),"+f"(d[84]),"+f"(d[85]),"+f"(d[86]),"+f"(d[87]),"+f"(d[88]),"+f"(d[89]),"+f"(d[90]),"+f"(d[91]),"+f"(d[92]),"+f"(d[93]),"+f"(d[94]),"+f"(d[95]),"+f"(d[96]),"+f"(d[97]),"+f"(d[98]),"+f"(d[99]),"+f"(d[100]),"+f"(d[101]),"+f"(d[102]),"+f"(d[103]),"+f"(d[104]),"+f"(d[105]),"+f"(d[106]),"+f"(d[107]) : "l"(da), "l"(db), "r"(sd));
}
__device__ __forceinline__ void wg_ss_160(float (&d)[80], uint64_t da, uint64_t db, int sd) {
  asm volatile("{\n.reg .pred p;\nsetp.ne.b32 p, %82, 0;\n"
    "wgmma.mma_async.sync.aligned.m64n160k16.f32.bf16.bf16 {%0,%1,%2,%3,%4,%5,%6,%7,%8,%9,%10,%11,%12,%13,%14,%15,%16,%17,%18,%19,%20,%21,%22,%23,%24,%25,%26,%27,%28,%29,%30,%31,%32,%33,%34,%35,%36,%37,%38,%39,%40,%41,%42,%43,%44,%45,%46,%47,%48,%49,%50,%51,%52,%53,%54,%55,%56,%57,%58,%59,%60,%61,%62,%63,%64,%65,%66,%67,%68,%69,%70,%71,%72,%73,%74,%75,%76,%77,%78,%79}, %80, %81, p, 1, 1, 0, 1;\n}\n"
    : "+f"(d[0]),"+f"(d[1]),"+f"(d[2]),"+f"(d[3]),"+f"(d[4]),"+f"(d[5]),"+f"(d[6]),"+f"(d[7]),"+f"(d[8]),"+f"(d[9]),"+f"(d[10]),"+f"(d[11]),"+f"(d[12]),"+f"(d[13]),"+f"(d[14]),"+f"(d[15]),"+f"(d[16]),"+f"(d[17]),"+f"(d[18]),"+f"(d[19]),"+f"(d[20]),"+f"(d[21]),"+f"(d[22]),"+f"(d[23]),"+f"(d[24]),"+f"(d[25]),"+f"(d[26]),"+f"(d[27]),"+f"(d[28]),"+f"(d[29]),"+f"(d[30]),"+f"(d[31]),"+f"(d[32]),"+f"(d[33]),"+f"(d[34]),"+f"(d[35]),"+f"(d[36]),"+f"(d[37]),"+f"(d[38]),"+f"(d[39]),"+f"(d[40]),"+f"(d[41]),"+f"(d[42]),"+f"(d[43]),"+f"(d[44]),"+f"(d[45]),"+f"(d[46]),"+f"(d[47]),"+f"(d[48]),"+f"(d[49]),"+f"(d[50]),"+f"(d[51]),"+f"(d[52]),"+f"(d[53]),"+f"(d[54]),"+f"(d[55]),"+f"(d[56]),"+f"(d[57]),"+f"(d[58]),"+f"(d[59]),"+f"(d[60]),"+f"(d[61]),"+f"(d[62]),"+f"(d[63]),"+f"(d[64]),"+f"(d[65]),"+f"(d[66]),"+f"(d[67]),"+f"(d[68]),"+f"(d[69]),"+f"(d[70]),"+f"(d[71]),"+f"(d[72]),"+f"(d[73]),"+f"(d[74]),"+f"(d[75]),"+f"(d[76]),"+f"(d[77]),"+f"(d[78]),"+f"(d[79]) : "l"(da), "l"(db), "r"(sd));
}
__device__ __forceinline__ void wg_rs_216(float (&d)[108], uint32_t a0, uint32_t a1, uint32_t a2, uint32_t a3, uint64_t db) {
  asm volatile("{\n.reg .pred p;\nsetp.ne.b32 p, 1, 0;\n"
    "wgmma.mma_async.sync.aligned.m64n216k16.f32.bf16.bf16 {%0,%1,%2,%3,%4,%5,%6,%7,%8,%9,%10,%11,%12,%13,%14,%15,%16,%17,%18,%19,%20,%21,%22,%23,%24,%25,%26,%27,%28,%29,%30,%31,%32,%33,%34,%35,%36,%37,%38,%39,%40,%41,%42,%43,%44,%45,%46,%47,%48,%49,%50,%51,%52,%53,%54,%55,%56,%57,%58,%59,%60,%61,%62,%63,%64,%65,%66,%67,%68,%69,%70,%71,%72,%73,%74,%75,%76,%77,%78,%79,%80,%81,%82,%83,%84,%85,%86,%87,%88,%89,%90,%91,%92,%93,%94,%95,%96,%97,%98,%99,%100,%101,%102,%103,%104,%105,%106,%107}, {%108,%109,%110,%111}, %112, p, 1, 1, 1;\n}\n"
    : "+f"(d[0]),"+f"(d[1]),"+f"(d[2]),"+f"(d[3]),"+f"(d[4]),"+f"(d[5]),"+f"(d[6]),"+f"(d[7]),"+f"(d[8]),"+f"(d[9]),"+f"(d[10]),"+f"(d[11]),"+f"(d[12]),"+f"(d[13]),"+f"(d[14]),"+f"(d[15]),"+f"(d[16]),"+f"(d[17]),"+f"(d[18]),"+f"(d[19]),"+f"(d[20]),"+f"(d[21]),"+f"(d[22]),"+f"(d[23]),"+f"(d[24]),"+f"(d[25]),"+f"(d[26]),"+f"(d[27]),"+f"(d[28]),"+f"(d[29]),"+f"(d[30]),"+f"(d[31]),"+f"(d[32]),"+f"(d[33]),"+f"(d[34]),"+f"(d[35]),"+f"(d[36]),"+f"(d[37]),"+f"(d[38]),"+f"(d[39]),"+f"(d[40]),"+f"(d[41]),"+f"(d[42]),"+f"(d[43]),"+f"(d[44]),"+f"(d[45]),"+f"(d[46]),"+f"(d[47]),"+f"(d[48]),"+f"(d[49]),"+f"(d[50]),"+f"(d[51]),"+f"(d[52]),"+f"(d[53]),"+f"(d[54]),"+f"(d[55]),"+f"(d[56]),"+f"(d[57]),"+f"(d[58]),"+f"(d[59]),"+f"(d[60]),"+f"(d[61]),"+f"(d[62]),"+f"(d[63]),"+f"(d[64]),"+f"(d[65]),"+f"(d[66]),"+f"(d[67]),"+f"(d[68]),"+f"(d[69]),"+f"(d[70]),"+f"(d[71]),"+f"(d[72]),"+f"(d[73]),"+f"(d[74]),"+f"(d[75]),"+f"(d[76]),"+f"(d[77]),"+f"(d[78]),"+f"(d[79]),"+f"(d[80]),"+f"(d[81]),"+f"(d[82]),"+f"(d[83]),"+f"(d[84]),"+f"(d[85]),"+f"(d[86]),"+f"(d[87]),"+f"(d[88]),"+f"(d[89]),"+f"(d[90]),"+f"(d[91]),"+f"(d[92]),"+f"(d[93]),"+f"(d[94]),"+f"(d[95]),"+f"(d[96]),"+f"(d[97]),"+f"(d[98]),"+f"(d[99]),"+f"(d[100]),"+f"(d[101]),"+f"(d[102]),"+f"(d[103]),"+f"(d[104]),"+f"(d[105]),"+f"(d[106]),"+f"(d[107]) : "r"(a0), "r"(a1), "r"(a2), "r"(a3), "l"(db));
}
__device__ __forceinline__ void wg_cv_0_0(float (&d)[128], uint32_t a0, uint32_t a1, uint32_t a2, uint32_t a3, uint32_t db) {
  asm volatile("{\n.reg .pred p;\n.reg .b64 t;\nsetp.ne.b32 p, 0, 0;\nmov.b64 t, {%20, 8};\n"
    "wgmma.mma_async.sync.aligned.m64n32k16.f32.bf16.bf16 {%0,%1,%2,%3,%4,%5,%6,%7,%8,%9,%10,%11,%12,%13,%14,%15}, {%16,%17,%18,%19}, t, p, 1, 1, 0;\n}\n"
    : "+f"(d[0]),"+f"(d[1]),"+f"(d[2]),"+f"(d[3]),"+f"(d[4]),"+f"(d[5]),"+f"(d[6]),"+f"(d[7]),"+f"(d[8]),"+f"(d[9]),"+f"(d[10]),"+f"(d[11]),"+f"(d[12]),"+f"(d[13]),"+f"(d[14]),"+f"(d[15]) : "r"(a0), "r"(a1), "r"(a2), "r"(a3), "r"(db));
}
__device__ __forceinline__ void wg_cv_0_1(float (&d)[128], uint32_t a0, uint32_t a1, uint32_t a2, uint32_t a3, uint32_t db) {
  asm volatile("{\n.reg .pred p;\n.reg .b64 t;\nsetp.ne.b32 p, 1, 0;\nmov.b64 t, {%20, 8};\n"
    "wgmma.mma_async.sync.aligned.m64n32k16.f32.bf16.bf16 {%0,%1,%2,%3,%4,%5,%6,%7,%8,%9,%10,%11,%12,%13,%14,%15}, {%16,%17,%18,%19}, t, p, 1, 1, 0;\n}\n"
    : "+f"(d[0]),"+f"(d[1]),"+f"(d[2]),"+f"(d[3]),"+f"(d[4]),"+f"(d[5]),"+f"(d[6]),"+f"(d[7]),"+f"(d[8]),"+f"(d[9]),"+f"(d[10]),"+f"(d[11]),"+f"(d[12]),"+f"(d[13]),"+f"(d[14]),"+f"(d[15]) : "r"(a0), "r"(a1), "r"(a2), "r"(a3), "r"(db));
}
__device__ __forceinline__ void wg_cv_1_0(float (&d)[128], uint32_t a0, uint32_t a1, uint32_t a2, uint32_t a3, uint32_t db) {
  asm volatile("{\n.reg .pred p;\n.reg .b64 t;\nsetp.ne.b32 p, 0, 0;\nmov.b64 t, {%20, 8};\n"
    "wgmma.mma_async.sync.aligned.m64n32k16.f32.bf16.bf16 {%0,%1,%2,%3,%4,%5,%6,%7,%8,%9,%10,%11,%12,%13,%14,%15}, {%16,%17,%18,%19}, t, p, 1, 1, 0;\n}\n"
    : "+f"(d[16]),"+f"(d[17]),"+f"(d[18]),"+f"(d[19]),"+f"(d[20]),"+f"(d[21]),"+f"(d[22]),"+f"(d[23]),"+f"(d[24]),"+f"(d[25]),"+f"(d[26]),"+f"(d[27]),"+f"(d[28]),"+f"(d[29]),"+f"(d[30]),"+f"(d[31]) : "r"(a0), "r"(a1), "r"(a2), "r"(a3), "r"(db));
}
__device__ __forceinline__ void wg_cv_1_1(float (&d)[128], uint32_t a0, uint32_t a1, uint32_t a2, uint32_t a3, uint32_t db) {
  asm volatile("{\n.reg .pred p;\n.reg .b64 t;\nsetp.ne.b32 p, 1, 0;\nmov.b64 t, {%20, 8};\n"
    "wgmma.mma_async.sync.aligned.m64n32k16.f32.bf16.bf16 {%0,%1,%2,%3,%4,%5,%6,%7,%8,%9,%10,%11,%12,%13,%14,%15}, {%16,%17,%18,%19}, t, p, 1, 1, 0;\n}\n"
    : "+f"(d[16]),"+f"(d[17]),"+f"(d[18]),"+f"(d[19]),"+f"(d[20]),"+f"(d[21]),"+f"(d[22]),"+f"(d[23]),"+f"(d[24]),"+f"(d[25]),"+f"(d[26]),"+f"(d[27]),"+f"(d[28]),"+f"(d[29]),"+f"(d[30]),"+f"(d[31]) : "r"(a0), "r"(a1), "r"(a2), "r"(a3), "r"(db));
}
__device__ __forceinline__ void wg_cv_2_0(float (&d)[128], uint32_t a0, uint32_t a1, uint32_t a2, uint32_t a3, uint32_t db) {
  asm volatile("{\n.reg .pred p;\n.reg .b64 t;\nsetp.ne.b32 p, 0, 0;\nmov.b64 t, {%20, 8};\n"
    "wgmma.mma_async.sync.aligned.m64n32k16.f32.bf16.bf16 {%0,%1,%2,%3,%4,%5,%6,%7,%8,%9,%10,%11,%12,%13,%14,%15}, {%16,%17,%18,%19}, t, p, 1, 1, 0;\n}\n"
    : "+f"(d[32]),"+f"(d[33]),"+f"(d[34]),"+f"(d[35]),"+f"(d[36]),"+f"(d[37]),"+f"(d[38]),"+f"(d[39]),"+f"(d[40]),"+f"(d[41]),"+f"(d[42]),"+f"(d[43]),"+f"(d[44]),"+f"(d[45]),"+f"(d[46]),"+f"(d[47]) : "r"(a0), "r"(a1), "r"(a2), "r"(a3), "r"(db));
}
__device__ __forceinline__ void wg_cv_2_1(float (&d)[128], uint32_t a0, uint32_t a1, uint32_t a2, uint32_t a3, uint32_t db) {
  asm volatile("{\n.reg .pred p;\n.reg .b64 t;\nsetp.ne.b32 p, 1, 0;\nmov.b64 t, {%20, 8};\n"
    "wgmma.mma_async.sync.aligned.m64n32k16.f32.bf16.bf16 {%0,%1,%2,%3,%4,%5,%6,%7,%8,%9,%10,%11,%12,%13,%14,%15}, {%16,%17,%18,%19}, t, p, 1, 1, 0;\n}\n"
    : "+f"(d[32]),"+f"(d[33]),"+f"(d[34]),"+f"(d[35]),"+f"(d[36]),"+f"(d[37]),"+f"(d[38]),"+f"(d[39]),"+f"(d[40]),"+f"(d[41]),"+f"(d[42]),"+f"(d[43]),"+f"(d[44]),"+f"(d[45]),"+f"(d[46]),"+f"(d[47]) : "r"(a0), "r"(a1), "r"(a2), "r"(a3), "r"(db));
}
__device__ __forceinline__ void wg_cv_3_0(float (&d)[128], uint32_t a0, uint32_t a1, uint32_t a2, uint32_t a3, uint32_t db) {
  asm volatile("{\n.reg .pred p;\n.reg .b64 t;\nsetp.ne.b32 p, 0, 0;\nmov.b64 t, {%20, 8};\n"
    "wgmma.mma_async.sync.aligned.m64n32k16.f32.bf16.bf16 {%0,%1,%2,%3,%4,%5,%6,%7,%8,%9,%10,%11,%12,%13,%14,%15}, {%16,%17,%18,%19}, t, p, 1, 1, 0;\n}\n"
    : "+f"(d[48]),"+f"(d[49]),"+f"(d[50]),"+f"(d[51]),"+f"(d[52]),"+f"(d[53]),"+f"(d[54]),"+f"(d[55]),"+f"(d[56]),"+f"(d[57]),"+f"(d[58]),"+f"(d[59]),"+f"(d[60]),"+f"(d[61]),"+f"(d[62]),"+f"(d[63]) : "r"(a0), "r"(a1), "r"(a2), "r"(a3), "r"(db));
}
__device__ __forceinline__ void wg_cv_3_1(float (&d)[128], uint32_t a0, uint32_t a1, uint32_t a2, uint32_t a3, uint32_t db) {
  asm volatile("{\n.reg .pred p;\n.reg .b64 t;\nsetp.ne.b32 p, 1, 0;\nmov.b64 t, {%20, 8};\n"
    "wgmma.mma_async.sync.aligned.m64n32k16.f32.bf16.bf16 {%0,%1,%2,%3,%4,%5,%6,%7,%8,%9,%10,%11,%12,%13,%14,%15}, {%16,%17,%18,%19}, t, p, 1, 1, 0;\n}\n"
    : "+f"(d[48]),"+f"(d[49]),"+f"(d[50]),"+f"(d[51]),"+f"(d[52]),"+f"(d[53]),"+f"(d[54]),"+f"(d[55]),"+f"(d[56]),"+f"(d[57]),"+f"(d[58]),"+f"(d[59]),"+f"(d[60]),"+f"(d[61]),"+f"(d[62]),"+f"(d[63]) : "r"(a0), "r"(a1), "r"(a2), "r"(a3), "r"(db));
}
__device__ __forceinline__ void wg_cv_4_0(float (&d)[128], uint32_t a0, uint32_t a1, uint32_t a2, uint32_t a3, uint32_t db) {
  asm volatile("{\n.reg .pred p;\n.reg .b64 t;\nsetp.ne.b32 p, 0, 0;\nmov.b64 t, {%20, 8};\n"
    "wgmma.mma_async.sync.aligned.m64n32k16.f32.bf16.bf16 {%0,%1,%2,%3,%4,%5,%6,%7,%8,%9,%10,%11,%12,%13,%14,%15}, {%16,%17,%18,%19}, t, p, 1, 1, 0;\n}\n"
    : "+f"(d[64]),"+f"(d[65]),"+f"(d[66]),"+f"(d[67]),"+f"(d[68]),"+f"(d[69]),"+f"(d[70]),"+f"(d[71]),"+f"(d[72]),"+f"(d[73]),"+f"(d[74]),"+f"(d[75]),"+f"(d[76]),"+f"(d[77]),"+f"(d[78]),"+f"(d[79]) : "r"(a0), "r"(a1), "r"(a2), "r"(a3), "r"(db));
}
__device__ __forceinline__ void wg_cv_4_1(float (&d)[128], uint32_t a0, uint32_t a1, uint32_t a2, uint32_t a3, uint32_t db) {
  asm volatile("{\n.reg .pred p;\n.reg .b64 t;\nsetp.ne.b32 p, 1, 0;\nmov.b64 t, {%20, 8};\n"
    "wgmma.mma_async.sync.aligned.m64n32k16.f32.bf16.bf16 {%0,%1,%2,%3,%4,%5,%6,%7,%8,%9,%10,%11,%12,%13,%14,%15}, {%16,%17,%18,%19}, t, p, 1, 1, 0;\n}\n"
    : "+f"(d[64]),"+f"(d[65]),"+f"(d[66]),"+f"(d[67]),"+f"(d[68]),"+f"(d[69]),"+f"(d[70]),"+f"(d[71]),"+f"(d[72]),"+f"(d[73]),"+f"(d[74]),"+f"(d[75]),"+f"(d[76]),"+f"(d[77]),"+f"(d[78]),"+f"(d[79]) : "r"(a0), "r"(a1), "r"(a2), "r"(a3), "r"(db));
}
__device__ __forceinline__ void wg_cv_5_0(float (&d)[128], uint32_t a0, uint32_t a1, uint32_t a2, uint32_t a3, uint32_t db) {
  asm volatile("{\n.reg .pred p;\n.reg .b64 t;\nsetp.ne.b32 p, 0, 0;\nmov.b64 t, {%20, 8};\n"
    "wgmma.mma_async.sync.aligned.m64n32k16.f32.bf16.bf16 {%0,%1,%2,%3,%4,%5,%6,%7,%8,%9,%10,%11,%12,%13,%14,%15}, {%16,%17,%18,%19}, t, p, 1, 1, 0;\n}\n"
    : "+f"(d[80]),"+f"(d[81]),"+f"(d[82]),"+f"(d[83]),"+f"(d[84]),"+f"(d[85]),"+f"(d[86]),"+f"(d[87]),"+f"(d[88]),"+f"(d[89]),"+f"(d[90]),"+f"(d[91]),"+f"(d[92]),"+f"(d[93]),"+f"(d[94]),"+f"(d[95]) : "r"(a0), "r"(a1), "r"(a2), "r"(a3), "r"(db));
}
__device__ __forceinline__ void wg_cv_5_1(float (&d)[128], uint32_t a0, uint32_t a1, uint32_t a2, uint32_t a3, uint32_t db) {
  asm volatile("{\n.reg .pred p;\n.reg .b64 t;\nsetp.ne.b32 p, 1, 0;\nmov.b64 t, {%20, 8};\n"
    "wgmma.mma_async.sync.aligned.m64n32k16.f32.bf16.bf16 {%0,%1,%2,%3,%4,%5,%6,%7,%8,%9,%10,%11,%12,%13,%14,%15}, {%16,%17,%18,%19}, t, p, 1, 1, 0;\n}\n"
    : "+f"(d[80]),"+f"(d[81]),"+f"(d[82]),"+f"(d[83]),"+f"(d[84]),"+f"(d[85]),"+f"(d[86]),"+f"(d[87]),"+f"(d[88]),"+f"(d[89]),"+f"(d[90]),"+f"(d[91]),"+f"(d[92]),"+f"(d[93]),"+f"(d[94]),"+f"(d[95]) : "r"(a0), "r"(a1), "r"(a2), "r"(a3), "r"(db));
}
__device__ __forceinline__ void wg_cv_6_0(float (&d)[128], uint32_t a0, uint32_t a1, uint32_t a2, uint32_t a3, uint32_t db) {
  asm volatile("{\n.reg .pred p;\n.reg .b64 t;\nsetp.ne.b32 p, 0, 0;\nmov.b64 t, {%20, 8};\n"
    "wgmma.mma_async.sync.aligned.m64n32k16.f32.bf16.bf16 {%0,%1,%2,%3,%4,%5,%6,%7,%8,%9,%10,%11,%12,%13,%14,%15}, {%16,%17,%18,%19}, t, p, 1, 1, 0;\n}\n"
    : "+f"(d[96]),"+f"(d[97]),"+f"(d[98]),"+f"(d[99]),"+f"(d[100]),"+f"(d[101]),"+f"(d[102]),"+f"(d[103]),"+f"(d[104]),"+f"(d[105]),"+f"(d[106]),"+f"(d[107]),"+f"(d[108]),"+f"(d[109]),"+f"(d[110]),"+f"(d[111]) : "r"(a0), "r"(a1), "r"(a2), "r"(a3), "r"(db));
}
__device__ __forceinline__ void wg_cv_6_1(float (&d)[128], uint32_t a0, uint32_t a1, uint32_t a2, uint32_t a3, uint32_t db) {
  asm volatile("{\n.reg .pred p;\n.reg .b64 t;\nsetp.ne.b32 p, 1, 0;\nmov.b64 t, {%20, 8};\n"
    "wgmma.mma_async.sync.aligned.m64n32k16.f32.bf16.bf16 {%0,%1,%2,%3,%4,%5,%6,%7,%8,%9,%10,%11,%12,%13,%14,%15}, {%16,%17,%18,%19}, t, p, 1, 1, 0;\n}\n"
    : "+f"(d[96]),"+f"(d[97]),"+f"(d[98]),"+f"(d[99]),"+f"(d[100]),"+f"(d[101]),"+f"(d[102]),"+f"(d[103]),"+f"(d[104]),"+f"(d[105]),"+f"(d[106]),"+f"(d[107]),"+f"(d[108]),"+f"(d[109]),"+f"(d[110]),"+f"(d[111]) : "r"(a0), "r"(a1), "r"(a2), "r"(a3), "r"(db));
}
__device__ __forceinline__ void wg_cv_7_0(float (&d)[128], uint32_t a0, uint32_t a1, uint32_t a2, uint32_t a3, uint32_t db) {
  asm volatile("{\n.reg .pred p;\n.reg .b64 t;\nsetp.ne.b32 p, 0, 0;\nmov.b64 t, {%20, 8};\n"
    "wgmma.mma_async.sync.aligned.m64n32k16.f32.bf16.bf16 {%0,%1,%2,%3,%4,%5,%6,%7,%8,%9,%10,%11,%12,%13,%14,%15}, {%16,%17,%18,%19}, t, p, 1, 1, 0;\n}\n"
    : "+f"(d[112]),"+f"(d[113]),"+f"(d[114]),"+f"(d[115]),"+f"(d[116]),"+f"(d[117]),"+f"(d[118]),"+f"(d[119]),"+f"(d[120]),"+f"(d[121]),"+f"(d[122]),"+f"(d[123]),"+f"(d[124]),"+f"(d[125]),"+f"(d[126]),"+f"(d[127]) : "r"(a0), "r"(a1), "r"(a2), "r"(a3), "r"(db));
}
__device__ __forceinline__ void wg_cv_7_1(float (&d)[128], uint32_t a0, uint32_t a1, uint32_t a2, uint32_t a3, uint32_t db) {
  asm volatile("{\n.reg .pred p;\n.reg .b64 t;\nsetp.ne.b32 p, 1, 0;\nmov.b64 t, {%20, 8};\n"
    "wgmma.mma_async.sync.aligned.m64n32k16.f32.bf16.bf16 {%0,%1,%2,%3,%4,%5,%6,%7,%8,%9,%10,%11,%12,%13,%14,%15}, {%16,%17,%18,%19}, t, p, 1, 1, 0;\n}\n"
    : "+f"(d[112]),"+f"(d[113]),"+f"(d[114]),"+f"(d[115]),"+f"(d[116]),"+f"(d[117]),"+f"(d[118]),"+f"(d[119]),"+f"(d[120]),"+f"(d[121]),"+f"(d[122]),"+f"(d[123]),"+f"(d[124]),"+f"(d[125]),"+f"(d[126]),"+f"(d[127]) : "r"(a0), "r"(a1), "r"(a2), "r"(a3), "r"(db));
}
template <class F, class T> __device__ __forceinline__ void conv_chain_1(float (&d)[128], uint32_t (&a)[64], uint32_t db, uint32_t ao, uint32_t ab, F hand, T dead) {
  wg_cv_7_0(d, a[60], a[61], a[62], a[63], db + 0);
  wg_cv_6_0(d, a[52], a[53], a[54], a[55], db + 0);
  dead();
  wg_cv_7_1(d, a[56], a[57], a[58], a[59], db + 16);
  wg_cv_5_0(d, a[44], a[45], a[46], a[47], db + 0);
  wg_cv_6_1(d, a[48], a[49], a[50], a[51], db + 16);
  wg_cv_7_1(d, a[52], a[53], a[54], a[55], db + 32);
  wg_cv_5_1(d, a[40], a[41], a[42], a[43], db + 16);
  wg_cv_6_1(d, a[44], a[45], a[46], a[47], db + 32);
  wg_cv_7_1(d, a[48], a[49], a[50], a[51], db + 48);
  wg_cv_6_1(d, a[40], a[41], a[42], a[43], db + 48);
  wg_cv_7_1(d, a[44], a[45], a[46], a[47], db + 64);
  wg_cv_7_1(d, a[40], a[41], a[42], a[43], db + 80);
  wg_commit();
  wg_cv_7_1(d, a[36], a[37], a[38], a[39], db + 96);
  wg_cv_6_1(d, a[36], a[37], a[38], a[39], db + 64);
  wg_cv_5_1(d, a[36], a[37], a[38], a[39], db + 32);
  wg_cv_4_0(d, a[36], a[37], a[38], a[39], db + 0);
  wg_commit(); wg_wait<1>();
  wg_cv_7_1(d, a[32], a[33], a[34], a[35], db + 112);
  wg_cv_6_1(d, a[32], a[33], a[34], a[35], db + 80);
  wg_cv_5_1(d, a[32], a[33], a[34], a[35], db + 48);
  a[60] = lds32(ab + (3840));
  a[61] = lds32(ab + (3968));
  a[62] = lds32(ab + (3824));
  a[63] = lds32(ab + (3952));
  wg_cv_4_1(d, a[32], a[33], a[34], a[35], db + 16);
  wg_cv_7_1(d, a[28], a[29], a[30], a[31], db + 128);
  wg_cv_6_1(d, a[28], a[29], a[30], a[31], db + 96);
  wg_cv_5_1(d, a[28], a[29], a[30], a[31], db + 64);
  a[56] = lds32(ab + (3584));
  a[57] = lds32(ab + (3712));
  a[58] = lds32(ab + (3568));
  a[59] = lds32(ab + (3696));
  wg_cv_4_1(d, a[28], a[29], a[30], a[31], db + 32);
  wg_cv_3_0(d, a[28], a[29], a[30], a[31], db + 0);
  wg_cv_7_1(d, a[24], a[25], a[26], a[27], db + 144);
  wg_cv_6_1(d, a[24], a[25], a[26], a[27], db + 112);
  a[52] = lds32(ab + (3328));
  a[53] = lds32(ab + (3456));
  a[54] = lds32(ab + (3312));
  a[55] = lds32(ab + (3440));
  wg_cv_5_1(d, a[24], a[25], a[26], a[27], db + 80);
  wg_cv_4_1(d, a[24], a[25], a[26], a[27], db + 48);
  wg_cv_3_1(d, a[24], a[25], a[26], a[27], db + 16);
  wg_commit();
  wg_cv_7_1(d, a[20], a[21], a[22], a[23], db + 160);
  wg_cv_6_1(d, a[20], a[21], a[22], a[23], db + 128);
  wg_cv_5_1(d, a[20], a[21], a[22], a[23], db + 96);
  wg_cv_4_1(d, a[20], a[21], a[22], a[23], db + 64);
  wg_commit(); wg_wait<1>();
  a[48] = lds32(ab + (3072));
  a[49] = lds32(ab + (3200));
  a[50] = lds32(ab + (3056));
  a[51] = lds32(ab + (3184));
  wg_cv_3_1(d, a[20], a[21], a[22], a[23], db + 32);
  wg_cv_2_0(d, a[20], a[21], a[22], a[23], db + 0);
  wg_cv_7_1(d, a[16], a[17], a[18], a[19], db + 176);
  wg_cv_6_1(d, a[16], a[17], a[18], a[19], db + 144);
  a[44] = lds32(ab + (2816));
  a[45] = lds32(ab + (2944));
  a[46] = lds32(ab + (2800));
  a[47] = lds32(ab + (2928));
  wg_cv_5_1(d, a[16], a[17], a[18], a[19], db + 112);
  wg_cv_4_1(d, a[16], a[17], a[18], a[19], db + 80);
  wg_cv_3_1(d, a[16], a[17], a[18], a[19], db + 48);
  wg_cv_2_1(d, a[16], a[17], a[18], a[19], db + 16);
  a[40] = lds32(ab + (2560));
  a[41] = lds32(ab + (2688));
  a[42] = lds32(ab + (2544));
  a[43] = lds32(ab + (2672));
  wg_cv_7_1(d, a[12], a[13], a[14], a[15], db + 192);
  wg_cv_6_1(d, a[12], a[13], a[14], a[15], db + 160);
  wg_cv_5_1(d, a[12], a[13], a[14], a[15], db + 128);
  wg_cv_4_1(d, a[12], a[13], a[14], a[15], db + 96);
  a[36] = lds32(ab + (2304));
  a[37] = lds32(ab + (2432));
  a[38] = lds32(ab + (2288));
  a[39] = lds32(ab + (2416));
  wg_cv_3_1(d, a[12], a[13], a[14], a[15], db + 64);
  wg_cv_2_1(d, a[12], a[13], a[14], a[15], db + 32);
  wg_cv_1_0(d, a[12], a[13], a[14], a[15], db + 0);
  wg_cv_7_1(d, a[8], a[9], a[10], a[11], db + 208);
  a[32] = lds32(ab + (2048));
  a[33] = lds32(ab + (2176));
  a[34] = lds32(ab + (2032));
  a[35] = lds32(ab + (2160));
  wg_cv_6_1(d, a[8], a[9], a[10], a[11], db + 176);
  wg_cv_5_1(d, a[8], a[9], a[10], a[11], db + 144);
  wg_cv_4_1(d, a[8], a[9], a[10], a[11], db + 112);
  wg_cv_3_1(d, a[8], a[9], a[10], a[11], db + 80);
  a[28] = lds32(ab + (1792));
  a[29] = lds32(ab + (1920));
  a[30] = lds32(ab + (1776));
  a[31] = lds32(ab + (1904));
  wg_cv_2_1(d, a[8], a[9], a[10], a[11], db + 48);
  wg_cv_1_1(d, a[8], a[9], a[10], a[11], db + 16);
  wg_commit();
  wg_cv_7_1(d, a[4], a[5], a[6], a[7], db + 224);
  wg_cv_6_1(d, a[4], a[5], a[6], a[7], db + 192);
  wg_cv_5_1(d, a[4], a[5], a[6], a[7], db + 160);
  wg_cv_4_1(d, a[4], a[5], a[6], a[7], db + 128);
  wg_commit(); wg_wait<1>();
  a[24] = lds32(ab + (1536));
  a[25] = lds32(ab + (1664));
  a[26] = lds32(ab + (1520));
  a[27] = lds32(ab + (1648));
  hand();
  wg_cv_3_1(d, a[4], a[5], a[6], a[7], db + 96);
  wg_cv_2_1(d, a[4], a[5], a[6], a[7], db + 64);
  wg_cv_1_1(d, a[4], a[5], a[6], a[7], db + 32);
  wg_cv_0_0(d, a[4], a[5], a[6], a[7], db + 0);
  a[20] = lds32(ab + (1280));
  a[21] = lds32(ab + (1408));
  a[22] = lds32(ab + (1264));
  a[23] = lds32(ab + (1392));
  wg_cv_7_1(d, a[0], a[1], a[2], a[3], db + 240);
  wg_cv_6_1(d, a[0], a[1], a[2], a[3], db + 208);
  wg_cv_5_1(d, a[0], a[1], a[2], a[3], db + 176);
  wg_cv_4_1(d, a[0], a[1], a[2], a[3], db + 144);
  a[16] = lds32(ab + (1024));
  a[17] = lds32(ab + (1152));
  a[18] = lds32(ab + (1008));
  a[19] = lds32(ab + (1136));
  wg_cv_3_1(d, a[0], a[1], a[2], a[3], db + 112);
  wg_cv_2_1(d, a[0], a[1], a[2], a[3], db + 80);
  wg_cv_1_1(d, a[0], a[1], a[2], a[3], db + 48);
  wg_cv_0_1(d, a[0], a[1], a[2], a[3], db + 16);
  wg_commit();
  a[12] = lds32(ab + (768));
  a[13] = lds32(ab + (896));
  a[14] = lds32(ab + (752));
  a[15] = lds32(ab + (880));
  a[8] = lds32(ab + (512));
  a[9] = lds32(ab + (640));
  a[10] = lds32(ab + (496));
  a[11] = lds32(ab + (624));
}
template <class F, class T> __device__ __forceinline__ void conv_chain_0(float (&d)[128], uint32_t (&a)[64], uint32_t db, uint32_t ao, uint32_t ab, F hand, T dead) {
  wg_cv_7_0(d, a[60], a[61], a[62], a[63], db + 0);
  wg_cv_6_0(d, a[52], a[53], a[54], a[55], db + 0);
  dead();
  wg_cv_7_1(d, a[56], a[57], a[58], a[59], db + 16);
  wg_cv_5_0(d, a[44], a[45], a[46], a[47], db + 0);
  wg_cv_6_1(d, a[48], a[49], a[50], a[51], db + 16);
  wg_cv_7_1(d, a[52], a[53], a[54], a[55], db + 32);
  wg_cv_5_1(d, a[40], a[41], a[42], a[43], db + 16);
  wg_cv_6_1(d, a[44], a[45], a[46], a[47], db + 32);
  wg_cv_7_1(d, a[48], a[49], a[50], a[51], db + 48);
  wg_cv_6_1(d, a[40], a[41], a[42], a[43], db + 48);
  wg_cv_7_1(d, a[44], a[45], a[46], a[47], db + 64);
  wg_cv_7_1(d, a[40], a[41], a[42], a[43], db + 80);
  wg_commit();
  wg_cv_7_1(d, a[36], a[37], a[38], a[39], db + 96);
  wg_cv_6_1(d, a[36], a[37], a[38], a[39], db + 64);
  wg_cv_5_1(d, a[36], a[37], a[38], a[39], db + 32);
  wg_cv_4_0(d, a[36], a[37], a[38], a[39], db + 0);
  wg_cv_7_1(d, a[32], a[33], a[34], a[35], db + 112);
  wg_cv_6_1(d, a[32], a[33], a[34], a[35], db + 80);
  wg_cv_5_1(d, a[32], a[33], a[34], a[35], db + 48);
  wg_cv_4_1(d, a[32], a[33], a[34], a[35], db + 16);
  wg_cv_7_1(d, a[28], a[29], a[30], a[31], db + 128);
  wg_cv_6_1(d, a[28], a[29], a[30], a[31], db + 96);
  wg_cv_5_1(d, a[28], a[29], a[30], a[31], db + 64);
  wg_cv_4_1(d, a[28], a[29], a[30], a[31], db + 32);
  wg_cv_3_0(d, a[28], a[29], a[30], a[31], db + 0);
  wg_cv_7_1(d, a[24], a[25], a[26], a[27], db + 144);
  wg_cv_6_1(d, a[24], a[25], a[26], a[27], db + 112);
  wg_cv_5_1(d, a[24], a[25], a[26], a[27], db + 80);
  wg_cv_4_1(d, a[24], a[25], a[26], a[27], db + 48);
  wg_cv_3_1(d, a[24], a[25], a[26], a[27], db + 16);
  wg_commit();
  wg_cv_7_1(d, a[20], a[21], a[22], a[23], db + 160);
  wg_cv_6_1(d, a[20], a[21], a[22], a[23], db + 128);
  wg_cv_5_1(d, a[20], a[21], a[22], a[23], db + 96);
  wg_cv_4_1(d, a[20], a[21], a[22], a[23], db + 64);
  wg_cv_3_1(d, a[20], a[21], a[22], a[23], db + 32);
  wg_cv_2_0(d, a[20], a[21], a[22], a[23], db + 0);
  wg_cv_7_1(d, a[16], a[17], a[18], a[19], db + 176);
  wg_cv_6_1(d, a[16], a[17], a[18], a[19], db + 144);
  wg_cv_5_1(d, a[16], a[17], a[18], a[19], db + 112);
  wg_cv_4_1(d, a[16], a[17], a[18], a[19], db + 80);
  wg_cv_3_1(d, a[16], a[17], a[18], a[19], db + 48);
  wg_cv_2_1(d, a[16], a[17], a[18], a[19], db + 16);
  wg_cv_7_1(d, a[12], a[13], a[14], a[15], db + 192);
  wg_cv_6_1(d, a[12], a[13], a[14], a[15], db + 160);
  wg_cv_5_1(d, a[12], a[13], a[14], a[15], db + 128);
  wg_cv_4_1(d, a[12], a[13], a[14], a[15], db + 96);
  wg_cv_3_1(d, a[12], a[13], a[14], a[15], db + 64);
  wg_cv_2_1(d, a[12], a[13], a[14], a[15], db + 32);
  wg_cv_1_0(d, a[12], a[13], a[14], a[15], db + 0);
  wg_cv_7_1(d, a[8], a[9], a[10], a[11], db + 208);
  wg_cv_6_1(d, a[8], a[9], a[10], a[11], db + 176);
  wg_cv_5_1(d, a[8], a[9], a[10], a[11], db + 144);
  wg_cv_4_1(d, a[8], a[9], a[10], a[11], db + 112);
  wg_cv_3_1(d, a[8], a[9], a[10], a[11], db + 80);
  wg_cv_2_1(d, a[8], a[9], a[10], a[11], db + 48);
  wg_cv_1_1(d, a[8], a[9], a[10], a[11], db + 16);
  wg_commit();
  wg_cv_7_1(d, a[4], a[5], a[6], a[7], db + 224);
  wg_cv_6_1(d, a[4], a[5], a[6], a[7], db + 192);
  wg_cv_5_1(d, a[4], a[5], a[6], a[7], db + 160);
  wg_cv_4_1(d, a[4], a[5], a[6], a[7], db + 128);
  hand();
  wg_cv_3_1(d, a[4], a[5], a[6], a[7], db + 96);
  wg_cv_2_1(d, a[4], a[5], a[6], a[7], db + 64);
  wg_cv_1_1(d, a[4], a[5], a[6], a[7], db + 32);
  wg_cv_0_0(d, a[4], a[5], a[6], a[7], db + 0);
  wg_cv_7_1(d, a[0], a[1], a[2], a[3], db + 240);
  wg_cv_6_1(d, a[0], a[1], a[2], a[3], db + 208);
  wg_cv_5_1(d, a[0], a[1], a[2], a[3], db + 176);
  wg_cv_4_1(d, a[0], a[1], a[2], a[3], db + 144);
  wg_cv_3_1(d, a[0], a[1], a[2], a[3], db + 112);
  wg_cv_2_1(d, a[0], a[1], a[2], a[3], db + 80);
  wg_cv_1_1(d, a[0], a[1], a[2], a[3], db + 48);
  wg_cv_0_1(d, a[0], a[1], a[2], a[3], db + 16);
  wg_commit();
}
constexpr bool CV_OWN = false;
constexpr int CV_RELOADED = 2;

struct Params {
  const __nv_bfloat16 *q, *k, *v, *shift_k, *ssm_k, *ssm_D, *w1, *b1, *w2, *b2;
  __nv_bfloat16* out;
};
struct Maps { CUtensorMap q0, qa, w1, w1x, k, v, hs, hx, ha, w2, w2x, kvs, qf, y, out; };

__global__ void __cluster_dims__(2, 1, 1) __launch_bounds__(384, 1) h3_kernel(const __grid_constant__ Maps M, const Params P) {
  extern __shared__ __align__(1024) uint8_t smem_raw[];
  constexpr uint32_t sc = 1024;
  const int tid = threadIdx.x, lane = tid & 31;
  if (tid == 0) { prefetch_map(&M.q0); prefetch_map(&M.w1); prefetch_map(&M.w1x); }
  const int warp = __shfl_sync(0xffffffffu, tid >> 5, 0);
  const uint32_t sb = __shfl_sync(0xffffffffu, s32(smem_raw), 0);
  const int b = blockIdx.x, pr = b >> 1;
  const int t7q = ((pr - 36) * 37) >> 8;
  const int G = pr < 4 ? 0 : (pr < 36 ? (pr - 4) & 7 : pr - 35 - 7 * t7q), gi = pr < 4 ? 4 + pr : (pr < 36 ? (pr - 4) >> 3 : 4 + t7q);
  const int kh = b & 1, nt = (G & 1) * 2 + (gi & 1), rb = (G >> 1) * 4 + (gi >> 1);
  const int dir = (G ^ (G >> 1)) & 1, ri = (gi & 1) * 2 + kh, ci = (G >> 2) * 4 + (gi >> 1);
  const uint32_t gmap = (nt & 1) ? 0x03412u : 0x43210u;
  const int j = kh * 4 + nt;
  const uint32_t bar = sb + M_BAR;
  auto BAR = [&](int i) { return bar + 8 * i; };
  auto g1_load = [&](int kc) {
    const uint32_t st = sb + (kc & 3) * G1_STAGE, fb = BAR(B_F1 + (kc & 3));
    const int k0 = dir && kc >= COM ? 576 + COM * 64 - kc * 64 : kc * 64;
    mbar_expect(fb, G1_TX);
    tma2d(st, &M.qa, k0, rb * 128, fb);
    tma3d(st + 16384, &M.w1, 0, k0, 3 * j, fb);
    tma2d(st + 40960, &M.w1x, 1536 + 24 * j, k0, fb);
  };
  auto kv_load = [&](int r, int hf) {
    const uint32_t st = sb + KVS + (r < 3 ? r : r - 3) * KV_BUF, fb = BAR((hf ? B_KIN1 : B_KIN) + r);
    mbar_expect(fb, KV_BUF / 2);
    tma2d(st + 4096 + hf * 2432, &M.k, 128 * r + 64 * (b & 1), 32 * (b >> 1) + 16 * hf - 3, fb);
    tma2d(st + hf * 2048, &M.v, 128 * r + 64 * (b & 1), 32 * (b >> 1) + 16 * hf, fb);
  };
  auto conv_sum = [&](int c, int ck, bool third, uint32_t ep) {
    const uint32_t ra = sb + cv_p(c) + ck * 16;
    __nv_bfloat16* yp = g_yT + (size_t)(128 * c + b) * SL + ck * 8;
    uint4 p[2][4];
    auto ld = [&](int u) {
#pragma unroll
      for (int w = 0; w < 4; w++) p[u & 1][w] = lds128((u == 0 && ck < 2 * w) ? sb + M_ZERO : ra + u * 512 + w * (4096 - 32));
    };
    auto st = [&](int u) {
      auto sum = [&](uint32_t a0, uint32_t a1, uint32_t a2, uint32_t a3) { return badd2(badd2(badd2(a3, a2), a1), a0); };
      const uint4* r = p[u & 1];
      const uint32_t m = ~ck & 1u;
      stg128(yp + u * 256, (sum(r[0].x, r[1].x, r[2].x, r[3].x) & ~m) | (ep & m), sum(r[0].y, r[1].y, r[2].y, r[3].y), sum(r[0].z, r[1].z, r[2].z, r[3].z), sum(r[0].w, r[1].w, r[2].w, r[3].w));
    };
    ld(0); ld(1); st(0);
    if (third) ld(2);
    st(1);
    if (third) st(2);
  };
  if (warp == 8) {
    if (lane == 0) {
      TS(0);
      mbar_init(BAR(B_F0), 1); mbar_init(BAR(B_F1), 1);
    }
    __syncwarp();
    ONE(mbar_expect(BAR(B_F0), G1_TX - 8192);
        tma2d(sb, &M.q0, 0, rb * 128, BAR(B_F0));
        tma3d(sb + 16384, &M.w1, 0, 0, 3 * j, BAR(B_F0));
        tma2d(sb + 40960, &M.w1x, 1536 + 24 * j, 0, BAR(B_F0));
        mbar_expect(BAR(B_F1), 8192);
        tma2d(sb + 8192, &M.q0, 0, rb * 128 + 64, BAR(B_F1));
        for (int s = 1; s < 4; s++) mbar_init(BAR(B_F1 + s), 1));
    bar_arrive(NB_INIT, 384);
  } else if (warp == 9) ONE(prefetch_map(&M.qa));
  if ((sb & 0xFFFFFFu) != sc) { if (warp == 8) { mbar_wait(BAR(B_F0), 0); mbar_wait(BAR(B_F1), 0); } return; }

  if (warp >= 8) {
    asm volatile("setmaxnreg.dec.sync.aligned.u32 " REG_AUX ";");
    auto table = [&](int c, int aw) {
      const uint32_t kb = sb + cv_t(c);
      const uint32_t dd = lds32(sb + M_AUX + aw * 32 + c * 4);
      if (lane < 2) sts128(kb + lane * (KT_E - 16), 0u, 0u, 0u, 0u);
      uint4 r[8];
#pragma unroll
      for (int it = 0; it < 8; it++) r[it] = lds128(kb + KT_E + (it * 32 + lane) * 16);
      if (lane == 0) { r[0].x = __byte_perm(badd2(r[0].x, dd), r[0].x, 0x7610); sts32(kb + KT_E, r[0].x); }
#pragma unroll
      for (int it = 0; it < 8; it++) {
        const uint32_t pv = __shfl_sync(0xffffffffu, lane == 31 ? (it ? r[it ? it - 1 : 0].w : 0u) : r[it].w, lane - 1);
        sts128(kb + KT_O + (it * 32 + lane) * 16, __byte_perm(pv, r[it].x, 0x5432), __byte_perm(r[it].x, r[it].y, 0x5432),
               __byte_perm(r[it].y, r[it].z, 0x5432), __byte_perm(r[it].z, r[it].w, 0x5432));
      }
      __syncwarp();
      if (lane == 0) mbar_arrive(BAR(B_KT + c));
    };
    const int aw = warp - 9, at = tid - 288;
    auto x_load = [&](int c) { mbar_expect(BAR(B_XL + c), 4096); bulk_g2s(sb + cv_x(c) + XD, g_kvT + (size_t)(128 * c + b) * SL, 4096, BAR(B_XL + c)); };
    auto x_pad = [&](int c0, int c1) {
      if (lane < 17) for (int c = c0; c < c1; c++) sts128(sb + cv_x(c) + lane * 16, 0u, 0u, 0u, 0u);
      fence_async_smem();
      __syncwarp();
    };
    if (warp == 8) {
      ONE(g1_load(1); g1_load(2); g1_load(3));
      bar_sync(NB_INIT2, 128);
      unsigned ep;
#pragma unroll
      for (int kc = 3; kc < 10; kc++) {
        if (kc == 9) {
          bar_sync(NB_INIT3, 64);
          ep = lds32(sb + M_AUX + 20);
          mbar_wait(BAR(B_RED), 0);
          float2 u[8];
#pragma unroll
          for (int i = 0; i < 8; i++) u[i] = lds64f(sb + M_RED0 + (lane & 15) * 128 + ((i + lane) & 7) * 16 + (lane >> 4) * 8);
          const float c = bf_round(u[0].x * (1.f / 40)), cc = 40.f * c * c;
          float s1 = 0.f, s2 = 0.f;
#pragma unroll
          for (int i = 0; i < 8; i++) { s1 += fmaf(-40.f, c, u[i].x); s2 += fmaf(-2.f * c, u[i].x, u[i].y) + cc; }
          const float dm = s1 * (1.f / 320);
          st_relaxed64(&g_stat[dir * SL + rb * 128 + ri * 32 + lane], tagged(c + dm, ep), tagged(fmaf(-dm, s1, s2), ep));
          ONE(mbar_arrive(BAR(B_RD)));
        }
        if (kc > 3) mbar_wait(BAR(B_E1 + (kc & 3)), (kc >> 3) & 1);
        ONE(if (kc > 3) g1_load(kc);
            for (int r = 0; r < 3; r++) if (kc == ((KV_MAP >> (4 * r)) & 15)) { kv_load(r, 0); kv_load(r, 1); }
            for (int c = 0; c < 5; c++) if (kc == ((PF_RAW >> (4 * c)) & 15)) prefetch_l2(P.ssm_k + (size_t)(128 * c + b) * SL, 4096));
      }
      ONE(prefetch_map(&M.hs); prefetch_map(&M.hx); prefetch_map(&M.ha); prefetch_map(&M.w2); prefetch_map(&M.w2x));
      {
        mbar_wait(BAR(CS_WAIT ? B_FR : B_F1), 0);
        uint32_t x[16], n = 0;
#pragma unroll 1
        while (true) {
          uint32_t bad = 0;
#pragma unroll
          for (int i = 0; i < 4; i++) {
            const uint4 v = ld_relaxed128(g_stat + (i >> 1) * SL + rb * 128 + lane * 4 + (i & 1) * 2);
            x[4 * i] = v.x; x[4 * i + 1] = v.y; x[4 * i + 2] = v.z; x[4 * i + 3] = v.w;
          }
#pragma unroll
          for (int i = 0; i < 16; i++) { x[i] ^= ep & 15u; bad |= x[i]; }
          if (__all_sync(0xffffffffu, (bad & 15u) == 0) || spin_guard(n, 0x132)) break;
          RETRY(9);
        }
        uint32_t st[4];
#pragma unroll
        for (int i = 0; i < 4; i++) {
          const float ma = __uint_as_float(x[2 * i]), mb = __uint_as_float(x[8 + 2 * i]), dl = ma - mb;
          const float m2 = fmaf(dl * dl, 160.f, __uint_as_float(x[1 + 2 * i]) + __uint_as_float(x[9 + 2 * i]));
          const float vb = bf_round(fmaxf(m2, 0.f) * (1.f / DM));
          st[i] = pack_bf16(0.5f * (ma + mb), sqrt_fast(bf_round(vb + 1e-5f)));
        }
        sts128(sb + M_STAT + lane * 16, st[0], st[1], st[2], st[3]);
        __syncwarp();
        ONE(mbar_arrive(BAR(B_BX)));
      }
    } else {
      if (aw == 0) {
        if (lane == 0) {
#pragma unroll
          for (int s = 0; s < 4; s++) { mbar_init(BAR(B_E1 + s), 8); mbar_init(BAR(B_FR + s), 8); mbar_init(BAR(B_F2 + s), 1); mbar_init(BAR(B_E2 + s), 8); }
          mbar_init(BAR(B_KRAW), 1); mbar_init(BAR(B_KRAW + 1), 1);
          mbar_init(BAR(B_LNI), 4); mbar_init(BAR(B_RED), 4); mbar_init(BAR(B_RED1), 4); mbar_init(BAR(B_RD), 1); mbar_init(BAR(B_BX), 2);
        }
      } else if (aw == 1) {
        if (lane == 0) {
#pragma unroll
          for (int c = 0; c < 5; c++) { if (c == 0) { mbar_init(BAR(B_SK), 1); mbar_init(BAR(B_KD), 2); } mbar_init(BAR(B_XL + c), 1); mbar_init(BAR(B_KT + c), 1); mbar_init(BAR(B_XF + c), 1); mbar_init(BAR(B_SD + c), 4); }
        }
      } else if (lane == 0) {
#pragma unroll
        for (int i = 0; i < 8; i++) mbar_init(BAR(B_HB + i), 4);
#pragma unroll
        for (int c = 0; c < 3; c++) mbar_init(BAR(B_RF + c), 3);
        for (int r = 0; r < 5; r++) { mbar_init(BAR(B_KIN + r), 1); mbar_init(BAR(B_KIN1 + r), 1); }
        for (int i = 0; i < 3; i++) { mbar_init(BAR(B_YSLOT + i), 1); mbar_init(BAR(B_YL + i), 1); } mbar_init(BAR(B_XR), 1);
        for (int i = 0; i < 5; i++) mbar_init(BAR(B_OUT + i), 4);
        mbar_init(BAR(B_XD), 1); mbar_expect(BAR(B_XD), XD_N * 2048); mbar_init(BAR(B_XD + 1), 1); mbar_expect(BAR(B_XD + 1), (XD_M - XD_N) * 2048);
        mbar_init(BAR(B_XD + 2), 1); mbar_expect(BAR(B_XD + 2), (10 - XD_M) * 2048);
        asm volatile("fence.mbarrier_init.release.cluster;" ::: "memory");
        mbar_init(BAR(B_TD + 1), 8); mbar_init(BAR(B_FINQ), 1); mbar_init(BAR(B_FINY), 3);
      }
      __syncwarp();
      bar_arrive(NB_INIT, 384);
      if (aw == 1) ONE(prefetch_map(&M.k); prefetch_map(&M.v); mbar_expect(BAR(B_SK), 2560);
                       for (int r = 0; r < 5; r++) bulk_g2s(sb + M_SK + r * 512, P.shift_k + (128 * r + 64 * (b & 1)) * 4, 512, BAR(B_SK)));
      const uint32_t dv0 = ld_relaxed32(lane < 5 ? static_cast<const void*>(P.ssm_D + 128 * lane + (b & ~1)) : &g_launch[b * 8]);
      const uint32_t b2v = ldg32(reinterpret_cast<const uint32_t*>(P.b2 + nt * 160) + ((gmap >> (4 * (min(at, 79) >> 4))) & 7) * 16 + (at & 15));
      const int l27 = min(lane, 26), col = l27 < 24 ? 192 * j + 8 * l27 : 1536 + 24 * j + 8 * (l27 - 24);
      uint4 bb;
      if (aw == 2) bb = ldg128(P.b1 + col);
      bar_sync(NB_INIT2, 128);
      if (aw == 0) ONE(prefetch_map(&M.kvs));
      if (lane < 4) sts32(sb + M_ZERO + lane * 4, 0u);
      if (lane < 8) sts32(sb + M_AUX + aw * 32 + lane * 4, lane >= 5 ? dv0 + 1 : ((b & 1) ? dv0 >> 16 : dv0 & 0xFFFFu));
      if (at < 80) sts64f(sb + M_B2 + at * 8, 0.5f * bf_lo(b2v), 0.5f * bf_hi(b2v));
      __syncwarp();
      if (aw == 0) bar_arrive(NB_INIT3, 64);
      if (aw == 2) {
        const unsigned ep = lds32(sb + M_AUX + 64 + 20);
        const uint32_t ba = sb + M_BX + (l27 >> 2) * 512 + ((l27 & 3) << 4);
        mbar_wait(BAR(B_RED1), 0);
        const uint32_t tg = ep & 15u;
        float c0 = 0.f, c1 = 0.f;
#pragma unroll
        for (int i = 0; i < 16; i += 2) { c0 += __uint_as_float(lds32(sb + M_RED1 + i * 128 + lane * 4)); c1 += __uint_as_float(lds32(sb + M_RED1 + i * 128 + 128 + lane * 4)); }
        st_relaxed32(&g_cs[(dir * 8 + j) * 256 + ci * 32 + lane], tagged(c0 + c1, ep));
        if (lane == 0) TS(30);
        mbar_wait(BAR(B_RD), 0);
        sts128((ba + 128) ^ 16, 0u, 0u, 0u, 0u); sts128((ba + 192) ^ 16, bb.x, bb.y, bb.z, bb.w);
#pragma unroll
        for (int i = 4; i < 8; i++) sts128((ba + i * 64) ^ ((i >> 1) << 4), 0u, 0u, 0u, 0u);
        mbar_wait(BAR(CS_WAIT ? B_FR : B_F1), 0);
        auto raw_load = [&]() {
          if (!CS_WAIT) mbar_wait(BAR(B_FR), 0);
          ONE(mbar_expect(BAR(B_KRAW), KRAW_N * 4096); mbar_expect(BAR(B_KRAW + 1), (5 - KRAW_N) * 4096);
              for (int c = 0; c < 5; c++) bulk_g2s(sb + cv_t(c) + KT_E, P.ssm_k + (size_t)(128 * c + b) * SL, 4096, BAR(B_KRAW + (c >= KRAW_N))));
        };
        uint32_t x[16], n = 0;
#pragma unroll 1
        while (true) {
#pragma unroll
          for (int i = 0; i < 4; i++) {
            const uint4 v = ld_relaxed128(g_cs + ((i >> 1) * 8 + j) * 256 + l27 * 8 + (i & 1) * 4);
            x[4 * i] = v.x; x[4 * i + 1] = v.y; x[4 * i + 2] = v.z; x[4 * i + 3] = v.w;
          }
          if (!RAW_LATE && n == 0) raw_load();
          uint32_t bad = 0;
#pragma unroll
          for (int i = 0; i < 16; i++) { x[i] ^= tg; bad |= x[i]; }
          if (__all_sync(0xffffffffu, (bad & 15u) == 0) || spin_guard(n, 0x131)) break;
          RETRY(8);
        }
        if (RAW_LATE) raw_load();
        uint32_t hi[4], lo[4];
#pragma unroll
        for (int i = 0; i < 4; i++) {
          const float x0 = __uint_as_float(x[2 * i]) + __uint_as_float(x[8 + 2 * i]), x1 = __uint_as_float(x[2 * i + 1]) + __uint_as_float(x[9 + 2 * i]);
          hi[i] = pack_bf16(x0, x1); lo[i] = pack_bf16(x0 - bf_lo(hi[i]), x1 - bf_hi(hi[i]));
        }
        sts128(ba, hi[0], hi[1], hi[2], hi[3]); sts128(ba + 64, lo[0], lo[1], lo[2], lo[3]);
        fence_async_smem();
        __syncwarp();
        ONE(mbar_arrive(BAR(B_BX)); TS(54));
      }
      if (aw < 2) {
        auto done = [&](int r) {
          bulk_wait_read();
          ONE(kv_load(r + 3, aw); TSKV);
        };
        const uint32_t par = lds32(sb + M_AUX + aw * 32 + 20) & 1u;
        bool pend = false;
        mbar_wait(BAR(B_SK), 0);
#pragma unroll 1
        for (int r = 0; r < 5; r++) {
          const int c0 = 128 * r + 64 * (b & 1);
          const uint32_t buf = sb + KVS + (r < 3 ? r : r - 3) * KV_BUF, stg = buf + aw * 2048, vb = stg + lane * 4, kb = buf + 4096 + aw * 2432 + lane * 4;
          const uint4 sk = lds128(sb + M_SK + r * 512 + lane * 16);
          const uint32_t w0 = __byte_perm(sk.x, sk.z, 0x5410), w1 = __byte_perm(sk.x, sk.z, 0x7632);
          const uint32_t w2 = __byte_perm(sk.y, sk.w, 0x5410), w3 = __byte_perm(sk.y, sk.w, 0x7632);
          mbar_wait(BAR((aw ? B_KIN1 : B_KIN) + r), 0);
          if (at == 0 && r == 0) TS(56);
          uint32_t kk[19], o[16];
#pragma unroll
          for (int i = 0; i < 19; i++) { kk[i] = lds32(kb + i * 128); if (i >= 3) o[i - 3] = lds32(vb + (i - 3) * 128); }
#pragma unroll
          for (int i = 0; i < 16; i++) o[i] = bmul2(bfma2(kk[i + 3], w0, bfma2(kk[i + 2], w1, bfma2(kk[i + 1], w2, bmul2(kk[i], w3)))), o[i]);
          __syncwarp();
          const uint32_t a0 = stg + lane * 64 + ((lane & 6) << 3);
          const uint32_t s0 = (lane & 4) ? 0x7632 : 0x5410, s1 = s0 ^ 0x2222;
#pragma unroll
          for (int hh = 0; hh < 2; hh++) {
            const uint32_t* u = o + 8 * hh;
            const uint32_t a = a0 ^ (hh << 4);
            auto nz = [&](uint32_t x) { return hh ? x : (x & ~1u) | par; };
            sts128(a, nz(__byte_perm(u[1], u[0], s0)), __byte_perm(u[3], u[2], s0), __byte_perm(u[5], u[4], s0), __byte_perm(u[7], u[6], s0));
            sts128(a ^ 32, nz(__byte_perm(u[1], u[0], s1)), __byte_perm(u[3], u[2], s1), __byte_perm(u[5], u[4], s1), __byte_perm(u[7], u[6], s1));
          }
          if (pend) done(r - 1);
          fence_async_smem();
          __syncwarp();
          ONE(tma2d_st(&M.kvs, 32 * (b >> 1) + 16 * aw, c0, stg); bulk_commit());
          pend = r < 2 && mbar_test(BAR((aw ? B_KIN1 : B_KIN) + r + 1), 0);
          if (!pend && r < 2) done(r);
        }
      }
      if (aw == 2) {
        mbar_wait(BAR(B_FR + 1), 0);
        ONE(x_load(0));
        x_pad(0, 4);
      }
    }
#pragma unroll 1
    for (uint32_t t = (TB_MAP >> (8 * (warp - 8))) & 255; t & 15; t >>= 4) {
      const int c = (t & 15) - 1;
      mbar_wait(BAR(B_KRAW + (c >= KRAW_N)), 0);
      if (lane == 0 && c == 1) TS(35);
      table(c, max(aw, 0));
      if (lane == 0 && c == 2) TS(55);
    }
    const unsigned ep = lds32(sb + M_AUX + max(aw, 0) * 32 + 20);
    if (warp == 8) {
      const int hc = j * 192, hx = 1536 + j * 24;
#pragma unroll 1
      for (int n = 0; n < 32; n += 4) {
        const int i = (H_ORD >> n) & 7, hw = i >> 2, blk = i & 3;
        if (n == 4 * W2_PF) ONE(prefetch_l2(P.w2 + (size_t)b * (FF * DM / NCTA), FF * DM / NCTA * 2));
        mbar_wait(BAR(B_HB + i), 0);
        fence_async_smem();
        asm volatile("cp.async.bulk.wait_group %0;" ::"n"(H_FLY - 1) : "memory");
        ONE(tma2d_st(blk < 3 ? &M.hs : &M.hx, blk < 3 ? hc + blk * 64 : hx, rb * 128 + hw * 64, sb + hw * HST + blk * 8192); bulk_commit());
      }
      const int cf = (nt * 160 + (nt & 1) * 32) >> 6, ch = (nt >> 1) * 320 + 128;
      auto g2_k = [&](int kc) { return (kc < NSH ? kh * NSH + kc : NSH + kc) * 64; };
      auto g2_load_b = [&](int kc) {
        const int s = kc & 3;
        const uint32_t fb = BAR(B_F2 + s);
        mbar_expect(fb, kc >= NSH ? 8192 + 24576 : 16384 + 24576);
        tma3d(sb + g2_b(s), &M.w2, 0, g2_k(kc), cf, fb);
        tma2d(sb + g2_b(s) + 16384, &M.w2x, ch, g2_k(kc), fb);
      };
      auto g2_load_a = [&](int kc) {
        const int s = kc & 3, o = kc >= NSH ? kh : 0;
        tma2d(sb + g2_a(s) + o * 8192, kc >= NSH ? &M.hs : &M.ha, g2_k(kc), rb * 128 + o * 64, BAR(B_F2 + s));
      };
      bulk_wait_all();
      ONE(g2_load_b(0); g2_load_b(1));
      fence_release();
      ONE(signal_cnt(CNT_H + rb); TS(37));
      wait_cnt(CNT_H + rb, 8 * ep);
      ONE(TS(39); g2_load_a(0); g2_load_a(1); prefetch_map(&M.qf); prefetch_map(&M.y); prefetch_map(&M.out));
      mbar_wait(BAR(B_KD), 0);
      ONE(g2_load_b(3));
      mbar_wait(BAR(B_TD + 1), 0);
      fence_async_smem();
      ONE(g2_load_b(2); g2_load_a(2));
      mbar_wait(BAR(B_SD + 3), 0);
      ONE(mbar_expect(BAR(B_FINQ), 20480);
          for (int i = 0; i < 5; i++) tma2d(sb + FIN_Q + i * 4096, &M.qf, nt * 160 + ((gmap >> (4 * i)) & 7) * 32, rb * 128 + kh * 64, BAR(B_FINQ)));
      mbar_wait(BAR(B_RF + 2), 0);
      ONE(g2_load_a(3); TS(38));
#pragma unroll 1
      for (int kc = 4; kc < NST; kc++) {
        mbar_wait(BAR(B_E2 + (kc & 3)), ((kc >> 2) - 1) & 1);
                ONE(g2_load_a(kc); g2_load_b(kc); if (kc >= Y_KC && kc < Y_KC + 3) mbar_arrive(BAR(B_YSLOT + kc - Y_KC)));
      }
      if (lane == 0) g_launch[b * 8] = ep;
#pragma unroll 1
      for (int i = 0; i < 5; i++) {
        const int gi = (gmap >> (4 * i)) & 7;
        mbar_wait(BAR(B_OUT + i), 0);
        fence_async_smem();
        ONE(tma2d_st(&M.out, nt * 160 + gi * 32, rb * 128 + kh * 64, sb + FIN_Q + i * 4096));
      }
      ONE(bulk_commit());
      bulk_wait_read();
    } else {
      if (aw < 2) { bulk_wait_read(); ONE(mbar_arrive(BAR(B_KD)); if (aw == 0) TS(34)); }
      if (aw == 2) {
#pragma unroll 1
        for (int c = 0, n = 0; c < 5;) {
          if (n == 0 && c < 4) {
            mbar_wait(BAR((X_TRIG >> (8 * c)) & 255), 0);
            if (c == 3) { mbar_wait(BAR(B_KD), 0); x_pad(4, 5); }
          }
          if (n || c < 4) ONE(x_load(n ? c : c + 1));
          mbar_wait(BAR(B_XL + c), n & 1);
          const uint32_t a = sb + cv_x(c) + XD + lane * 32;
          const uint32_t v = ((lds32(a) ^ ep) | (lds32(a + 1024) ^ ep) | (lds32(a + 2048) ^ ep) | (lds32(a + 3072) ^ ep)) & 1u;
          if (__all_sync(0xffffffffu, v == 0) || n > 100000) {
            ONE(mbar_arrive(BAR(B_XF + c)); if (c == 0) TS(36); if (c >= 3) TS(28 + c));
            c++; n = 0;
          } else {
            n++;
            RETRY(c);
          }
        }
      }
      if (RED_GATE) mbar_wait(BAR(RED_GATE == 1 ? B_TD + 1 : B_SD + RED_GATE - 1), 0);
#pragma unroll 1
      for (int c = 0; c < 5; c++) {
        mbar_wait(BAR(B_SD + c), 0);
        conv_sum(c, aw * 96 + lane, aw < 2, ep);
        __syncwarp();
        if (c < 3 && lane == 0) mbar_arrive(BAR(B_RF + c));
        if (at == 0) TS(59 + c);
      }
      bar_sync(NB_AUX, 96);
      if (aw == 0) ONE(mbar_arrive_remote(mapa(BAR(B_XR), kh ^ 1)); TS(3));
      auto ytab = [](int a) { return (uint32_t)(fin_y(3 * a) >> 10 | fin_y(3 * a + 1) >> 10 << 8 | fin_y(3 * a + 2) >> 10 << 16 | fin_y(a == 2 ? 9 : 3 * a) >> 10 << 24); };
      const uint32_t yt = aw == 0 ? ytab(0) : (aw == 1 ? ytab(1) : ytab(2));
      mbar_wait(BAR(B_YSLOT + aw), 0);
#pragma unroll 1
      for (int n = 0;; n++) {
        ONE(mbar_expect(BAR(B_YL + aw), aw == 2 ? 8192 : 6144));
#pragma unroll 1
        for (int i = 0; i < (aw == 2 ? 4 : 3); i++) {
          const int np = 3 * aw + i;
          ONE(tma2d(sb + (((yt >> (8 * i)) & 255) << 10), &M.y, rb * 128 + kh * 64, nt * 160 + ((gmap >> (4 * (np >> 1))) & 7) * 32 + (np & 1) * 16, BAR(B_YL + aw)));
        }
        mbar_wait(BAR(B_YL + aw), n & 1);
        uint32_t bad = 0;
#pragma unroll
        for (int i = 0; i < 4; i++) {
          const uint32_t a = sb + (((yt >> (8 * i)) & 255) << 10) + (lane >> 2) * 128 + ((((lane & 3) * 2) ^ (lane >> 2)) << 4);
          bad |= (lds32(a) ^ ep) | (lds32(a + 1024) ^ ep);
        }
        if (__all_sync(0xffffffffu, (bad & 1u) == 0) || n > 100000) break;
        RETRY(5 + aw);
        if (lane == 0) TS(33);
      }
      ONE(mbar_arrive(BAR(B_FINY)); if (aw == 2) TS(40));
    }
  } else {
    if (INC_KC < 0) asm volatile("setmaxnreg.inc.sync.aligned.u32 " REG_CON ";");
    const int wg = warp >> 2, w = warp & 3, g = lane >> 2, q = lane & 3;
    constexpr bool elect = false;
    uint32_t ca[64];
    const uint32_t ab0 = sb + ((g & 1) ? KT_E : KT_O) + (8 * w + 4 + (g >> 1) - q) * 4;
    auto conv_lda = [&](int c, int k0, int k1) {
      const uint32_t ab = ab0 + cv_t(c);
#pragma unroll
      for (int ks = 15; ks >= 0; ks--) {
        if (ks >= k0 && ks < k1) {
          ca[4 * ks + 0] = lds32(ab + ks * 256);
          ca[4 * ks + 1] = lds32(ab + ks * 256 + 128);
          ca[4 * ks + 2] = lds32(ab + ks * 256 - 16);
          ca[4 * ks + 3] = lds32(ab + ks * 256 + 112);
        }
      }
    };
    {
      float d[108];
      bool stag = false;
      auto g1_release = [&](int kc) { if (lane == 0) mbar_arrive(BAR(kc < 6 ? B_E1 + (kc & 3) : B_FR + kc - 6)); };
      auto g1_wait = [&](int kc) { mbar_wait(BAR(B_F1 + (kc & 3)), (kc >> 2) & 1); };
      auto g1_issue = [&](int kc) {
        const int s = kc & 3;
        if (kc == 0) { if (wg == 1) { mbar_wait(BAR(B_F1), 0); bar_sync(NB_LEAD, 256); } mbar_wait(BAR(B_F0), 0); }
        if (tid == 0) TS(8 + kc);
        const uint32_t st = sc + s * G1_STAGE;
        const uint64_t da = mkdesc(st + wg * 8192, 16, 1024, 1), db = mkdesc(st + 16384, 8192, 1024, 1);
        wg_fence();
#pragma unroll
        for (int k = 0; k < 4; k++) {
          wg_ss_216(d, da + k * 2, db + k * 128, (kc | k) != 0);
          if (k == REL_K || k == 3) wg_commit();
          if (k == REL_K && kc > 0) { wg_wait<1>(); if (kc != STAG_KC + 1 || !stag) g1_release(kc - 1); }
        }
        if (kc == 0 && wg == 0) bar_arrive(NB_LEAD, 256);
      };
      const int t7 = tid & 127, wr = ((t7 >> 3) & 1) * 4 + (t7 >> 4) * 8, wc = 4 * min(ci, 6) + ((t7 >> 1) & 3);
      const uint32_t sa0 = sb + (wg ? 16384 + (wc >> 3) * 8192 + wr * 128 + (((wc ^ wr) & 7) << 4) + (t7 & 1) * 8 : ri * 4096 + t7 * 16);
      float t1 = 0.f, t2 = 0.f, t3 = 0.f, t4 = 0.f;
      auto piece = [&](int i) {
        const uint32_t so = (i & 3) * G1_STAGE;
        if (wg == 0) {
          const uint4 x = lds128(sa0 + so), y = lds128(sa0 + so + 2048);
          const uint32_t xx[4] = {x.x, x.y, x.z, x.w}, yy[4] = {y.x, y.y, y.z, y.w};
#pragma unroll
          for (int e = 0; e < 4; e++) {
            const float u = bf_lo(xx[e]), v = bf_hi(xx[e]), r = bf_lo(yy[e]), z = bf_hi(yy[e]);
            t1 += u; t2 = fmaf(u, u, t2); t3 += r; t4 = fmaf(r, r, t4);
            t1 += v; t2 = fmaf(v, v, t2); t3 += z; t4 = fmaf(z, z, t4);
          }
        } else {
          float2 xx[4];
#pragma unroll
          for (int e = 0; e < 4; e++) xx[e] = lds64f((sa0 ^ (e * 144)) + so);
#pragma unroll
          for (int e = 0; e < 4; e++) {
            const uint32_t u = __float_as_uint(xx[e].x), v = __float_as_uint(xx[e].y);
            t1 += bf_lo(u); t2 += bf_hi(u); t3 += bf_lo(v); t4 += bf_hi(v);
          }
        }
      };
      bar_sync(NB_INIT, 384);
#pragma unroll
      for (int kc = 0; kc < 10; kc++) {
        g1_issue(kc);
        if (kc < 5 && (kc >= COM || kc == dir)) { g1_wait(kc); piece(kc); }
        if (kc == 5 - PEEK) {
          if (dir || COM == 2) { g1_wait(5); piece(5); }
          sts128(sb + (wg ? M_RED1 : M_RED0) + t7 * 16, __float_as_uint(t1), __float_as_uint(t2), __float_as_uint(t3), __float_as_uint(t4));
          __syncwarp();
          if (lane == 0) mbar_arrive(BAR(wg ? B_RED1 : B_RED));
        }
        if (kc == INC_KC) asm volatile("setmaxnreg.inc.sync.aligned.u32 " REG_CON ";");
        if (kc < 9) g1_wait(kc + 1);
        if (kc == STAG_KC && wg == 1 && (STAG_ALL || mbar_test(BAR(B_BX), 0))) {
          if (STAG_REL) { wg_wait<0>(); g1_release(kc); stag = true; }
          mbar_wait(BAR(B_LNI), 0);
        }
      }
      uint2 s0, s1;
      {
        mbar_wait(BAR(B_BX), 0);
        s0.x = lds32(sb + M_STAT + (wg * 64 + w * 16 + g) * 4); s1.x = lds32(sb + M_STAT + (wg * 64 + w * 16 + g + 8) * 4);
        if (tid == 0) TS(46);
        const uint32_t f0 = q == 0 ? ((s0.x & 0xFFFFu) * 0x10001u) ^ 0x80008000u : (q == 1 ? s0.x ^ 0x8000u : 0u);
        const uint32_t f1 = q == 0 ? ((s1.x & 0xFFFFu) * 0x10001u) ^ 0x80008000u : (q == 1 ? s1.x ^ 0x8000u : 0u);
        wg_fence();
        wg_rs_216(d, f0, f1, 0u, 0u, mkdesc(sc + M_BX, 512, 0, 2));
        wg_commit();
        if (wg == 0 && lane == 0) mbar_arrive(BAR(B_LNI));
      }
      wg_wait<1>();
      if (lane == 0) mbar_arrive(BAR(B_FR + 3));
      const float r0 = rcp_fast(bf_hi(s0.x)), r1 = rcp_fast(bf_hi(s1.x));
      constexpr float C1 = 0.7978845608028654f, C2 = 0.7978845608028654f * 0.044715f;
      const float ga0 = C1 * r0, gb0 = C2 * r0 * r0 * r0, ga1 = C1 * r1, gb1 = C2 * r1 * r1 * r1;
      if (wg == 0) mbar_wait(BAR(B_FR + 2), 0);
      wg_wait<0>();
      if (elect) TS(1 + 47 * wg);
      if (wg == 1) bar_sync(NB_GELU, 256);
      sched_fence(sb);
      const int mi = lane >> 3, row = w * 16 + (mi & 1) * 8 + (lane & 7);
      const uint32_t hs = sb + wg * HST;
      float u[2][8];
#pragma unroll
      for (int st = -1; st < 15; st++) {
        const int nb = 2 * (st - 1);
        if (st >= 1) {
          uint32_t p[4];
#pragma unroll
          for (int e = 0; e < (nb < 26 ? 4 : 2); e++) {
            const float x = d[4 * nb + 2 * e], y = d[4 * nb + 2 * e + 1];
            p[e] = pack_bf16(fmaf(x, u[(st - 1) & 1][2 * e], x), fmaf(y, u[(st - 1) & 1][2 * e + 1], y));
          }
          const int nbm = nb + (mi >> 1);
          if (nb < 24) stsm4(hs + (nb >> 3) * 8192 + row * 128 + (((nbm & 7) ^ (row & 7)) << 4), p[0], p[1], p[2], p[3]);
          else if (nb == 24) stsm4(hs + 24576 + row * 48 + (mi >> 1) * 16, p[0], p[1], p[2], p[3]);
          else stsm2(hs + 24576 + row * 48 + 32, p[0], p[1]);
          if ((nb & 7) == 6 || nb == 26) {
            __syncwarp();
            if (lane == 0) mbar_arrive(BAR(B_HB + wg * 4 + (nb >> 3)));
          }
        }
        if (st >= 0 && st < 14) {
#pragma unroll
          for (int i = 0; i < (st < 13 ? 8 : 4); i++) u[st & 1][i] = tanh_fast(u[st & 1][i]);
        }
        if (st + 1 < 14) {
#pragma unroll
          for (int i = 0; i < (st + 1 < 13 ? 8 : 4); i++) {
            const float x = d[8 * (st + 1) + i];
            u[(st + 1) & 1][i] = x * fmaf(x * ((i & 2) ? gb1 : gb0), x, (i & 2) ? ga1 : ga0);
          }
        }
        constexpr int S0 = A_NB0 / 2, NK = CV_OWN ? 16 - CV_RELOADED : 16;
        if (st >= S0 && st < 14) conv_lda(wg, 16 - (st + 1 - S0) * NK / (14 - S0), 16 - (st - S0) * NK / (14 - S0));
        if (2 * st == GELU_NB && wg == 0) bar_arrive(NB_GELU, 256);
        if (st + 1 == S0) mbar_wait(BAR(B_KT + wg), 0); else if (st < 14 && (st + 1) % SCH == 0) sched_fence(sb);
      }
      if (elect) TS(2 + 47 * wg);
    }
#pragma unroll 1
    for (int c = wg; c < 5; c += 2) {
      float d[128];
      mbar_wait(BAR(B_XF + c), 0);
      if (c < 3) mbar_wait(BAR(B_KT + c + 2), 0);
      const uint64_t db = mkdesc(sc + cv_x(c), 16, 128, 0);
      if (c > 0) { if (wg) bar_sync(NB_TURN + 1, 256); else bar_sync(NB_TURN, 256); }
      wg_fence();
      auto hand = [&]() { if (wg) bar_arrive(NB_TURN, 256); else if (c < 4 || !HAND4) bar_arrive(NB_TURN + 1, 256); };
      const uint32_t ao = ab0 + cv_t(c);
      if (c < 3) conv_chain_1(d, ca, db, ao, ao + 2 * KT_CH, hand, []() {});
      else conv_chain_0(d, ca, db, ao, 0, hand, [&]() { if (lane == 0) mbar_arrive(BAR(B_TD + 1)); });
      if (c == 4 && HAND4) bar_arrive(NB_TURN + 1, 256);
      mbar_wait(BAR(c >= 3 ? B_RF + c - 3 : B_FR + 3), 0);
      wg_wait<0>();
      if (elect) TS(41 + c);
      if (c < 3 && !CV_OWN) conv_lda(c + 2, 0, CV_RELOADED);
      const uint32_t wa = sb + cv_p(c) + w * 4096 + lane * 16;
#pragma unroll
      for (int n4 = 0; n4 < 32; n4 += 4) {
        uint32_t p[4];
#pragma unroll
        for (int e = 0; e < 4; e++) {
          const int nb = n4 + e;
          float x = d[4 * nb], y = d[4 * nb + 1];
          if (nb > 0) { x += d[4 * nb - 2]; y += d[4 * nb - 1]; }
          p[e] = pack_bf16(x, y);
        }
        stsm4t(wa + n4 * 128, p[0], p[1], p[2], p[3]);
      }
      __syncwarp();
      if (lane == 0) mbar_arrive(BAR(B_SD + c));
    }
    if (elect) TS(51 + wg);
    {
      float d[80];
      const uint32_t aoff = (wg ^ kh) * 8192;
      const uint64_t boff = (uint64_t)(nt & 1) << 51;
      const uint32_t s0 = lds32(sb + M_STAT + ((wg ^ kh) * 64 + w * 16 + g) * 4), s1 = lds32(sb + M_STAT + ((wg ^ kh) * 64 + w * 16 + g + 8) * 4);
      auto g2_release = [&](int kc) { if (lane == 0) mbar_arrive(BAR(B_E2 + (kc & 3))); };
      auto g2_mma_w = [&](int kc, int first, bool rel, auto side) {
        const int s = kc & 3;
        mbar_wait(BAR(B_F2 + s), (kc >> 2) & 1);
        const uint64_t da = mkdesc(sc + g2_a(s) + aoff, 16, 1024, 1), db = mkdesc(sc + g2_b(s), 8192, 1024, 1) | boff;
        wg_fence();
#pragma unroll
        for (int k = 0; k < 4; k++) {
          wg_ss_160(d, da + k * 2, db + k * 128, k ? 1 : first);
          if ((k == REL_K && rel) || k == 3) wg_commit();
          if (k == REL_K && rel) { wg_wait<1>(); g2_release(kc - 1); }
          side(k);
        }
      };
      auto g2_mma = [&](int kc, int first, bool rel) { g2_mma_w(kc, first, rel, [](int) {}); };
      sched_fence(sb);
      if (wg == 1) bar_sync(NB_TURN + 1, 256);
      g2_mma(0, 0, false);
      if (wg == 0) bar_arrive(NB_LEAD, 256);
#pragma unroll
      for (int kc = 1; kc < XP_KC; kc++) {
        if (tid == 0) TS(17 + kc);
        if (kc == LEAD_KC && wg == 1) bar_sync(NB_LEAD, 256);
        g2_mma(kc, 1, true);
      }
      if (wg == 1) {
        float bi[40];
#pragma unroll
        for (int nb = 0; nb < 20; nb++) { const float2 v = lds64f(sb + M_B2 + nb * 32 + q * 8); bi[2 * nb] = v.x; bi[2 * nb + 1] = v.y; }
        const float c0 = 0.25f * rcp_fast(bf_hi(s0)), c1 = 0.25f * rcp_fast(bf_hi(s1));
#pragma unroll
        for (int kc = XP_KC; kc < NSH; kc++) {
          g2_mma(kc, 1, kc < NST - 3);
          if (kc == END_KC) bar_arrive(NB_END, 256);
        }
        mbar_wait(BAR(B_XR), 0);
        wg_wait<0>();
#pragma unroll
        for (int kc = NSH - 1; kc < NST - 4; kc++) g2_release(kc);
        if (elect) TS(53);
        const uint32_t ra = mapa(sb, kh ^ 1), rbar = ra + M_BAR + 8 * B_XD, dst = ra + (tid & 127) * 16;
#pragma unroll
        for (int i = 0; i < 10; i++) {
          const float *dd = d + 8 * i, *bb = bi + 4 * i;
          st_async128(dst + (i < 5 ? P0 + i * 2048 : P1 + (i - 5) * 2048), pack_bf16(fmaf(dd[0], c0, bb[0]), fmaf(dd[1], c0, bb[1])), pack_bf16(fmaf(dd[2], c1, bb[0]), fmaf(dd[3], c1, bb[1])),
                      pack_bf16(fmaf(dd[4], c0, bb[2]), fmaf(dd[5], c0, bb[3])), pack_bf16(fmaf(dd[6], c1, bb[2]), fmaf(dd[7], c1, bb[3])), rbar + 8 * ((i >= XD_N) + (i >= XD_M)));
          sched_fence(sb);
        }
        if (elect) TS(7);
      } else {
        const int mi = lane >> 3, row = (mi & 1) * 8 + (lane & 7);
        const uint32_t qa = sb + FIN_Q + (w * 16 + row) * 64 + (((mi >> 1) ^ ((row >> 1) & 3)) << 4), qb = qa ^ 32;
        auto q_addr = [&](int np) { return ((np & 1) ? qb : qa) + (np >> 1) * 4096; };
        uint32_t sv[40], xq[40];
        const uint32_t m0 = (s0 & 0xFFFFu) * 0x10001u, m1 = (s1 & 0xFFFFu) * 0x10001u;
        float rs0 = rcp_fast(bf_hi(s0)), rs1 = rcp_fast(bf_hi(s1));
#pragma unroll
        for (int kc = XP_KC; kc < 10; kc++) {
          if (tid == 0) TS(17 + kc);
          g2_mma(kc, 1, true);
          if (kc >= XP_KC && XP_KC < 10) {
            mbar_wait(BAR(B_FINQ), 0);
#pragma unroll
            for (int np = 10 * (kc - XP_KC) / (XP_KC < 10 ? 10 - XP_KC : 1); np < 10 * (kc + 1 - XP_KC) / (XP_KC < 10 ? 10 - XP_KC : 1); np++) {
              ldsm4(q_addr(np), xq[4 * np], xq[4 * np + 1], xq[4 * np + 2], xq[4 * np + 3]);
#pragma unroll
              for (int e = 0; e < 4; e++) {
                const uint32_t dm = bsub2(xq[4 * np + e], (e & 1) ? m1 : m0);
                const float rs = (e & 1) ? rs1 : rs0;
                sv[4 * np + e] = pack_bf16(bf_lo(dm) * rs, bf_hi(dm) * rs);
              }
            }
          }
        }
        const uint32_t ya = sb + (mi >> 1) * 1024 + (lane & 7) * 128 + (((2 * w + (mi & 1)) ^ (lane & 7)) << 4);
        uint32_t y[3][4];
        auto y_step = [&](int i) {
          if (i < 0 || i >= 12) return;
          if (i >= 2) {
#pragma unroll
            for (int e = 0; e < 4; e++) asm volatile("mul.rn.bf16x2 %0, %0, %1;" : "+r"(sv[4 * (i - 2) + e]) : "r"(y[(i - 2) % 3][e]));
          }
          if (i < 10) ldsm4t(ya + fin_y(i), y[i % 3][0], y[i % 3][1], y[i % 3][2], y[i % 3][3]);
          if (YFENCE) sched_fence(sb);
        };
        rs0 *= 0.25f; rs1 *= 0.25f;
        if (tid == 0) TS(27);
#pragma unroll
        for (int kc = 9; kc < NST; kc++) {
          if (kc == YP_KC) mbar_wait(BAR(B_FINY), 0);
          if (kc > 9) g2_mma_w(kc, 1, kc < NST - 3 && kc != HOLD_KC + 1, [&](int k) { y_step(4 * (kc - YP_KC) + k); });
          if (kc == HOLD_KC) {
            if (kc < NST - 4) { wg_wait<0>(); g2_release(kc); }
            if (tid == 0) TS(28);
            bar_sync(NB_END, 256);
          }
        }
        if (tid == 0) TS(29);
        if (tid == 0) TS(47);
        mbar_wait(BAR(B_XD), 0);
        if (tid == 0) TS(5);
        uint4 v[10];
        auto ld_v = [&](int n0, int n1) {
#pragma unroll
          for (int i = n0; i < n1; i++) v[i] = lds128(sb + tid * 16 + (i < 5 ? P0 + i * 2048 : P1 + (i - 5) * 2048));
        };
        ld_v(0, XD_N);
        wg_wait<0>();
        if (tid == 0) TS(4);
        float t[2][8];
#pragma unroll
        for (int st = -1; st < 11; st++) {
          if (st == XD_N - 3) { mbar_wait(BAR(B_XD + 1), 0); ld_v(XD_N, XD_M); }
          if (st == XD_M - 3) { mbar_wait(BAR(B_XD + 2), 0); ld_v(XD_M, 10); }
          if (st >= 1) {
            const int np = st - 1;
            uint32_t o[4];
#pragma unroll
            for (int e = 0; e < 4; e++) {
              const float h0 = d[8 * np + 2 * e], h1 = d[8 * np + 2 * e + 1];
              o[e] = bfma2(sv[4 * np + e], pack_bf16(fmaf(h0, t[np & 1][2 * e], h0), fmaf(h1, t[np & 1][2 * e + 1], h1)), xq[4 * np + e]);
            }
            stsm4(q_addr(np), o[0], o[1], o[2], o[3]);
            if (np & 1) {
              if (np == 9 && tid == 0) TS(50);
              __syncwarp();
              if (lane == 0) mbar_arrive(BAR(B_OUT + (np >> 1)));
            }
          }
          if (st >= 0 && st < 10) {
#pragma unroll
            for (int i = 0; i < 8; i++) t[st & 1][i] = tanh_fast(d[8 * st + i]);
          }
          if (st + 1 < 10) {
            const int np = st + 1;
            const uint32_t pw[4] = {v[np].x, v[np].y, v[np].z, v[np].w};
#pragma unroll
            for (int e = 0; e < 4; e++) {
              d[8 * np + 2 * e] = fmaf(d[8 * np + 2 * e], (e & 1) ? rs1 : rs0, bf_lo(pw[e]));
              d[8 * np + 2 * e + 1] = fmaf(d[8 * np + 2 * e + 1], (e & 1) ? rs1 : rs0, bf_hi(pw[e]));
            }
          }
          if (SCH2 && (st + 1) % (SCH2 ? SCH2 : 1) == 0) sched_fence(sb);
        }
      }
    }
  }
}

typedef CUresult (*EncFn)(CUtensorMap*, CUtensorMapDataType, cuuint32_t, void*, const cuuint64_t*, const cuuint64_t*, const cuuint32_t*, const cuuint32_t*,
                          CUtensorMapInterleave, CUtensorMapSwizzle, CUtensorMapL2promotion, CUtensorMapFloatOOBfill);

static void make_map(EncFn enc, CUtensorMap* tm, const void* ptr, int cols, int rows, int bc, int br, int grp, CUtensorMapSwizzle sw,
                     CUtensorMapL2promotion promo = CU_TENSOR_MAP_L2_PROMOTION_NONE) {
  cuuint64_t gd[3] = {(cuuint64_t)(grp ? bc : cols), (cuuint64_t)rows, (cuuint64_t)(cols / bc)};
  cuuint64_t gs[2] = {(cuuint64_t)cols * 2, (cuuint64_t)bc * 2};
  cuuint32_t bd[3] = {(cuuint32_t)bc, (cuuint32_t)br, (cuuint32_t)grp};
  cuuint32_t es[3] = {1, 1, 1};
  CUresult r = enc(tm, CU_TENSOR_MAP_DATA_TYPE_BFLOAT16, grp ? 3 : 2, const_cast<void*>(ptr), gd, gs, bd, es, CU_TENSOR_MAP_INTERLEAVE_NONE, sw,
                   promo, CU_TENSOR_MAP_FLOAT_OOB_FILL_NONE);
  (void)r;
}

}

extern "C" void kernel_launch(void* const* d_in, const int* in_sizes, int n_in, void* d_out, int out_size) {
  using namespace h3;
  (void)in_sizes; (void)n_in; (void)out_size;
  static EncFn enc = nullptr;
  static void *p_h = nullptr, *p_yT = nullptr, *p_kvT = nullptr;
  if (!enc) {
    void* fn = nullptr; cudaDriverEntryPointQueryResult qr;
    cudaGetDriverEntryPoint("cuTensorMapEncodeTiled", &fn, cudaEnableDefault, &qr);
    enc = (EncFn)fn;
    cudaGetSymbolAddress(&p_h, g_h);
    cudaGetSymbolAddress(&p_yT, g_yT);
    cudaGetSymbolAddress(&p_kvT, g_kvT);
    cudaFuncSetAttribute(h3_kernel, cudaFuncAttributeMaxDynamicSharedMemorySize, SMEM_BYTES);
  }
  Params P;
  P.q = (const __nv_bfloat16*)d_in[0]; P.k = (const __nv_bfloat16*)d_in[1]; P.v = (const __nv_bfloat16*)d_in[2];
  P.shift_k = (const __nv_bfloat16*)d_in[3]; P.ssm_k = (const __nv_bfloat16*)d_in[4]; P.ssm_D = (const __nv_bfloat16*)d_in[5];
  P.out = (__nv_bfloat16*)d_out;
  P.w1 = (const __nv_bfloat16*)d_in[7]; P.b1 = (const __nv_bfloat16*)d_in[8]; P.w2 = (const __nv_bfloat16*)d_in[9]; P.b2 = (const __nv_bfloat16*)d_in[10];
  const CUtensorMapSwizzle S128 = CU_TENSOR_MAP_SWIZZLE_128B, S64 = CU_TENSOR_MAP_SWIZZLE_64B, S0 = CU_TENSOR_MAP_SWIZZLE_NONE;
  Maps M;
  make_map(enc, &M.q0, P.q, DM, SL, 64, 64, 0, S128);
  make_map(enc, &M.qa, P.q, DM, SL, 64, 128, 0, S128);
  make_map(enc, &M.w1, P.w1, FF, DM, 64, 64, 3, S128);
  make_map(enc, &M.w1x, P.w1, FF, DM, 24, 64, 0, S128, WS_PROMO);
  make_map(enc, &M.k, P.k, DM, SL, 64, 19, 0, S0);
  make_map(enc, &M.v, P.v, DM, SL, 64, 16, 0, S0);
  make_map(enc, &M.hs, p_h, FF, SL, 64, 64, 0, S128);
  make_map(enc, &M.hx, p_h, FF, SL, 24, 64, 0, S0);
  make_map(enc, &M.ha, p_h, FF, SL, 64, 128, 0, S128);
  make_map(enc, &M.w2, P.w2, DM, FF, 64, 64, 2, S128);
  make_map(enc, &M.w2x, P.w2, DM, FF, 64, 64, 0, S128);
  make_map(enc, &M.kvs, p_kvT, SL, DM, 16, 64, 0, CU_TENSOR_MAP_SWIZZLE_32B);
  make_map(enc, &M.qf, P.q, DM, SL, 32, 64, 0, S64);
  make_map(enc, &M.y, p_yT, SL, DM, 64, 16, 0, S128);
  make_map(enc, &M.out, d_out, DM, SL, 32, 64, 0, S64);
  h3_kernel<<<NCTA, 384, SMEM_BYTES>>>(M, P);
}
```

```cpp
#include <cuda_runtime.h>
#include <cuda_bf16.h>
#include <cuda.h>
#include <stdint.h>

namespace h3 {

constexpr int SL = 2048, DM = 640, FF = 1728;
constexpr int NCTA = 128;

__device__ __align__(1024) __nv_bfloat16 g_h[SL * FF];
__device__ __align__(1024) __nv_bfloat16 g_kvT[DM * SL];
__device__ __align__(1024) __nv_bfloat16 g_yT[DM * SL];
__device__ __align__(1024) uint2 g_stat[2 * SL];
__device__ __align__(1024) uint32_t g_cs[2 * 8 * 256];
__device__ __align__(1024) unsigned g_cnt[64 * 32];
__device__ __align__(1024) unsigned g_launch[NCTA * 8];
#define RETRY(i)
constexpr int CNT_H = 0;

constexpr int G1_STAGE = 49152, G1_TX = 16384 + 24576 + 3072;
constexpr int HST = 49152;
constexpr int P0 = 81920, P1 = 140288, P2 = 156672;
constexpr int XCH = 4368, XD = 272, X0 = 173056, X4 = 221184;
constexpr int KVS = 196608, KV_BUF = 8960;
constexpr int KT_CH = 8240, KT_O = 16, KT_E = 4144, KT0 = 98304;
constexpr int FIN_Q = X0;
constexpr int MISC = 226816;
constexpr int M_BX = MISC;
constexpr int M_RED0 = M_BX + 2048, M_RED1 = M_BX;
constexpr int M_SK = KVS + 3 * KV_BUF;
constexpr int M_STAT = M_BX + 3584;
constexpr int M_B2 = MISC - 640;
constexpr int M_AUX = M_STAT + 512;
constexpr int M_ZERO = M_AUX + 96;
constexpr int M_BAR = M_ZERO + 16;
constexpr int M_TS = M_BAR + 94 * 8;
constexpr int SMEM_BYTES = M_TS + 256;
__host__ __device__ constexpr int fin_y(int np) {
  return np < 3 ? P0 + 10240 + np * 2048 : (np < 6 ? P1 + 10240 + (np - 3) * 2048 : (np == 6 ? FIN_Q + 20480 : (np < 9 ? X4 + (np - 7) * 2048 : M_BX + 512)));
}
static_assert(fin_y(9) % 1024 == 0 && fin_y(6) % 1024 == 0 && fin_y(6) + 2048 <= KVS && fin_y(7) % 1024 == 0, "smem");
__host__ __device__ constexpr int cv_x(int c) { return c == 4 ? X4 : X0 + c * XCH; }
__host__ __device__ constexpr int cv_p(int c) { return c == 2 ? P2 : ((c == 0 || c == 3) ? P0 : P1); }
__host__ __device__ constexpr int cv_t(int c) { return KT0 + c * KT_CH; }
__host__ __device__ constexpr int g2_a(int s) { return s == 0 ? 0 : (s == 1 ? 40960 : (s == 2 ? 98304 : P2)); }
__host__ __device__ constexpr int g2_b(int s) { return s == 0 ? 16384 : (s == 1 ? 57344 : (s == 2 ? 114688 : KVS)); }
static_assert(M_SK + 2560 <= M_B2 && X4 + XCH <= M_B2 && KVS + 24576 <= X4 && X0 + 4 * XCH <= KVS && FIN_Q + 20480 <= KVS, "smem");
static_assert(KT0 + 5 * KT_CH <= P1 && P1 + 16384 <= P2 && P2 + 16384 <= X0 && SMEM_BYTES <= 232448 && MISC % 512 == 0 && M_BAR % 8 == 0, "smem");
constexpr int B_E1 = 0, B_FR = 4, B_E2 = 8, B_TD = 11  , B_RF = 13;
constexpr int B_HB = 16, B_SD = 24, B_OUT = 29, B_LNI = 34, B_RED = 35, B_RED1 = 36, B_FINY = 37, B_BX = 38, B_KD = 39;
constexpr int B_F2 = 40, B_KRAW = 44, B_RD = 46, B_SK = 47, B_XL = 48, B_KT = 53, B_XF = 58, B_KIN = 63, B_KIN1 = 68, B_YSLOT = 73,
              B_YL = 76, B_XR = 79, B_XD = 80, B_FINQ = 83, B_F1 = 88, B_F0 = 92;
constexpr int NB_INIT = 1, NB_INIT2 = 2, NB_AUX = 3, NB_LEAD = 4, NB_GELU = 5, NB_TURN = 6  , NB_END = 8, NB_INIT3 = 9, NB_WG1 = 10;

#define STAG_KC 8
#define STAG_ALL 1
#define STAG_REL 0
#define COM 2
#define PEEK 0
#define PRO 1
#define INC_KC 6
#define KV_MAP 0x764
#define WS_PROMO CU_TENSOR_MAP_L2_PROMOTION_L2_128B
#define RAW_LATE 0
#define PF_RAW 0x00007
#define REL_K 0
#define CS_WAIT 1
#define GELU_NB 8
#define H_ORD 0x73625410
#define W2_PF 7
#define H_FLY 8
#define TB_MAP 0x01040532u
#define KRAW_N 2
#define XT1 (B_FR + 3)
#define XT2 (B_HB + 1)
#define XT3 (B_HB + 3)
#define XT4 (B_HB + 7)
#define X_TRIG ((XT1) | (XT2) << 8 | (XT3) << 16 | (XT4) << 24)
#define FENCE_KIND 1
#define SCH2 0
#define SCH 1
#define A_NB0 14
#define HAND4 1
#define LEAD_KC 1
#define RED_GATE 3
#define XP_KC 4
#define NSH 12
#define NST (27 - NSH)
#define YP_KC 12
#define YFENCE 1
#define Y_MAP 0x210
#define Y_KC 9
#define XD_N 6
#define XD_M 8
#define HOLD_KC 11
#define END_KC (NSH - 1)
#define REG_AUX "56"
#define REG_CON "224"
#define LDQ ".nc.L1::no_allocate"
#define LDP ""

__device__ __forceinline__ uint32_t s32(const void* p) { return (uint32_t)__cvta_generic_to_shared(p); }
__device__ __forceinline__ uint32_t clk() { uint32_t t; asm volatile("mov.u32 %0, %%clock;" : "=r"(t)); return t; }
__device__ __forceinline__ bool elect_one() {
  uint32_t p; asm volatile("{\n.reg .pred P;\nelect.sync _|P, 0xffffffff;\nselp.u32 %0, 1, 0, P;\n}" : "=r"(p)); return p;
}
#define ONE(...) do { if (elect_one()) { __VA_ARGS__; } __syncwarp(); } while (0)
__device__ __forceinline__ void mbar_init(uint32_t a, int c) { asm volatile("mbarrier.init.shared::cta.b64 [%0], %1;" ::"r"(a), "r"(c) : "memory"); }
__device__ __forceinline__ void mbar_expect(uint32_t a, int b) { asm volatile("mbarrier.arrive.expect_tx.shared::cta.b64 _, [%0], %1;" ::"r"(a), "r"(b) : "memory"); }
__device__ __forceinline__ void mbar_arrive(uint32_t a) { asm volatile("mbarrier.arrive.shared::cta.b64 _, [%0];" ::"r"(a) : "memory"); }
__device__ __forceinline__ bool spin_guard(uint32_t& n, uint32_t) {
  return ++n > (1u << 20);
}
__device__ __forceinline__ void mbar_wait(uint32_t a, int ph) {
  asm volatile("{\n.reg .pred p;\n.reg .u32 n;\nmov.u32 n, 0;\nW:\n.pragma \"nounroll\";\nmbarrier.try_wait.parity.shared::cta.b64 p, [%0], %1;\n"
               "add.u32 n, n, 1;\nsetp.ge.or.u32 p, n, 0x100000, p;\n@!p bra W;\n}" ::"r"(a), "r"(ph) : "memory");
}
__device__ __forceinline__ bool mbar_test(uint32_t a, int ph) {
  uint32_t ok;
  asm volatile("{\n.reg .pred p;\nmbarrier.test_wait.parity.shared::cta.b64 p, [%1], %2;\nselp.u32 %0, 1, 0, p;\n}" : "=r"(ok) : "r"(a), "r"(ph) : "memory");
  return __all_sync(0xffffffffu, ok);
}
__device__ __forceinline__ void sched_fence(uint32_t a) {
  asm volatile("{\n.reg .pred p;\nsetp.eq.u32 p, %0, 0;\n@p exit;\n}" ::"r"(a) : "memory");
}
__device__ __forceinline__ void keep(uint32_t& v) { v = __shfl_sync(0xffffffffu, v, threadIdx.x & 31); }
__device__ __forceinline__ void tma2d(uint32_t dst, const CUtensorMap* tm, int c0, int c1, uint32_t bar) {
  asm volatile("cp.async.bulk.tensor.2d.shared::cluster.global.mbarrier::complete_tx::bytes [%0], [%1, {%3, %4}], [%2];"
               ::"r"(dst), "l"(tm), "r"(bar), "r"(c0), "r"(c1) : "memory");
}
__device__ __forceinline__ void tma3d(uint32_t dst, const CUtensorMap* tm, int c0, int c1, int c2, uint32_t bar) {
  asm volatile("cp.async.bulk.tensor.3d.shared::cluster.global.mbarrier::complete_tx::bytes [%0], [%1, {%3, %4, %5}], [%2];"
               ::"r"(dst), "l"(tm), "r"(bar), "r"(c0), "r"(c1), "r"(c2) : "memory");
}
__device__ __forceinline__ void tma2d_st(const CUtensorMap* tm, int c0, int c1, uint32_t src) {
  asm volatile("cp.async.bulk.tensor.2d.global.shared::cta.bulk_group [%0, {%2, %3}], [%1];" ::"l"(tm), "r"(src), "r"(c0), "r"(c1) : "memory");
}
__device__ __forceinline__ void tma3d_st(const CUtensorMap* tm, int c0, int c1, int c2, uint32_t src) {
  asm volatile("cp.async.bulk.tensor.3d.global.shared::cta.bulk_group [%0, {%2, %3, %4}], [%1];" ::"l"(tm), "r"(src), "r"(c0), "r"(c1), "r"(c2) : "memory");
}
__device__ __forceinline__ void bulk_g2s(uint32_t dst, const void* src, int bytes, uint32_t bar) {
  asm volatile("cp.async.bulk.shared::cluster.global.mbarrier::complete_tx::bytes [%0], [%1], %2, [%3];" ::"r"(dst), "l"(src), "r"(bytes), "r"(bar) : "memory");
}
__device__ __forceinline__ void bulk_commit() { asm volatile("cp.async.bulk.commit_group;" ::: "memory"); }
__device__ __forceinline__ void bulk_wait_read() { asm volatile("cp.async.bulk.wait_group.read 0;" ::: "memory"); }
__device__ __forceinline__ void bulk_wait_all() { asm volatile("cp.async.bulk.wait_group 0;" ::: "memory"); }
__device__ __forceinline__ void fence_async_smem() { asm volatile("fence.proxy.async.shared::cta;" ::: "memory"); }
__device__ __forceinline__ void fence_async_all() { asm volatile("fence.proxy.async;" ::: "memory"); }
__device__ __forceinline__ void fence_gpu() { asm volatile("fence.acq_rel.gpu;" ::: "memory"); }
#define bar_sync(id, n) asm volatile("bar.sync %0, %1;" ::"n"(id), "n"(n) : "memory")
#define bar_arrive(id, n) asm volatile("bar.arrive %0, %1;" ::"n"(id), "n"(n) : "memory")
__device__ __forceinline__ void wg_fence() { asm volatile("wgmma.fence.sync.aligned;" ::: "memory"); }
__device__ __forceinline__ void wg_commit() { asm volatile("wgmma.commit_group.sync.aligned;" ::: "memory"); }
template <int N> __device__ __forceinline__ void wg_wait() { asm volatile("wgmma.wait_group.sync.aligned %0;" ::"n"(N) : "memory"); }
__device__ __forceinline__ uint64_t mkdesc(uint32_t addr, uint32_t lbo, uint32_t sbo, int sw) {
  return (uint64_t)((addr & 0x3FFFF) >> 4) | ((uint64_t)(lbo >> 4) << 16) | ((uint64_t)(sbo >> 4) << 32) | ((uint64_t)sw << 62);
}
__device__ __forceinline__ uint32_t ldg32(const void* p) { uint32_t v; asm volatile("ld.global" LDQ ".b32 %0, [%1];" : "=r"(v) : "l"(p)); return v; }
template <int OFF> __device__ __forceinline__ uint32_t ldg32o(const void* p) { uint32_t v; asm volatile("ld.global" LDQ ".b32 %0, [%1+%2];" : "=r"(v) : "l"(p), "n"(OFF)); return v; }
template <int I> __device__ __forceinline__ void kv_loads(const void* kp, const void* vp, uint32_t (&kk)[16], uint32_t (&o)[16]) {
  kk[I] = ldg32o<I * DM * 2>(kp); o[I] = ldg32o<I * DM * 2>(vp);
  if constexpr (I < 15) kv_loads<I + 1>(kp, vp, kk, o);
}
__device__ __forceinline__ uint4 ldg128(const void* p) {
  uint4 v; asm volatile("ld.global" LDQ LDP ".v4.b32 {%0,%1,%2,%3}, [%4];" : "=r"(v.x), "=r"(v.y), "=r"(v.z), "=r"(v.w) : "l"(p)); return v;
}
__device__ __forceinline__ void stg128(void* p, uint32_t x, uint32_t y, uint32_t z, uint32_t w) {
  asm volatile("st.global.v4.b32 [%0], {%1,%2,%3,%4};" ::"l"(p), "r"(x), "r"(y), "r"(z), "r"(w) : "memory");
}
__device__ __forceinline__ uint4 ld_relaxed128(const void* p) {
  uint4 v; asm volatile("ld.relaxed.gpu.global.v4.b32 {%0,%1,%2,%3}, [%4];" : "=r"(v.x), "=r"(v.y), "=r"(v.z), "=r"(v.w) : "l"(p) : "memory"); return v;
}
__device__ __forceinline__ uint2 ld_relaxed64(const void* p) {
  uint2 v; asm volatile("ld.relaxed.gpu.global.v2.b32 {%0,%1}, [%2];" : "=r"(v.x), "=r"(v.y) : "l"(p) : "memory"); return v;
}
__device__ __forceinline__ uint4 ld_relaxed_b128(const void* p) {
  uint4 v; asm volatile("{\n.reg .b128 t;\nld.relaxed.gpu.global.b128 t, [%4];\nmov.b128 {%0,%1,%2,%3}, t;\n}" : "=r"(v.x), "=r"(v.y), "=r"(v.z), "=r"(v.w) : "l"(p) : "memory"); return v;
}
__device__ __forceinline__ void st_relaxed_b128(void* p, uint32_t x, uint32_t y, uint32_t z, uint32_t w) {
  asm volatile("{\n.reg .b128 t;\nmov.b128 t, {%1,%2,%3,%4};\nst.relaxed.gpu.global.b128 [%0], t;\n}" ::"l"(p), "r"(x), "r"(y), "r"(z), "r"(w) : "memory");
}
__device__ __forceinline__ void st_relaxed64(void* p, uint32_t x, uint32_t y) {
  asm volatile("{\n.reg .b64 t;\nmov.b64 t, {%1,%2};\nst.relaxed.gpu.global.b64 [%0], t;\n}" ::"l"(p), "r"(x), "r"(y) : "memory");
}
__device__ __forceinline__ void st_relaxed32(void* p, uint32_t x) { asm volatile("st.relaxed.gpu.global.b32 [%0], %1;" ::"l"(p), "r"(x) : "memory"); }
__device__ __forceinline__ uint32_t ld_relaxed32(const void* p) { uint32_t v; asm volatile("ld.relaxed.gpu.global.b32 %0, [%1];" : "=r"(v) : "l"(p) : "memory"); return v; }
__device__ __forceinline__ void st_relaxed128(void* p, uint32_t x, uint32_t y, uint32_t z, uint32_t w) {
  asm volatile("{\n.reg .b64 t, u;\nmov.b64 t, {%1,%2};\nmov.b64 u, {%3,%4};\nst.relaxed.gpu.global.v2.b64 [%0], {t, u};\n}" ::"l"(p), "r"(x), "r"(y), "r"(z), "r"(w) : "memory");
}
__device__ __forceinline__ void fence_release() { asm volatile("fence.proxy.async.global;\nfence.release.gpu;" ::: "memory"); }
__device__ __forceinline__ void fence_acquire() { asm volatile("fence.acquire.gpu;\nfence.proxy.async.global;" ::: "memory"); }
__device__ __forceinline__ void signal_cnt(int idx) { asm volatile("red.relaxed.gpu.global.add.u32 [%0], 1;" ::"l"(&g_cnt[idx * 32]) : "memory"); }
__device__ __forceinline__ void wait_cnt(int idx, unsigned target) {
  uint32_t n = 0;
#pragma unroll 1
  while (!__all_sync(0xffffffffu, (int)(ld_relaxed32(&g_cnt[idx * 32]) - target) >= 0)) {
    if (spin_guard(n, 0x100 + idx)) break;
  }
  fence_acquire();
}
__device__ __forceinline__ void bulk_s2g(void* dst, uint32_t src, int bytes) {
  asm volatile("cp.async.bulk.global.shared::cta.bulk_group [%0], [%1], %2;" ::"l"(dst), "r"(src), "r"(bytes) : "memory");
}
__device__ __forceinline__ void bulk_add_s2g(void* dst, uint32_t src, int bytes) {
  asm volatile("cp.reduce.async.bulk.global.shared::cta.bulk_group.add.noftz.bf16 [%0], [%1], %2;" ::"l"(dst), "r"(src), "r"(bytes) : "memory");
}
__device__ __forceinline__ void prefetch_l2(const void* p, int bytes) { asm volatile("cp.async.bulk.prefetch.L2.global [%0], %1;" ::"l"(p), "r"(bytes) : "memory"); }
__device__ __forceinline__ void prefetch_tile(const CUtensorMap* tm, int c0, int c1) {
  asm volatile("cp.async.bulk.prefetch.tensor.2d.L2.global.tile [%0, {%1, %2}];" ::"l"(tm), "r"(c0), "r"(c1) : "memory");
}
__device__ __forceinline__ void prefetch_map(const CUtensorMap* tm) { asm volatile("prefetch.tensormap [%0];" ::"l"(tm) : "memory"); }
__device__ __forceinline__ uint32_t pack_bf16(float lo, float hi) {
  uint32_t r; asm("cvt.rn.bf16x2.f32 %0, %1, %2;" : "=r"(r) : "f"(hi), "f"(lo)); return r;
}
__device__ __forceinline__ float bf_lo(uint32_t v) { return __uint_as_float(v << 16); }
__device__ __forceinline__ float bf_hi(uint32_t v) { return __uint_as_float(v & 0xFFFF0000u); }
__device__ __forceinline__ float bf_round(float x) { return __bfloat162float(__float2bfloat16_rn(x)); }
__device__ __forceinline__ uint32_t bmul2(uint32_t a, uint32_t b) { uint32_t r; asm("mul.rn.bf16x2 %0, %1, %2;" : "=r"(r) : "r"(a), "r"(b)); return r; }
__device__ __forceinline__ uint32_t bfma2(uint32_t a, uint32_t b, uint32_t c) { uint32_t r; asm("fma.rn.bf16x2 %0, %1, %2, %3;" : "=r"(r) : "r"(a), "r"(b), "r"(c)); return r; }
__device__ __forceinline__ uint32_t badd2(uint32_t a, uint32_t b) { uint32_t r; asm("add.rn.bf16x2 %0, %1, %2;" : "=r"(r) : "r"(a), "r"(b)); return r; }
__device__ __forceinline__ uint32_t bsub2(uint32_t a, uint32_t b) { uint32_t r; asm("sub.rn.bf16x2 %0, %1, %2;" : "=r"(r) : "r"(a), "r"(b)); return r; }
__device__ __forceinline__ uint32_t tagged(float v, uint32_t ep) { return (__float_as_uint(v) & ~15u) | (ep & 15u); }
__device__ __forceinline__ float tanh_fast(float x) { float r; asm("tanh.approx.f32 %0, %1;" : "=f"(r) : "f"(x)); return r; }
__device__ __forceinline__ float rcp_fast(float x) { float r; asm("rcp.approx.ftz.f32 %0, %1;" : "=f"(r) : "f"(x)); return r; }
__device__ __forceinline__ float sqrt_fast(float x) { float r; asm("sqrt.approx.ftz.f32 %0, %1;" : "=f"(r) : "f"(x)); return r; }
__device__ __forceinline__ uint32_t lds32(uint32_t a) { uint32_t v; asm volatile("ld.shared.b32 %0, [%1];" : "=r"(v) : "r"(a)); return v; }
__device__ __forceinline__ uint4 lds128(uint32_t a) { uint4 v; asm volatile("ld.shared.v4.b32 {%0,%1,%2,%3}, [%4];" : "=r"(v.x), "=r"(v.y), "=r"(v.z), "=r"(v.w) : "r"(a)); return v; }
__device__ __forceinline__ float2 lds64f(uint32_t a) { float2 v; asm volatile("ld.shared.v2.f32 {%0,%1}, [%2];" : "=f"(v.x), "=f"(v.y) : "r"(a)); return v; }
__device__ __forceinline__ void sts64f(uint32_t a, float x, float y) { asm volatile("st.shared.v2.f32 [%0], {%1,%2};" ::"r"(a), "f"(x), "f"(y) : "memory"); }
__device__ __forceinline__ void sts32(uint32_t a, uint32_t x) { asm volatile("st.shared.b32 [%0], %1;" ::"r"(a), "r"(x) : "memory"); }
__device__ __forceinline__ void sts128(uint32_t a, uint32_t x, uint32_t y, uint32_t z, uint32_t w) { asm volatile("st.shared.v4.b32 [%0], {%1,%2,%3,%4};" ::"r"(a), "r"(x), "r"(y), "r"(z), "r"(w) : "memory"); }
__device__ __forceinline__ void stsm4(uint32_t a, uint32_t r0, uint32_t r1, uint32_t r2, uint32_t r3) {
  asm volatile("stmatrix.sync.aligned.m8n8.x4.shared.b16 [%0], {%1,%2,%3,%4};" ::"r"(a), "r"(r0), "r"(r1), "r"(r2), "r"(r3) : "memory");
}
__device__ __forceinline__ void stsm4t(uint32_t a, uint32_t r0, uint32_t r1, uint32_t r2, uint32_t r3) {
  asm volatile("stmatrix.sync.aligned.m8n8.x4.trans.shared.b16 [%0], {%1,%2,%3,%4};" ::"r"(a), "r"(r0), "r"(r1), "r"(r2), "r"(r3) : "memory");
}
__device__ __forceinline__ void stsm2(uint32_t a, uint32_t r0, uint32_t r1) {
  asm volatile("stmatrix.sync.aligned.m8n8.x2.shared.b16 [%0], {%1,%2};" ::"r"(a), "r"(r0), "r"(r1) : "memory");
}
__device__ __forceinline__ void ldsm4(uint32_t a, uint32_t& r0, uint32_t& r1, uint32_t& r2, uint32_t& r3) {
  asm volatile("ldmatrix.sync.aligned.m8n8.x4.shared.b16 {%0,%1,%2,%3}, [%4];" : "=r"(r0), "=r"(r1), "=r"(r2), "=r"(r3) : "r"(a) : "memory");
}
__device__ __forceinline__ void ldsm4t(uint32_t a, uint32_t& r0, uint32_t& r1, uint32_t& r2, uint32_t& r3) {
  asm volatile("ldmatrix.sync.aligned.m8n8.x4.trans.shared.b16 {%0,%1,%2,%3}, [%4];" : "=r"(r0), "=r"(r1), "=r"(r2), "=r"(r3) : "r"(a) : "memory");
}
__device__ __forceinline__ uint32_t mapa(uint32_t a, uint32_t rank) { uint32_t r; asm("mapa.shared::cluster.u32 %0, %1, %2;" : "=r"(r) : "r"(a), "r"(rank)); return r; }
__device__ __forceinline__ void mbar_arrive_remote(uint32_t a) { asm volatile("mbarrier.arrive.relaxed.cluster.shared::cluster.b64 _, [%0];" ::"r"(a) : "memory"); }
__device__ __forceinline__ void st_async128(uint32_t a, uint32_t x, uint32_t y, uint32_t z, uint32_t w, uint32_t bar) {
  asm volatile("st.async.weak.shared::cluster.mbarrier::complete_tx::bytes.v4.b32 [%0], {%1,%2,%3,%4}, [%5];" ::"r"(a), "r"(x), "r"(y), "r"(z), "r"(w), "r"(bar) : "memory");
}
#define TS(i)

#define TSKV
__device__ __forceinline__ void wg_ss_216(float (&d)[108], uint64_t da, uint64_t db, int sd) {
  asm volatile("{\n.reg .pred p;\nsetp.ne.b32 p, %110, 0;\n"
    "wgmma.mma_async.sync.aligned.m64n216k16.f32.bf16.bf16 {%0,%1,%2,%3,%4,%5,%6,%7,%8,%9,%10,%11,%12,%13,%14,%15,%16,%17,%18,%19,%20,%21,%22,%23,%24,%25,%26,%27,%28,%29,%30,%31,%32,%33,%34,%35,%36,%37,%38,%39,%40,%41,%42,%43,%44,%45,%46,%47,%48,%49,%50,%51,%52,%53,%54,%55,%56,%57,%58,%59,%60,%61,%62,%63,%64,%65,%66,%67,%68,%69,%70,%71,%72,%73,%74,%75,%76,%77,%78,%79,%80,%81,%82,%83,%84,%85,%86,%87,%88,%89,%90,%91,%92,%93,%94,%95,%96,%97,%98,%99,%100,%101,%102,%103,%104,%105,%106,%107}, %108, %109, p, 1, 1, 0, 1;\n}\n"
    : "+f"(d[0]),"+f"(d[1]),"+f"(d[2]),"+f"(d[3]),"+f"(d[4]),"+f"(d[5]),"+f"(d[6]),"+f"(d[7]),"+f"(d[8]),"+f"(d[9]),"+f"(d[10]),"+f"(d[11]),"+f"(d[12]),"+f"(d[13]),"+f"(d[14]),"+f"(d[15]),"+f"(d[16]),"+f"(d[17]),"+f"(d[18]),"+f"(d[19]),"+f"(d[20]),"+f"(d[21]),"+f"(d[22]),"+f"(d[23]),"+f"(d[24]),"+f"(d[25]),"+f"(d[26]),"+f"(d[27]),"+f"(d[28]),"+f"(d[29]),"+f"(d[30]),"+f"(d[31]),"+f"(d[32]),"+f"(d[33]),"+f"(d[34]),"+f"(d[35]),"+f"(d[36]),"+f"(d[37]),"+f"(d[38]),"+f"(d[39]),"+f"(d[40]),"+f"(d[41]),"+f"(d[42]),"+f"(d[43]),"+f"(d[44]),"+f"(d[45]),"+f"(d[46]),"+f"(d[47]),"+f"(d[48]),"+f"(d[49]),"+f"(d[50]),"+f"(d[51]),"+f"(d[52]),"+f"(d[53]),"+f"(d[54]),"+f"(d[55]),"+f"(d[56]),"+f"(d[57]),"+f"(d[58]),"+f"(d[59]),"+f"(d[60]),"+f"(d[61]),"+f"(d[62]),"+f"(d[63]),"+f"(d[64]),"+f"(d[65]),"+f"(d[66]),"+f"(d[67]),"+f"(d[68]),"+f"(d[69]),"+f"(d[70]),"+f"(d[71]),"+f"(d[72]),"+f"(d[73]),"+f"(d[74]),"+f"(d[75]),"+f"(d[76]),"+f"(d[77]),"+f"(d[78]),"+f"(d[79]),"+f"(d[80]),"+f"(d[81]),"+f"(d[82]),"+f"(d[83]),"+f"(d[84]),"+f"(d[85]),"+f"(d[86]),"+f"(d[87]),"+f"(d[88]),"+f"(d[89]),"+f"(d[90]),"+f"(d[91]),"+f"(d[92]),"+f"(d[93]),"+f"(d[94]),"+f"(d[95]),"+f"(d[96]),"+f"(d[97]),"+f"(d[98]),"+f"(d[99]),"+f"(d[100]),"+f"(d[101]),"+f"(d[102]),"+f"(d[103]),"+f"(d[104]),"+f"(d[105]),"+f"(d[106]),"+f"(d[107]) : "l"(da), "l"(db), "r"(sd));
}
__device__ __forceinline__ void wg_ss_160(float (&d)[80], uint64_t da, uint64_t db, int sd) {
  asm volatile("{\n.reg .pred p;\nsetp.ne.b32 p, %82, 0;\n"
    "wgmma.mma_async.sync.aligned.m64n160k16.f32.bf16.bf16 {%0,%1,%2,%3,%4,%5,%6,%7,%8,%9,%10,%11,%12,%13,%14,%15,%16,%17,%18,%19,%20,%21,%22,%23,%24,%25,%26,%27,%28,%29,%30,%31,%32,%33,%34,%35,%36,%37,%38,%39,%40,%41,%42,%43,%44,%45,%46,%47,%48,%49,%50,%51,%52,%53,%54,%55,%56,%57,%58,%59,%60,%61,%62,%63,%64,%65,%66,%67,%68,%69,%70,%71,%72,%73,%74,%75,%76,%77,%78,%79}, %80, %81, p, 1, 1, 0, 1;\n}\n"
    : "+f"(d[0]),"+f"(d[1]),"+f"(d[2]),"+f"(d[3]),"+f"(d[4]),"+f"(d[5]),"+f"(d[6]),"+f"(d[7]),"+f"(d[8]),"+f"(d[9]),"+f"(d[10]),"+f"(d[11]),"+f"(d[12]),"+f"(d[13]),"+f"(d[14]),"+f"(d[15]),"+f"(d[16]),"+f"(d[17]),"+f"(d[18]),"+f"(d[19]),"+f"(d[20]),"+f"(d[21]),"+f"(d[22]),"+f"(d[23]),"+f"(d[24]),"+f"(d[25]),"+f"(d[26]),"+f"(d[27]),"+f"(d[28]),"+f"(d[29]),"+f"(d[30]),"+f"(d[31]),"+f"(d[32]),"+f"(d[33]),"+f"(d[34]),"+f"(d[35]),"+f"(d[36]),"+f"(d[37]),"+f"(d[38]),"+f"(d[39]),"+f"(d[40]),"+f"(d[41]),"+f"(d[42]),"+f"(d[43]),"+f"(d[44]),"+f"(d[45]),"+f"(d[46]),"+f"(d[47]),"+f"(d[48]),"+f"(d[49]),"+f"(d[50]),"+f"(d[51]),"+f"(d[52]),"+f"(d[53]),"+f"(d[54]),"+f"(d[55]),"+f"(d[56]),"+f"(d[57]),"+f"(d[58]),"+f"(d[59]),"+f"(d[60]),"+f"(d[61]),"+f"(d[62]),"+f"(d[63]),"+f"(d[64]),"+f"(d[65]),"+f"(d[66]),"+f"(d[67]),"+f"(d[68]),"+f"(d[69]),"+f"(d[70]),"+f"(d[71]),"+f"(d[72]),"+f"(d[73]),"+f"(d[74]),"+f"(d[75]),"+f"(d[76]),"+f"(d[77]),"+f"(d[78]),"+f"(d[79]) : "l"(da), "l"(db), "r"(sd));
}
__device__ __forceinline__ void wg_rs_216(float (&d)[108], uint32_t a0, uint32_t a1, uint32_t a2, uint32_t a3, uint64_t db) {
  asm volatile("{\n.reg .pred p;\nsetp.ne.b32 p, 1, 0;\n"
    "wgmma.mma_async.sync.aligned.m64n216k16.f32.bf16.bf16 {%0,%1,%2,%3,%4,%5,%6,%7,%8,%9,%10,%11,%12,%13,%14,%15,%16,%17,%18,%19,%20,%21,%22,%23,%24,%25,%26,%27,%28,%29,%30,%31,%32,%33,%34,%35,%36,%37,%38,%39,%40,%41,%42,%43,%44,%45,%46,%47,%48,%49,%50,%51,%52,%53,%54,%55,%56,%57,%58,%59,%60,%61,%62,%63,%64,%65,%66,%67,%68,%69,%70,%71,%72,%73,%74,%75,%76,%77,%78,%79,%80,%81,%82,%83,%84,%85,%86,%87,%88,%89,%90,%91,%92,%93,%94,%95,%96,%97,%98,%99,%100,%101,%102,%103,%104,%105,%106,%107}, {%108,%109,%110,%111}, %112, p, 1, 1, 1;\n}\n"
    : "+f"(d[0]),"+f"(d[1]),"+f"(d[2]),"+f"(d[3]),"+f"(d[4]),"+f"(d[5]),"+f"(d[6]),"+f"(d[7]),"+f"(d[8]),"+f"(d[9]),"+f"(d[10]),"+f"(d[11]),"+f"(d[12]),"+f"(d[13]),"+f"(d[14]),"+f"(d[15]),"+f"(d[16]),"+f"(d[17]),"+f"(d[18]),"+f"(d[19]),"+f"(d[20]),"+f"(d[21]),"+f"(d[22]),"+f"(d[23]),"+f"(d[24]),"+f"(d[25]),"+f"(d[26]),"+f"(d[27]),"+f"(d[28]),"+f"(d[29]),"+f"(d[30]),"+f"(d[31]),"+f"(d[32]),"+f"(d[33]),"+f"(d[34]),"+f"(d[35]),"+f"(d[36]),"+f"(d[37]),"+f"(d[38]),"+f"(d[39]),"+f"(d[40]),"+f"(d[41]),"+f"(d[42]),"+f"(d[43]),"+f"(d[44]),"+f"(d[45]),"+f"(d[46]),"+f"(d[47]),"+f"(d[48]),"+f"(d[49]),"+f"(d[50]),"+f"(d[51]),"+f"(d[52]),"+f"(d[53]),"+f"(d[54]),"+f"(d[55]),"+f"(d[56]),"+f"(d[57]),"+f"(d[58]),"+f"(d[59]),"+f"(d[60]),"+f"(d[61]),"+f"(d[62]),"+f"(d[63]),"+f"(d[64]),"+f"(d[65]),"+f"(d[66]),"+f"(d[67]),"+f"(d[68]),"+f"(d[69]),"+f"(d[70]),"+f"(d[71]),"+f"(d[72]),"+f"(d[73]),"+f"(d[74]),"+f"(d[75]),"+f"(d[76]),"+f"(d[77]),"+f"(d[78]),"+f"(d[79]),"+f"(d[80]),"+f"(d[81]),"+f"(d[82]),"+f"(d[83]),"+f"(d[84]),"+f"(d[85]),"+f"(d[86]),"+f"(d[87]),"+f"(d[88]),"+f"(d[89]),"+f"(d[90]),"+f"(d[91]),"+f"(d[92]),"+f"(d[93]),"+f"(d[94]),"+f"(d[95]),"+f"(d[96]),"+f"(d[97]),"+f"(d[98]),"+f"(d[99]),"+f"(d[100]),"+f"(d[101]),"+f"(d[102]),"+f"(d[103]),"+f"(d[104]),"+f"(d[105]),"+f"(d[106]),"+f"(d[107]) : "r"(a0), "r"(a1), "r"(a2), "r"(a3), "l"(db));
}
__device__ __forceinline__ void wg_cv_0_0(float (&d)[128], uint32_t a0, uint32_t a1, uint32_t a2, uint32_t a3, uint32_t db) {
  asm volatile("{\n.reg .pred p;\n.reg .b64 t;\nsetp.ne.b32 p, 0, 0;\nmov.b64 t, {%20, 8};\n"
    "wgmma.mma_async.sync.aligned.m64n32k16.f32.bf16.bf16 {%0,%1,%2,%3,%4,%5,%6,%7,%8,%9,%10,%11,%12,%13,%14,%15}, {%16,%17,%18,%19}, t, p, 1, 1, 0;\n}\n"
    : "+f"(d[0]),"+f"(d[1]),"+f"(d[2]),"+f"(d[3]),"+f"(d[4]),"+f"(d[5]),"+f"(d[6]),"+f"(d[7]),"+f"(d[8]),"+f"(d[9]),"+f"(d[10]),"+f"(d[11]),"+f"(d[12]),"+f"(d[13]),"+f"(d[14]),"+f"(d[15]) : "r"(a0), "r"(a1), "r"(a2), "r"(a3), "r"(db));
}
__device__ __forceinline__ void wg_cv_0_1(float (&d)[128], uint32_t a0, uint32_t a1, uint32_t a2, uint32_t a3, uint32_t db) {
  asm volatile("{\n.reg .pred p;\n.reg .b64 t;\nsetp.ne.b32 p, 1, 0;\nmov.b64 t, {%20, 8};\n"
    "wgmma.mma_async.sync.aligned.m64n32k16.f32.bf16.bf16 {%0,%1,%2,%3,%4,%5,%6,%7,%8,%9,%10,%11,%12,%13,%14,%15}, {%16,%17,%18,%19}, t, p, 1, 1, 0;\n}\n"
    : "+f"(d[0]),"+f"(d[1]),"+f"(d[2]),"+f"(d[3]),"+f"(d[4]),"+f"(d[5]),"+f"(d[6]),"+f"(d[7]),"+f"(d[8]),"+f"(d[9]),"+f"(d[10]),"+f"(d[11]),"+f"(d[12]),"+f"(d[13]),"+f"(d[14]),"+f"(d[15]) : "r"(a0), "r"(a1), "r"(a2), "r"(a3), "r"(db));
}
__device__ __forceinline__ void wg_cv_1_0(float (&d)[128], uint32_t a0, uint32_t a1, uint32_t a2, uint32_t a3, uint32_t db) {
  asm volatile("{\n.reg .pred p;\n.reg .b64 t;\nsetp.ne.b32 p, 0, 0;\nmov.b64 t, {%20, 8};\n"
    "wgmma.mma_async.sync.aligned.m64n32k16.f32.bf16.bf16 {%0,%1,%2,%3,%4,%5,%6,%7,%8,%9,%10,%11,%12,%13,%14,%15}, {%16,%17,%18,%19}, t, p, 1, 1, 0;\n}\n"
    : "+f"(d[16]),"+f"(d[17]),"+f"(d[18]),"+f"(d[19]),"+f"(d[20]),"+f"(d[21]),"+f"(d[22]),"+f"(d[23]),"+f"(d[24]),"+f"(d[25]),"+f"(d[26]),"+f"(d[27]),"+f"(d[28]),"+f"(d[29]),"+f"(d[30]),"+f"(d[31]) : "r"(a0), "r"(a1), "r"(a2), "r"(a3), "r"(db));
}
__device__ __forceinline__ void wg_cv_1_1(float (&d)[128], uint32_t a0, uint32_t a1, uint32_t a2, uint32_t a3, uint32_t db) {
  asm volatile("{\n.reg .pred p;\n.reg .b64 t;\nsetp.ne.b32 p, 1, 0;\nmov.b64 t, {%20, 8};\n"
    "wgmma.mma_async.sync.aligned.m64n32k16.f32.bf16.bf16 {%0,%1,%2,%3,%4,%5,%6,%7,%8,%9,%10,%11,%12,%13,%14,%15}, {%16,%17,%18,%19}, t, p, 1, 1, 0;\n}\n"
    : "+f"(d[16]),"+f"(d[17]),"+f"(d[18]),"+f"(d[19]),"+f"(d[20]),"+f"(d[21]),"+f"(d[22]),"+f"(d[23]),"+f"(d[24]),"+f"(d[25]),"+f"(d[26]),"+f"(d[27]),"+f"(d[28]),"+f"(d[29]),"+f"(d[30]),"+f"(d[31]) : "r"(a0), "r"(a1), "r"(a2), "r"(a3), "r"(db));
}
__device__ __forceinline__ void wg_cv_2_0(float (&d)[128], uint32_t a0, uint32_t a1, uint32_t a2, uint32_t a3, uint32_t db) {
  asm volatile("{\n.reg .pred p;\n.reg .b64 t;\nsetp.ne.b32 p, 0, 0;\nmov.b64 t, {%20, 8};\n"
    "wgmma.mma_async.sync.aligned.m64n32k16.f32.bf16.bf16 {%0,%1,%2,%3,%4,%5,%6,%7,%8,%9,%10,%11,%12,%13,%14,%15}, {%16,%17,%18,%19}, t, p, 1, 1, 0;\n}\n"
    : "+f"(d[32]),"+f"(d[33]),"+f"(d[34]),"+f"(d[35]),"+f"(d[36]),"+f"(d[37]),"+f"(d[38]),"+f"(d[39]),"+f"(d[40]),"+f"(d[41]),"+f"(d[42]),"+f"(d[43]),"+f"(d[44]),"+f"(d[45]),"+f"(d[46]),"+f"(d[47]) : "r"(a0), "r"(a1), "r"(a2), "r"(a3), "r"(db));
}
__device__ __forceinline__ void wg_cv_2_1(float (&d)[128], uint32_t a0, uint32_t a1, uint32_t a2, uint32_t a3, uint32_t db) {
  asm volatile("{\n.reg .pred p;\n.reg .b64 t;\nsetp.ne.b32 p, 1, 0;\nmov.b64 t, {%20, 8};\n"
    "wgmma.mma_async.sync.aligned.m64n32k16.f32.bf16.bf16 {%0,%1,%2,%3,%4,%5,%6,%7,%8,%9,%10,%11,%12,%13,%14,%15}, {%16,%17,%18,%19}, t, p, 1, 1, 0;\n}\n"
    : "+f"(d[32]),"+f"(d[33]),"+f"(d[34]),"+f"(d[35]),"+f"(d[36]),"+f"(d[37]),"+f"(d[38]),"+f"(d[39]),"+f"(d[40]),"+f"(d[41]),"+f"(d[42]),"+f"(d[43]),"+f"(d[44]),"+f"(d[45]),"+f"(d[46]),"+f"(d[47]) : "r"(a0), "r"(a1), "r"(a2), "r"(a3), "r"(db));
}
__device__ __forceinline__ void wg_cv_3_0(float (&d)[128], uint32_t a0, uint32_t a1, uint32_t a2, uint32_t a3, uint32_t db) {
  asm volatile("{\n.reg .pred p;\n.reg .b64 t;\nsetp.ne.b32 p, 0, 0;\nmov.b64 t, {%20, 8};\n"
    "wgmma.mma_async.sync.aligned.m64n32k16.f32.bf16.bf16 {%0,%1,%2,%3,%4,%5,%6,%7,%8,%9,%10,%11,%12,%13,%14,%15}, {%16,%17,%18,%19}, t, p, 1, 1, 0;\n}\n"
    : "+f"(d[48]),"+f"(d[49]),"+f"(d[50]),"+f"(d[51]),"+f"(d[52]),"+f"(d[53]),"+f"(d[54]),"+f"(d[55]),"+f"(d[56]),"+f"(d[57]),"+f"(d[58]),"+f"(d[59]),"+f"(d[60]),"+f"(d[61]),"+f"(d[62]),"+f"(d[63]) : "r"(a0), "r"(a1), "r"(a2), "r"(a3), "r"(db));
}
__device__ __forceinline__ void wg_cv_3_1(float (&d)[128], uint32_t a0, uint32_t a1, uint32_t a2, uint32_t a3, uint32_t db) {
  asm volatile("{\n.reg .pred p;\n.reg .b64 t;\nsetp.ne.b32 p, 1, 0;\nmov.b64 t, {%20, 8};\n"
    "wgmma.mma_async.sync.aligned.m64n32k16.f32.bf16.bf16 {%0,%1,%2,%3,%4,%5,%6,%7,%8,%9,%10,%11,%12,%13,%14,%15}, {%16,%17,%18,%19}, t, p, 1, 1, 0;\n}\n"
    : "+f"(d[48]),"+f"(d[49]),"+f"(d[50]),"+f"(d[51]),"+f"(d[52]),"+f"(d[53]),"+f"(d[54]),"+f"(d[55]),"+f"(d[56]),"+f"(d[57]),"+f"(d[58]),"+f"(d[59]),"+f"(d[60]),"+f"(d[61]),"+f"(d[62]),"+f"(d[63]) : "r"(a0), "r"(a1), "r"(a2), "r"(a3), "r"(db));
}
__device__ __forceinline__ void wg_cv_4_0(float (&d)[128], uint32_t a0, uint32_t a1, uint32_t a2, uint32_t a3, uint32_t db) {
  asm volatile("{\n.reg .pred p;\n.reg .b64 t;\nsetp.ne.b32 p, 0, 0;\nmov.b64 t, {%20, 8};\n"
    "wgmma.mma_async.sync.aligned.m64n32k16.f32.bf16.bf16 {%0,%1,%2,%3,%4,%5,%6,%7,%8,%9,%10,%11,%12,%13,%14,%15}, {%16,%17,%18,%19}, t, p, 1, 1, 0;\n}\n"
    : "+f"(d[64]),"+f"(d[65]),"+f"(d[66]),"+f"(d[67]),"+f"(d[68]),"+f"(d[69]),"+f"(d[70]),"+f"(d[71]),"+f"(d[72]),"+f"(d[73]),"+f"(d[74]),"+f"(d[75]),"+f"(d[76]),"+f"(d[77]),"+f"(d[78]),"+f"(d[79]) : "r"(a0), "r"(a1), "r"(a2), "r"(a3), "r"(db));
}
__device__ __forceinline__ void wg_cv_4_1(float (&d)[128], uint32_t a0, uint32_t a1, uint32_t a2, uint32_t a3, uint32_t db) {
  asm volatile("{\n.reg .pred p;\n.reg .b64 t;\nsetp.ne.b32 p, 1, 0;\nmov.b64 t, {%20, 8};\n"
    "wgmma.mma_async.sync.aligned.m64n32k16.f32.bf16.bf16 {%0,%1,%2,%3,%4,%5,%6,%7,%8,%9,%10,%11,%12,%13,%14,%15}, {%16,%17,%18,%19}, t, p, 1, 1, 0;\n}\n"
    : "+f"(d[64]),"+f"(d[65]),"+f"(d[66]),"+f"(d[67]),"+f"(d[68]),"+f"(d[69]),"+f"(d[70]),"+f"(d[71]),"+f"(d[72]),"+f"(d[73]),"+f"(d[74]),"+f"(d[75]),"+f"(d[76]),"+f"(d[77]),"+f"(d[78]),"+f"(d[79]) : "r"(a0), "r"(a1), "r"(a2), "r"(a3), "r"(db));
}
__device__ __forceinline__ void wg_cv_5_0(float (&d)[128], uint32_t a0, uint32_t a1, uint32_t a2, uint32_t a3, uint32_t db) {
  asm volatile("{\n.reg .pred p;\n.reg .b64 t;\nsetp.ne.b32 p, 0, 0;\nmov.b64 t, {%20, 8};\n"
    "wgmma.mma_async.sync.aligned.m64n32k16.f32.bf16.bf16 {%0,%1,%2,%3,%4,%5,%6,%7,%8,%9,%10,%11,%12,%13,%14,%15}, {%16,%17,%18,%19}, t, p, 1, 1, 0;\n}\n"
    : "+f"(d[80]),"+f"(d[81]),"+f"(d[82]),"+f"(d[83]),"+f"(d[84]),"+f"(d[85]),"+f"(d[86]),"+f"(d[87]),"+f"(d[88]),"+f"(d[89]),"+f"(d[90]),"+f"(d[91]),"+f"(d[92]),"+f"(d[93]),"+f"(d[94]),"+f"(d[95]) : "r"(a0), "r"(a1), "r"(a2), "r"(a3), "r"(db));
}
__device__ __forceinline__ void wg_cv_5_1(float (&d)[128], uint32_t a0, uint32_t a1, uint32_t a2, uint32_t a3, uint32_t db) {
  asm volatile("{\n.reg .pred p;\n.reg .b64 t;\nsetp.ne.b32 p, 1, 0;\nmov.b64 t, {%20, 8};\n"
    "wgmma.mma_async.sync.aligned.m64n32k16.f32.bf16.bf16 {%0,%1,%2,%3,%4,%5,%6,%7,%8,%9,%10,%11,%12,%13,%14,%15}, {%16,%17,%18,%19}, t, p, 1, 1, 0;\n}\n"
    : "+f"(d[80]),"+f"(d[81]),"+f"(d[82]),"+f"(d[83]),"+f"(d[84]),"+f"(d[85]),"+f"(d[86]),"+f"(d[87]),"+f"(d[88]),"+f"(d[89]),"+f"(d[90]),"+f"(d[91]),"+f"(d[92]),"+f"(d[93]),"+f"(d[94]),"+f"(d[95]) : "r"(a0), "r"(a1), "r"(a2), "r"(a3), "r"(db));
}
__device__ __forceinline__ void wg_cv_6_0(float (&d)[128], uint32_t a0, uint32_t a1, uint32_t a2, uint32_t a3, uint32_t db) {
  asm volatile("{\n.reg .pred p;\n.reg .b64 t;\nsetp.ne.b32 p, 0, 0;\nmov.b64 t, {%20, 8};\n"
    "wgmma.mma_async.sync.aligned.m64n32k16.f32.bf16.bf16 {%0,%1,%2,%3,%4,%5,%6,%7,%8,%9,%10,%11,%12,%13,%14,%15}, {%16,%17,%18,%19}, t, p, 1, 1, 0;\n}\n"
    : "+f"(d[96]),"+f"(d[97]),"+f"(d[98]),"+f"(d[99]),"+f"(d[100]),"+f"(d[101]),"+f"(d[102]),"+f"(d[103]),"+f"(d[104]),"+f"(d[105]),"+f"(d[106]),"+f"(d[107]),"+f"(d[108]),"+f"(d[109]),"+f"(d[110]),"+f"(d[111]) : "r"(a0), "r"(a1), "r"(a2), "r"(a3), "r"(db));
}
__device__ __forceinline__ void wg_cv_6_1(float (&d)[128], uint32_t a0, uint32_t a1, uint32_t a2, uint32_t a3, uint32_t db) {
  asm volatile("{\n.reg .pred p;\n.reg .b64 t;\nsetp.ne.b32 p, 1, 0;\nmov.b64 t, {%20, 8};\n"
    "wgmma.mma_async.sync.aligned.m64n32k16.f32.bf16.bf16 {%0,%1,%2,%3,%4,%5,%6,%7,%8,%9,%10,%11,%12,%13,%14,%15}, {%16,%17,%18,%19}, t, p, 1, 1, 0;\n}\n"
    : "+f"(d[96]),"+f"(d[97]),"+f"(d[98]),"+f"(d[99]),"+f"(d[100]),"+f"(d[101]),"+f"(d[102]),"+f"(d[103]),"+f"(d[104]),"+f"(d[105]),"+f"(d[106]),"+f"(d[107]),"+f"(d[108]),"+f"(d[109]),"+f"(d[110]),"+f"(d[111]) : "r"(a0), "r"(a1), "r"(a2), "r"(a3), "r"(db));
}
__device__ __forceinline__ void wg_cv_7_0(float (&d)[128], uint32_t a0, uint32_t a1, uint32_t a2, uint32_t a3, uint32_t db) {
  asm volatile("{\n.reg .pred p;\n.reg .b64 t;\nsetp.ne.b32 p, 0, 0;\nmov.b64 t, {%20, 8};\n"
    "wgmma.mma_async.sync.aligned.m64n32k16.f32.bf16.bf16 {%0,%1,%2,%3,%4,%5,%6,%7,%8,%9,%10,%11,%12,%13,%14,%15}, {%16,%17,%18,%19}, t, p, 1, 1, 0;\n}\n"
    : "+f"(d[112]),"+f"(d[113]),"+f"(d[114]),"+f"(d[115]),"+f"(d[116]),"+f"(d[117]),"+f"(d[118]),"+f"(d[119]),"+f"(d[120]),"+f"(d[121]),"+f"(d[122]),"+f"(d[123]),"+f"(d[124]),"+f"(d[125]),"+f"(d[126]),"+f"(d[127]) : "r"(a0), "r"(a1), "r"(a2), "r"(a3), "r"(db));
}
__device__ __forceinline__ void wg_cv_7_1(float (&d)[128], uint32_t a0, uint32_t a1, uint32_t a2, uint32_t a3, uint32_t db) {
  asm volatile("{\n.reg .pred p;\n.reg .b64 t;\nsetp.ne.b32 p, 1, 0;\nmov.b64 t, {%20, 8};\n"
    "wgmma.mma_async.sync.aligned.m64n32k16.f32.bf16.bf16 {%0,%1,%2,%3,%4,%5,%6,%7,%8,%9,%10,%11,%12,%13,%14,%15}, {%16,%17,%18,%19}, t, p, 1, 1, 0;\n}\n"
    : "+f"(d[112]),"+f"(d[113]),"+f"(d[114]),"+f"(d[115]),"+f"(d[116]),"+f"(d[117]),"+f"(d[118]),"+f"(d[119]),"+f"(d[120]),"+f"(d[121]),"+f"(d[122]),"+f"(d[123]),"+f"(d[124]),"+f"(d[125]),"+f"(d[126]),"+f"(d[127]) : "r"(a0), "r"(a1), "r"(a2), "r"(a3), "r"(db));
}
template <class F, class T> __device__ __forceinline__ void conv_chain_1(float (&d)[128], uint32_t (&a)[64], uint32_t db, uint32_t ao, uint32_t ab, F hand, T dead) {
  wg_cv_7_0(d, a[60], a[61], a[62], a[63], db + 0);
  wg_cv_6_0(d, a[52], a[53], a[54], a[55], db + 0);
  dead();
  wg_cv_7_1(d, a[56], a[57], a[58], a[59], db + 16);
  wg_cv_5_0(d, a[44], a[45], a[46], a[47], db + 0);
  wg_cv_6_1(d, a[48], a[49], a[50], a[51], db + 16);
  wg_cv_7_1(d, a[52], a[53], a[54], a[55], db + 32);
  wg_cv_5_1(d, a[40], a[41], a[42], a[43], db + 16);
  wg_cv_6_1(d, a[44], a[45], a[46], a[47], db + 32);
  wg_cv_7_1(d, a[48], a[49], a[50], a[51], db + 48);
  wg_cv_6_1(d, a[40], a[41], a[42], a[43], db + 48);
  wg_cv_7_1(d, a[44], a[45], a[46], a[47], db + 64);
  wg_cv_7_1(d, a[40], a[41], a[42], a[43], db + 80);
  wg_commit();
  wg_cv_7_1(d, a[36], a[37], a[38], a[39], db + 96);
  wg_cv_6_1(d, a[36], a[37], a[38], a[39], db + 64);
  wg_cv_5_1(d, a[36], a[37], a[38], a[39], db + 32);
  wg_cv_4_0(d, a[36], a[37], a[38], a[39], db + 0);
  wg_commit(); wg_wait<1>();
  wg_cv_7_1(d, a[32], a[33], a[34], a[35], db + 112);
  wg_cv_6_1(d, a[32], a[33], a[34], a[35], db + 80);
  wg_cv_5_1(d, a[32], a[33], a[34], a[35], db + 48);
  a[60] = lds32(ab + (3840));
  a[61] = lds32(ab + (3968));
  a[62] = lds32(ab + (3824));
  a[63] = lds32(ab + (3952));
  wg_cv_4_1(d, a[32], a[33], a[34], a[35], db + 16);
  wg_cv_7_1(d, a[28], a[29], a[30], a[31], db + 128);
  wg_cv_6_1(d, a[28], a[29], a[30], a[31], db + 96);
  wg_cv_5_1(d, a[28], a[29], a[30], a[31], db + 64);
  a[56] = lds32(ab + (3584));
  a[57] = lds32(ab + (3712));
  a[58] = lds32(ab + (3568));
  a[59] = lds32(ab + (3696));
  wg_cv_4_1(d, a[28], a[29], a[30], a[31], db + 32);
  wg_cv_3_0(d, a[28], a[29], a[30], a[31], db + 0);
  wg_cv_7_1(d, a[24], a[25], a[26], a[27], db + 144);
  wg_cv_6_1(d, a[24], a[25], a[26], a[27], db + 112);
  a[52] = lds32(ab + (3328));
  a[53] = lds32(ab + (3456));
  a[54] = lds32(ab + (3312));
  a[55] = lds32(ab + (3440));
  wg_cv_5_1(d, a[24], a[25], a[26], a[27], db + 80);
  wg_cv_4_1(d, a[24], a[25], a[26], a[27], db + 48);
  wg_cv_3_1(d, a[24], a[25], a[26], a[27], db + 16);
  wg_commit();
  wg_cv_7_1(d, a[20], a[21], a[22], a[23], db + 160);
  wg_cv_6_1(d, a[20], a[21], a[22], a[23], db + 128);
  wg_cv_5_1(d, a[20], a[21], a[22], a[23], db + 96);
  wg_cv_4_1(d, a[20], a[21], a[22], a[23], db + 64);
  wg_commit(); wg_wait<1>();
  a[48] = lds32(ab + (3072));
  a[49] = lds32(ab + (3200));
  a[50] = lds32(ab + (3056));
  a[51] = lds32(ab + (3184));
  wg_cv_3_1(d, a[20], a[21], a[22], a[23], db + 32);
  wg_cv_2_0(d, a[20], a[21], a[22], a[23], db + 0);
  wg_cv_7_1(d, a[16], a[17], a[18], a[19], db + 176);
  wg_cv_6_1(d, a[16], a[17], a[18], a[19], db + 144);
  a[44] = lds32(ab + (2816));
  a[45] = lds32(ab + (2944));
  a[46] = lds32(ab + (2800));
  a[47] = lds32(ab + (2928));
  wg_cv_5_1(d, a[16], a[17], a[18], a[19], db + 112);
  wg_cv_4_1(d, a[16], a[17], a[18], a[19], db + 80);
  wg_cv_3_1(d, a[16], a[17], a[18], a[19], db + 48);
  wg_cv_2_1(d, a[16], a[17], a[18], a[19], db + 16);
  a[40] = lds32(ab + (2560));
  a[41] = lds32(ab + (2688));
  a[42] = lds32(ab + (2544));
  a[43] = lds32(ab + (2672));
  wg_cv_7_1(d, a[12], a[13], a[14], a[15], db + 192);
  wg_cv_6_1(d, a[12], a[13], a[14], a[15], db + 160);
  wg_cv_5_1(d, a[12], a[13], a[14], a[15], db + 128);
  wg_cv_4_1(d, a[12], a[13], a[14], a[15], db + 96);
  a[36] = lds32(ab + (2304));
  a[37] = lds32(ab + (2432));
  a[38] = lds32(ab + (2288));
  a[39] = lds32(ab + (2416));
  wg_cv_3_1(d, a[12], a[13], a[14], a[15], db + 64);
  wg_cv_2_1(d, a[12], a[13], a[14], a[15], db + 32);
  wg_cv_1_0(d, a[12], a[13], a[14], a[15], db + 0);
  wg_cv_7_1(d, a[8], a[9], a[10], a[11], db + 208);
  a[32] = lds32(ab + (2048));
  a[33] = lds32(ab + (2176));
  a[34] = lds32(ab + (2032));
  a[35] = lds32(ab + (2160));
  wg_cv_6_1(d, a[8], a[9], a[10], a[11], db + 176);
  wg_cv_5_1(d, a[8], a[9], a[10], a[11], db + 144);
  wg_cv_4_1(d, a[8], a[9], a[10], a[11], db + 112);
  wg_cv_3_1(d, a[8], a[9], a[10], a[11], db + 80);
  a[28] = lds32(ab + (1792));
  a[29] = lds32(ab + (1920));
  a[30] = lds32(ab + (1776));
  a[31] = lds32(ab + (1904));
  wg_cv_2_1(d, a[8], a[9], a[10], a[11], db + 48);
  wg_cv_1_1(d, a[8], a[9], a[10], a[11], db + 16);
  wg_commit();
  wg_cv_7_1(d, a[4], a[5], a[6], a[7], db + 224);
  wg_cv_6_1(d, a[4], a[5], a[6], a[7], db + 192);
  wg_cv_5_1(d, a[4], a[5], a[6], a[7], db + 160);
  wg_cv_4_1(d, a[4], a[5], a[6], a[7], db + 128);
  wg_commit(); wg_wait<1>();
  a[24] = lds32(ab + (1536));
  a[25] = lds32(ab + (1664));
  a[26] = lds32(ab + (1520));
  a[27] = lds32(ab + (1648));
  hand();
  wg_cv_3_1(d, a[4], a[5], a[6], a[7], db + 96);
  wg_cv_2_1(d, a[4], a[5], a[6], a[7], db + 64);
  wg_cv_1_1(d, a[4], a[5], a[6], a[7], db + 32);
  wg_cv_0_0(d, a[4], a[5], a[6], a[7], db + 0);
  a[20] = lds32(ab + (1280));
  a[21] = lds32(ab + (1408));
  a[22] = lds32(ab + (1264));
  a[23] = lds32(ab + (1392));
  wg_cv_7_1(d, a[0], a[1], a[2], a[3], db + 240);
  wg_cv_6_1(d, a[0], a[1], a[2], a[3], db + 208);
  wg_cv_5_1(d, a[0], a[1], a[2], a[3], db + 176);
  wg_cv_4_1(d, a[0], a[1], a[2], a[3], db + 144);
  a[16] = lds32(ab + (1024));
  a[17] = lds32(ab + (1152));
  a[18] = lds32(ab + (1008));
  a[19] = lds32(ab + (1136));
  wg_cv_3_1(d, a[0], a[1], a[2], a[3], db + 112);
  wg_cv_2_1(d, a[0], a[1], a[2], a[3], db + 80);
  wg_cv_1_1(d, a[0], a[1], a[2], a[3], db + 48);
  wg_cv_0_1(d, a[0], a[1], a[2], a[3], db + 16);
  wg_commit();
  a[12] = lds32(ab + (768));
  a[13] = lds32(ab + (896));
  a[14] = lds32(ab + (752));
  a[15] = lds32(ab + (880));
  a[8] = lds32(ab + (512));
  a[9] = lds32(ab + (640));
  a[10] = lds32(ab + (496));
  a[11] = lds32(ab + (624));
}
template <class F, class T> __device__ __forceinline__ void conv_chain_0(float (&d)[128], uint32_t (&a)[64], uint32_t db, uint32_t ao, uint32_t ab, F hand, T dead) {
  wg_cv_7_0(d, a[60], a[61], a[62], a[63], db + 0);
  wg_cv_6_0(d, a[52], a[53], a[54], a[55], db + 0);
  dead();
  wg_cv_7_1(d, a[56], a[57], a[58], a[59], db + 16);
  wg_cv_5_0(d, a[44], a[45], a[46], a[47], db + 0);
  wg_cv_6_1(d, a[48], a[49], a[50], a[51], db + 16);
  wg_cv_7_1(d, a[52], a[53], a[54], a[55], db + 32);
  wg_cv_5_1(d, a[40], a[41], a[42], a[43], db + 16);
  wg_cv_6_1(d, a[44], a[45], a[46], a[47], db + 32);
  wg_cv_7_1(d, a[48], a[49], a[50], a[51], db + 48);
  wg_cv_6_1(d, a[40], a[41], a[42], a[43], db + 48);
  wg_cv_7_1(d, a[44], a[45], a[46], a[47], db + 64);
  wg_cv_7_1(d, a[40], a[41], a[42], a[43], db + 80);
  wg_commit();
  wg_cv_7_1(d, a[36], a[37], a[38], a[39], db + 96);
  wg_cv_6_1(d, a[36], a[37], a[38], a[39], db + 64);
  wg_cv_5_1(d, a[36], a[37], a[38], a[39], db + 32);
  wg_cv_4_0(d, a[36], a[37], a[38], a[39], db + 0);
  wg_cv_7_1(d, a[32], a[33], a[34], a[35], db + 112);
  wg_cv_6_1(d, a[32], a[33], a[34], a[35], db + 80);
  wg_cv_5_1(d, a[32], a[33], a[34], a[35], db + 48);
  wg_cv_4_1(d, a[32], a[33], a[34], a[35], db + 16);
  wg_cv_7_1(d, a[28], a[29], a[30], a[31], db + 128);
  wg_cv_6_1(d, a[28], a[29], a[30], a[31], db + 96);
  wg_cv_5_1(d, a[28], a[29], a[30], a[31], db + 64);
  wg_cv_4_1(d, a[28], a[29], a[30], a[31], db + 32);
  wg_cv_3_0(d, a[28], a[29], a[30], a[31], db + 0);
  wg_cv_7_1(d, a[24], a[25], a[26], a[27], db + 144);
  wg_cv_6_1(d, a[24], a[25], a[26], a[27], db + 112);
  wg_cv_5_1(d, a[24], a[25], a[26], a[27], db + 80);
  wg_cv_4_1(d, a[24], a[25], a[26], a[27], db + 48);
  wg_cv_3_1(d, a[24], a[25], a[26], a[27], db + 16);
  wg_commit();
  wg_cv_7_1(d, a[20], a[21], a[22], a[23], db + 160);
  wg_cv_6_1(d, a[20], a[21], a[22], a[23], db + 128);
  wg_cv_5_1(d, a[20], a[21], a[22], a[23], db + 96);
  wg_cv_4_1(d, a[20], a[21], a[22], a[23], db + 64);
  wg_cv_3_1(d, a[20], a[21], a[22], a[23], db + 32);
  wg_cv_2_0(d, a[20], a[21], a[22], a[23], db + 0);
  wg_cv_7_1(d, a[16], a[17], a[18], a[19], db + 176);
  wg_cv_6_1(d, a[16], a[17], a[18], a[19], db + 144);
  wg_cv_5_1(d, a[16], a[17], a[18], a[19], db + 112);
  wg_cv_4_1(d, a[16], a[17], a[18], a[19], db + 80);
  wg_cv_3_1(d, a[16], a[17], a[18], a[19], db + 48);
  wg_cv_2_1(d, a[16], a[17], a[18], a[19], db + 16);
  wg_cv_7_1(d, a[12], a[13], a[14], a[15], db + 192);
  wg_cv_6_1(d, a[12], a[13], a[14], a[15], db + 160);
  wg_cv_5_1(d, a[12], a[13], a[14], a[15], db + 128);
  wg_cv_4_1(d, a[12], a[13], a[14], a[15], db + 96);
  wg_cv_3_1(d, a[12], a[13], a[14], a[15], db + 64);
  wg_cv_2_1(d, a[12], a[13], a[14], a[15], db + 32);
  wg_cv_1_0(d, a[12], a[13], a[14], a[15], db + 0);
  wg_cv_7_1(d, a[8], a[9], a[10], a[11], db + 208);
  wg_cv_6_1(d, a[8], a[9], a[10], a[11], db + 176);
  wg_cv_5_1(d, a[8], a[9], a[10], a[11], db + 144);
  wg_cv_4_1(d, a[8], a[9], a[10], a[11], db + 112);
  wg_cv_3_1(d, a[8], a[9], a[10], a[11], db + 80);
  wg_cv_2_1(d, a[8], a[9], a[10], a[11], db + 48);
  wg_cv_1_1(d, a[8], a[9], a[10], a[11], db + 16);
  wg_commit();
  wg_cv_7_1(d, a[4], a[5], a[6], a[7], db + 224);
  wg_cv_6_1(d, a[4], a[5], a[6], a[7], db + 192);
  wg_cv_5_1(d, a[4], a[5], a[6], a[7], db + 160);
  wg_cv_4_1(d, a[4], a[5], a[6], a[7], db + 128);
  hand();
  wg_cv_3_1(d, a[4], a[5], a[6], a[7], db + 96);
  wg_cv_2_1(d, a[4], a[5], a[6], a[7], db + 64);
  wg_cv_1_1(d, a[4], a[5], a[6], a[7], db + 32);
  wg_cv_0_0(d, a[4], a[5], a[6], a[7], db + 0);
  wg_cv_7_1(d, a[0], a[1], a[2], a[3], db + 240);
  wg_cv_6_1(d, a[0], a[1], a[2], a[3], db + 208);
  wg_cv_5_1(d, a[0], a[1], a[2], a[3], db + 176);
  wg_cv_4_1(d, a[0], a[1], a[2], a[3], db + 144);
  wg_cv_3_1(d, a[0], a[1], a[2], a[3], db + 112);
  wg_cv_2_1(d, a[0], a[1], a[2], a[3], db + 80);
  wg_cv_1_1(d, a[0], a[1], a[2], a[3], db + 48);
  wg_cv_0_1(d, a[0], a[1], a[2], a[3], db + 16);
  wg_commit();
}
constexpr bool CV_OWN = false;
constexpr int CV_RELOADED = 2;

struct Params {
  const __nv_bfloat16 *q, *k, *v, *shift_k, *ssm_k, *ssm_D, *w1, *b1, *w2, *b2;
  __nv_bfloat16* out;
};
struct Maps { CUtensorMap q0, w1, w1x, k, v, hs, hx, ha, w2, w2x, kvs, qf, y, out; };

__global__ void __cluster_dims__(2, 1, 1) __launch_bounds__(384, 1) h3_kernel(const __grid_constant__ Maps M, const Params P) {
  extern __shared__ __align__(1024) uint8_t smem_raw[];
  constexpr uint32_t sc = 1024;
  const int tid = threadIdx.x, lane = tid & 31;
  if (tid == 0) { prefetch_map(&M.q0); prefetch_map(&M.w1); prefetch_map(&M.w1x); }
  const int warp = __shfl_sync(0xffffffffu, tid >> 5, 0);
  const uint32_t sb = __shfl_sync(0xffffffffu, s32(smem_raw), 0);
  const int b = blockIdx.x, pr = b >> 1;
  const int t7q = ((pr - 36) * 37) >> 8;
  const int G = pr < 4 ? 0 : (pr < 36 ? (pr - 4) & 7 : pr - 35 - 7 * t7q), gi = pr < 4 ? 4 + pr : (pr < 36 ? (pr - 4) >> 3 : 4 + t7q);
  const int kh = b & 1, nt = (G & 1) * 2 + (gi & 1), rb = (G >> 1) * 4 + (gi >> 1);
  const int dir = (G ^ (G >> 1)) & 1, ri = (gi & 1) * 2 + kh, ci = (G >> 2) * 4 + (gi >> 1);
  const uint32_t gmap = (nt & 1) ? 0x03412u : 0x43210u;
  const int j = kh * 4 + nt;
  const uint32_t bar = sb + M_BAR;
  auto BAR = [&](int i) { return bar + 8 * i; };
  auto g1_load = [&](int kc) {
    const uint32_t st = sb + (kc & 3) * G1_STAGE, fb = BAR(B_F1 + (kc & 3));
    const int k0 = dir && kc >= COM ? 576 + COM * 64 - kc * 64 : kc * 64;
    mbar_expect(fb, G1_TX);
    tma2d(st, &M.q0, k0, rb * 128, fb); tma2d(st + 8192, &M.q0, k0, rb * 128 + 64, fb);
    tma3d(st + 16384, &M.w1, 0, k0, 3 * j, fb);
    tma2d(st + 40960, &M.w1x, 1536 + 24 * j, k0, fb);
  };
  auto kv_load = [&](int r, int hf) {
    const uint32_t st = sb + KVS + (r < 3 ? r : r - 3) * KV_BUF, fb = BAR((hf ? B_KIN1 : B_KIN) + r);
    mbar_expect(fb, KV_BUF / 2);
    tma2d(st + 4096 + hf * 2432, &M.k, 128 * r + 64 * (b & 1), 32 * (b >> 1) + 16 * hf - 3, fb);
    tma2d(st + hf * 2048, &M.v, 128 * r + 64 * (b & 1), 32 * (b >> 1) + 16 * hf, fb);
  };
  auto conv_sum = [&](int c, int ck, bool third, uint32_t ep) {
    const uint32_t ra = sb + cv_p(c) + ck * 16;
    __nv_bfloat16* yp = g_yT + (size_t)(128 * c + b) * SL + ck * 8;
    uint4 p[2][4];
    auto ld = [&](int u) {
#pragma unroll
      for (int w = 0; w < 4; w++) p[u & 1][w] = lds128((u == 0 && ck < 2 * w) ? sb + M_ZERO : ra + u * 512 + w * (4096 - 32));
    };
    auto st = [&](int u) {
      auto sum = [&](uint32_t a0, uint32_t a1, uint32_t a2, uint32_t a3) { return badd2(badd2(badd2(a3, a2), a1), a0); };
      const uint4* r = p[u & 1];
      const uint32_t m = ~ck & 1u;
      stg128(yp + u * 256, (sum(r[0].x, r[1].x, r[2].x, r[3].x) & ~m) | (ep & m), sum(r[0].y, r[1].y, r[2].y, r[3].y), sum(r[0].z, r[1].z, r[2].z, r[3].z), sum(r[0].w, r[1].w, r[2].w, r[3].w));
    };
    ld(0); ld(1); st(0);
    if (third) ld(2);
    st(1);
    if (third) st(2);
  };
  if (warp == 8) {
    if (lane == 0) {
      TS(0);
      mbar_init(BAR(B_F0), 1); mbar_init(BAR(B_F1), 1);
    }
    __syncwarp();
    ONE(mbar_expect(BAR(B_F0), G1_TX - 8192);
        tma2d(sb, &M.q0, 0, rb * 128, BAR(B_F0));
        tma3d(sb + 16384, &M.w1, 0, 0, 3 * j, BAR(B_F0));
        tma2d(sb + 40960, &M.w1x, 1536 + 24 * j, 0, BAR(B_F0));
        mbar_expect(BAR(B_F1), 8192);
        tma2d(sb + 8192, &M.q0, 0, rb * 128 + 64, BAR(B_F1));
        for (int s = 1; s < 4; s++) mbar_init(BAR(B_F1 + s), 1));
    bar_arrive(NB_INIT, 384);
    ONE(for (int s = 1; s <= PRO; s++) g1_load(s));
  } else {
    const int blk = warp - (warp > 8);
    ONE(for (int i = 0; i < 8; i++) mbar_init(BAR(8 * blk + i), blk < 2 ? 8 : (blk < 5 ? 4 : 1));
        asm volatile("fence.mbarrier_init.release.cluster;" ::: "memory"));
    bar_sync(NB_INIT, 384);
  }
  if ((sb & 0xFFFFFFu) != sc) { if (warp == 8) { mbar_wait(BAR(B_F0), 0); for (int s = 0; s <= PRO; s++) mbar_wait(BAR(B_F1 + s), 0); } return; }

  if (warp >= 8) {
    asm volatile("setmaxnreg.dec.sync.aligned.u32 " REG_AUX ";");
    auto table = [&](int c, int aw) {
      const uint32_t kb = sb + cv_t(c);
      const uint32_t dd = lds32(sb + M_AUX + aw * 32 + c * 4);
      if (lane < 2) sts128(kb + lane * (KT_E - 16), 0u, 0u, 0u, 0u);
      uint4 r[8];
#pragma unroll
      for (int it = 0; it < 8; it++) r[it] = lds128(kb + KT_E + (it * 32 + lane) * 16);
      if (lane == 0) { r[0].x = __byte_perm(badd2(r[0].x, dd), r[0].x, 0x7610); sts32(kb + KT_E, r[0].x); }
#pragma unroll
      for (int it = 0; it < 8; it++) {
        const uint32_t pv = __shfl_sync(0xffffffffu, lane == 31 ? (it ? r[it ? it - 1 : 0].w : 0u) : r[it].w, lane - 1);
        sts128(kb + KT_O + (it * 32 + lane) * 16, __byte_perm(pv, r[it].x, 0x5432), __byte_perm(r[it].x, r[it].y, 0x5432),
               __byte_perm(r[it].y, r[it].z, 0x5432), __byte_perm(r[it].z, r[it].w, 0x5432));
      }
      __syncwarp();
      if (lane == 0) mbar_arrive(BAR(B_KT + c));
    };
    const int aw = warp - 9, at = tid - 288;
    auto x_load = [&](int c) { mbar_expect(BAR(B_XL + c), 4096); bulk_g2s(sb + cv_x(c) + XD, g_kvT + (size_t)(128 * c + b) * SL, 4096, BAR(B_XL + c)); };
    auto x_pad = [&](int c0, int c1) {
      if (lane < 17) for (int c = c0; c < c1; c++) sts128(sb + cv_x(c) + lane * 16, 0u, 0u, 0u, 0u);
      fence_async_smem();
      __syncwarp();
    };
    if (warp == 8) {
      if (PRO < 3) ONE(for (int s = PRO + 1; s < 4; s++) g1_load(s));
      bar_sync(NB_INIT2, 64);
      unsigned ep;
#pragma unroll
      for (int kc = 3; kc < 10; kc++) {
        if (kc == 9) {
          bar_sync(NB_INIT3, 64);
          ep = lds32(sb + M_AUX + 20);
          mbar_wait(BAR(B_RED), 0);
          float2 u[8];
#pragma unroll
          for (int i = 0; i < 8; i++) u[i] = lds64f(sb + M_RED0 + (lane & 15) * 128 + ((i + lane) & 7) * 16 + (lane >> 4) * 8);
          const float c = bf_round(u[0].x * (1.f / 40)), cc = 40.f * c * c;
          float s1 = 0.f, s2 = 0.f;
#pragma unroll
          for (int i = 0; i < 8; i++) { s1 += fmaf(-40.f, c, u[i].x); s2 += fmaf(-2.f * c, u[i].x, u[i].y) + cc; }
          const float dm = s1 * (1.f / 320);
          st_relaxed64(&g_stat[dir * SL + rb * 128 + ri * 32 + lane], tagged(c + dm, ep), tagged(fmaf(-dm, s1, s2), ep));
          ONE(mbar_arrive(BAR(B_RD)));
        }
        if (kc > 3) mbar_wait(BAR(B_E1 + (kc & 3)), (kc >> 3) & 1);
        ONE(if (kc > 3) g1_load(kc);
            for (int r = 0; r < 3; r++) if (kc == ((KV_MAP >> (4 * r)) & 15)) { kv_load(r, 0); kv_load(r, 1); }
            for (int c = 0; c < 5; c++) if (kc == ((PF_RAW >> (4 * c)) & 15)) prefetch_l2(P.ssm_k + (size_t)(128 * c + b) * SL, 4096));
      }
      ONE(prefetch_map(&M.hs); prefetch_map(&M.hx); prefetch_map(&M.ha); prefetch_map(&M.w2); prefetch_map(&M.w2x));
      {
        mbar_wait(BAR(CS_WAIT ? B_FR : B_F1), 0);
        uint32_t x[16], n = 0;
#pragma unroll 1
        while (true) {
          uint32_t bad = 0;
#pragma unroll
          for (int i = 0; i < 4; i++) {
            const uint4 v = ld_relaxed128(g_stat + (i >> 1) * SL + rb * 128 + lane * 4 + (i & 1) * 2);
            x[4 * i] = v.x; x[4 * i + 1] = v.y; x[4 * i + 2] = v.z; x[4 * i + 3] = v.w;
          }
#pragma unroll
          for (int i = 0; i < 16; i++) { x[i] ^= ep & 15u; bad |= x[i]; }
          if (__all_sync(0xffffffffu, (bad & 15u) == 0) || spin_guard(n, 0x132)) break;
          RETRY(9);
        }
        uint32_t st[4];
#pragma unroll
        for (int i = 0; i < 4; i++) {
          const float ma = __uint_as_float(x[2 * i]), mb = __uint_as_float(x[8 + 2 * i]), dl = ma - mb;
          const float m2 = fmaf(dl * dl, 160.f, __uint_as_float(x[1 + 2 * i]) + __uint_as_float(x[9 + 2 * i]));
          const float vb = bf_round(fmaxf(m2, 0.f) * (1.f / DM));
          st[i] = pack_bf16(0.5f * (ma + mb), sqrt_fast(bf_round(vb + 1e-5f)));
        }
        sts128(sb + M_STAT + lane * 16, st[0], st[1], st[2], st[3]);
        __syncwarp();
        if (lane < 2) mbar_arrive(BAR(B_BX));
      }
    } else {
      if (aw == 0) bar_arrive(NB_INIT2, 64);
      if (aw == 2) ONE(mbar_expect(BAR(B_XD), XD_N * 2048); mbar_expect(BAR(B_XD + 1), (XD_M - XD_N) * 2048); mbar_expect(BAR(B_XD + 2), (10 - XD_M) * 2048));
      if (aw == 1) mbar_wait(BAR(B_F0), 0);
      if (aw == 1) ONE(prefetch_map(&M.kvs); prefetch_map(&M.k); prefetch_map(&M.v); mbar_expect(BAR(B_SK), 2560);
                       for (int r = 0; r < 5; r++) bulk_g2s(sb + M_SK + r * 512, P.shift_k + (128 * r + 64 * (b & 1)) * 4, 512, BAR(B_SK)));
      const uint32_t dv0 = ld_relaxed32(lane < 5 ? static_cast<const void*>(P.ssm_D + 128 * lane + (b & ~1)) : &g_launch[b * 8]);
      const uint32_t b2v = ldg32(reinterpret_cast<const uint32_t*>(P.b2 + nt * 160) + ((gmap >> (4 * (min(at, 79) >> 4))) & 7) * 16 + (at & 15));
      const int l27 = min(lane, 26), col = l27 < 24 ? 192 * j + 8 * l27 : 1536 + 24 * j + 8 * (l27 - 24);
      uint4 bb;
      if (aw == 2) bb = ldg128(P.b1 + col);
      if (lane < 4) sts32(sb + M_ZERO + lane * 4, 0u);
      if (lane < 8) sts32(sb + M_AUX + aw * 32 + lane * 4, lane >= 5 ? dv0 + 1 : ((b & 1) ? dv0 >> 16 : dv0 & 0xFFFFu));
      if (at < 80) sts64f(sb + M_B2 + at * 8, 0.5f * bf_lo(b2v), 0.5f * bf_hi(b2v));
      __syncwarp();
      if (aw == 0) bar_arrive(NB_INIT3, 64);
      if (aw == 2) {
        const unsigned ep = lds32(sb + M_AUX + 64 + 20);
        const uint32_t ba = sb + M_BX + (l27 >> 2) * 512 + ((l27 & 3) << 4);
        mbar_wait(BAR(B_RED1), 0);
        const uint32_t tg = ep & 15u;
        float c0 = 0.f, c1 = 0.f;
#pragma unroll
        for (int i = 0; i < 16; i += 2) { c0 += __uint_as_float(lds32(sb + M_RED1 + i * 128 + lane * 4)); c1 += __uint_as_float(lds32(sb + M_RED1 + i * 128 + 128 + lane * 4)); }
        st_relaxed32(&g_cs[(dir * 8 + j) * 256 + ci * 32 + lane], tagged(c0 + c1, ep));
        if (lane == 0) TS(30);
        mbar_wait(BAR(B_RD), 0);
        sts128((ba + 128) ^ 16, 0u, 0u, 0u, 0u); sts128((ba + 192) ^ 16, bb.x, bb.y, bb.z, bb.w);
#pragma unroll
        for (int i = 4; i < 8; i++) sts128((ba + i * 64) ^ ((i >> 1) << 4), 0u, 0u, 0u, 0u);
        mbar_wait(BAR(CS_WAIT ? B_FR : B_F1), 0);
        auto raw_load = [&]() {
          if (!CS_WAIT) mbar_wait(BAR(B_FR), 0);
          ONE(mbar_expect(BAR(B_KRAW), KRAW_N * 4096); mbar_expect(BAR(B_KRAW + 1), (5 - KRAW_N) * 4096);
              for (int c = 0; c < 5; c++) bulk_g2s(sb + cv_t(c) + KT_E, P.ssm_k + (size_t)(128 * c + b) * SL, 4096, BAR(B_KRAW + (c >= KRAW_N))));
        };
        uint32_t x[16], n = 0;
#pragma unroll 1
        while (true) {
#pragma unroll
          for (int i = 0; i < 4; i++) {
            const uint4 v = ld_relaxed128(g_cs + ((i >> 1) * 8 + j) * 256 + l27 * 8 + (i & 1) * 4);
            x[4 * i] = v.x; x[4 * i + 1] = v.y; x[4 * i + 2] = v.z; x[4 * i + 3] = v.w;
          }
          if (!RAW_LATE && n == 0) raw_load();
          uint32_t bad = 0;
#pragma unroll
          for (int i = 0; i < 16; i++) { x[i] ^= tg; bad |= x[i]; }
          if (__all_sync(0xffffffffu, (bad & 15u) == 0) || spin_guard(n, 0x131)) break;
          RETRY(8);
        }
        if (RAW_LATE) raw_load();
        uint32_t hi[4], lo[4];
#pragma unroll
        for (int i = 0; i < 4; i++) {
          const float x0 = __uint_as_float(x[2 * i]) + __uint_as_float(x[8 + 2 * i]), x1 = __uint_as_float(x[2 * i + 1]) + __uint_as_float(x[9 + 2 * i]);
          hi[i] = pack_bf16(x0, x1); lo[i] = pack_bf16(x0 - bf_lo(hi[i]), x1 - bf_hi(hi[i]));
        }
        sts128(ba, hi[0], hi[1], hi[2], hi[3]); sts128(ba + 64, lo[0], lo[1], lo[2], lo[3]);
        fence_async_smem();
        __syncwarp();
        if (lane < 2) mbar_arrive(BAR(B_BX));
        if (lane == 0) TS(54);
      }
      if (aw < 2) {
        auto done = [&](int r) {
          bulk_wait_read();
          ONE(kv_load(r + 3, aw); TSKV);
        };
        const uint32_t par = lds32(sb + M_AUX + aw * 32 + 20) & 1u;
        bool pend = false;
        mbar_wait(BAR(B_SK), 0);
#pragma unroll 1
        for (int r = 0; r < 5; r++) {
          const int c0 = 128 * r + 64 * (b & 1);
          const uint32_t buf = sb + KVS + (r < 3 ? r : r - 3) * KV_BUF, stg = buf + aw * 2048, vb = stg + lane * 4, kb = buf + 4096 + aw * 2432 + lane * 4;
          const uint4 sk = lds128(sb + M_SK + r * 512 + lane * 16);
          const uint32_t w0 = __byte_perm(sk.x, sk.z, 0x5410), w1 = __byte_perm(sk.x, sk.z, 0x7632);
          const uint32_t w2 = __byte_perm(sk.y, sk.w, 0x5410), w3 = __byte_perm(sk.y, sk.w, 0x7632);
          mbar_wait(BAR((aw ? B_KIN1 : B_KIN) + r), 0);
          if (at == 0 && r == 0) TS(56);
          uint32_t kk[19], o[16];
#pragma unroll
          for (int i = 0; i < 19; i++) { kk[i] = lds32(kb + i * 128); if (i >= 3) o[i - 3] = lds32(vb + (i - 3) * 128); }
#pragma unroll
          for (int i = 0; i < 16; i++) o[i] = bmul2(bfma2(kk[i + 3], w0, bfma2(kk[i + 2], w1, bfma2(kk[i + 1], w2, bmul2(kk[i], w3)))), o[i]);
          __syncwarp();
          const uint32_t a0 = stg + lane * 64 + ((lane & 6) << 3);
          const uint32_t s0 = (lane & 4) ? 0x7632 : 0x5410, s1 = s0 ^ 0x2222;
#pragma unroll
          for (int hh = 0; hh < 2; hh++) {
            const uint32_t* u = o + 8 * hh;
            const uint32_t a = a0 ^ (hh << 4);
            auto nz = [&](uint32_t x) { return hh ? x : (x & ~1u) | par; };
            sts128(a, nz(__byte_perm(u[1], u[0], s0)), __byte_perm(u[3], u[2], s0), __byte_perm(u[5], u[4], s0), __byte_perm(u[7], u[6], s0));
            sts128(a ^ 32, nz(__byte_perm(u[1], u[0], s1)), __byte_perm(u[3], u[2], s1), __byte_perm(u[5], u[4], s1), __byte_perm(u[7], u[6], s1));
          }
          if (pend) done(r - 1);
          fence_async_smem();
          __syncwarp();
          ONE(tma2d_st(&M.kvs, 32 * (b >> 1) + 16 * aw, c0, stg); bulk_commit());
          pend = r < 2 && mbar_test(BAR((aw ? B_KIN1 : B_KIN) + r + 1), 0);
          if (!pend && r < 2) done(r);
        }
      }
      if (aw == 2) {
        mbar_wait(BAR(B_FR + 1), 0);
        ONE(x_load(0));
        x_pad(0, 4);
      }
    }
#pragma unroll 1
    for (uint32_t t = (TB_MAP >> (8 * (warp - 8))) & 255; t & 15; t >>= 4) {
      const int c = (t & 15) - 1;
      mbar_wait(BAR(B_KRAW + (c >= KRAW_N)), 0);
      if (lane == 0 && c == 1) TS(35);
      table(c, max(aw, 0));
      if (lane == 0 && c == 2) TS(55);
    }
    const unsigned ep = lds32(sb + M_AUX + max(aw, 0) * 32 + 20);
    if (warp == 8) {
      const int hc = j * 192, hx = 1536 + j * 24;
#pragma unroll 1
      for (int n = 0; n < 32; n += 4) {
        const int i = (H_ORD >> n) & 7, hw = i >> 2, blk = i & 3;
        if (n == 4 * W2_PF) ONE(prefetch_l2(P.w2 + (size_t)b * (FF * DM / NCTA), FF * DM / NCTA * 2));
        mbar_wait(BAR(B_HB + i), 0);
        fence_async_smem();
        asm volatile("cp.async.bulk.wait_group %0;" ::"n"(H_FLY - 1) : "memory");
        ONE(tma2d_st(blk < 3 ? &M.hs : &M.hx, blk < 3 ? hc + blk * 64 : hx, rb * 128 + hw * 64, sb + hw * HST + blk * 8192); bulk_commit());
      }
      const int cf = (nt * 160 + (nt & 1) * 32) >> 6, ch = (nt >> 1) * 320 + 128;
      auto g2_k = [&](int kc) { return (kc < NSH ? kh * NSH + kc : NSH + kc) * 64; };
      auto g2_load_b = [&](int kc) {
        const int s = kc & 3;
        const uint32_t fb = BAR(B_F2 + s);
        mbar_expect(fb, kc >= NSH ? 8192 + 24576 : 16384 + 24576);
        tma3d(sb + g2_b(s), &M.w2, 0, g2_k(kc), cf, fb);
        tma2d(sb + g2_b(s) + 16384, &M.w2x, ch, g2_k(kc), fb);
      };
      auto g2_load_a = [&](int kc) {
        const int s = kc & 3, o = kc >= NSH ? kh : 0;
        tma2d(sb + g2_a(s) + o * 8192, kc >= NSH ? &M.hs : &M.ha, g2_k(kc), rb * 128 + o * 64, BAR(B_F2 + s));
      };
      bulk_wait_all();
      ONE(g2_load_b(0); g2_load_b(1));
      fence_release();
      ONE(signal_cnt(CNT_H + rb); TS(37));
      wait_cnt(CNT_H + rb, 8 * ep);
      ONE(TS(39); g2_load_a(0); g2_load_a(1); prefetch_map(&M.qf); prefetch_map(&M.y); prefetch_map(&M.out));
      mbar_wait(BAR(B_KD), 0);
      ONE(g2_load_b(3));
      mbar_wait(BAR(B_TD + 1), 0);
      fence_async_smem();
      ONE(g2_load_b(2); g2_load_a(2));
      mbar_wait(BAR(B_SD + 3), 0);
      ONE(mbar_expect(BAR(B_FINQ), 20480);
          for (int i = 0; i < 5; i++) tma2d(sb + FIN_Q + i * 4096, &M.qf, nt * 160 + ((gmap >> (4 * i)) & 7) * 32, rb * 128 + kh * 64, BAR(B_FINQ)));
      mbar_wait(BAR(B_RF + 2), 0);
      ONE(g2_load_a(3); TS(38));
#pragma unroll 1
      for (int kc = 4; kc < NST; kc++) {
        mbar_wait(BAR(B_E2 + (kc & 3)), ((kc >> 2) - 1) & 1);
                ONE(g2_load_a(kc); g2_load_b(kc); if (kc >= Y_KC && kc < Y_KC + 3) mbar_arrive(BAR(B_YSLOT + kc - Y_KC)));
      }
      if (lane == 0) g_launch[b * 8] = ep;
#pragma unroll 1
      for (int i = 0; i < 5; i++) {
        const int gi = (gmap >> (4 * i)) & 7;
        mbar_wait(BAR(B_OUT + i), 0);
        fence_async_smem();
        ONE(tma2d_st(&M.out, nt * 160 + gi * 32, rb * 128 + kh * 64, sb + FIN_Q + i * 4096));
      }
      ONE(bulk_commit());
      bulk_wait_read();
    } else {
      if (aw < 2) { bulk_wait_read(); __syncwarp(); if (lane < 2) mbar_arrive(BAR(B_KD)); if (at == 0) TS(34); }
      if (aw == 2) {
#pragma unroll 1
        for (int c = 0, n = 0; c < 5;) {
          if (n == 0 && c < 4) {
            mbar_wait(BAR((X_TRIG >> (8 * c)) & 255), 0);
            if (c == 3) { mbar_wait(BAR(B_KD), 0); x_pad(4, 5); }
          }
          if (n || c < 4) ONE(x_load(n ? c : c + 1));
          mbar_wait(BAR(B_XL + c), n & 1);
          const uint32_t a = sb + cv_x(c) + XD + lane * 32;
          const uint32_t v = ((lds32(a) ^ ep) | (lds32(a + 1024) ^ ep) | (lds32(a + 2048) ^ ep) | (lds32(a + 3072) ^ ep)) & 1u;
          if (__all_sync(0xffffffffu, v == 0) || n > 100000) {
            ONE(mbar_arrive(BAR(B_XF + c)); if (c == 0) TS(36); if (c >= 3) TS(28 + c));
            c++; n = 0;
          } else {
            n++;
            RETRY(c);
          }
        }
      }
      if (RED_GATE) mbar_wait(BAR(RED_GATE == 1 ? B_TD + 1 : B_SD + RED_GATE - 1), 0);
#pragma unroll 1
      for (int c = 0; c < 5; c++) {
        mbar_wait(BAR(B_SD + c), 0);
        conv_sum(c, aw * 96 + lane, aw < 2, ep);
        __syncwarp();
        if (c < 3 && lane < 3 - (aw >> 1)) mbar_arrive(BAR(B_RF + c));
        if (at == 0) TS(59 + c);
      }
      bar_sync(NB_AUX, 96);
      if (aw == 0) ONE(mbar_arrive_remote(mapa(BAR(B_XR), kh ^ 1)); TS(3));
      auto ytab = [](int a) { return (uint32_t)(fin_y(3 * a) >> 10 | fin_y(3 * a + 1) >> 10 << 8 | fin_y(3 * a + 2) >> 10 << 16 | fin_y(a == 2 ? 9 : 3 * a) >> 10 << 24); };
      const uint32_t yt = aw == 0 ? ytab(0) : (aw == 1 ? ytab(1) : ytab(2));
      mbar_wait(BAR(B_YSLOT + ((Y_MAP >> (4 * aw)) & 3)), 0);
#pragma unroll 1
      for (int n = 0;; n++) {
        ONE(mbar_expect(BAR(B_YL + aw), aw == 2 ? 8192 : 6144));
#pragma unroll 1
        for (int i = 0; i < (aw == 2 ? 4 : 3); i++) {
          const int np = 3 * aw + i;
          ONE(tma2d(sb + (((yt >> (8 * i)) & 255) << 10), &M.y, rb * 128 + kh * 64, nt * 160 + ((gmap >> (4 * (np >> 1))) & 7) * 32 + (np & 1) * 16, BAR(B_YL + aw)));
        }
        mbar_wait(BAR(B_YL + aw), n & 1);
        uint32_t bad = 0;
#pragma unroll
        for (int i = 0; i < 4; i++) {
          const uint32_t a = sb + (((yt >> (8 * i)) & 255) << 10) + (lane >> 2) * 128 + ((((lane & 3) * 2) ^ (lane >> 2)) << 4);
          bad |= (lds32(a) ^ ep) | (lds32(a + 1024) ^ ep);
        }
        if (__all_sync(0xffffffffu, (bad & 1u) == 0) || n > 100000) break;
        RETRY(5 + aw);
        if (lane == 0) TS(33);
      }
      if (lane <= (aw >> 1)) mbar_arrive(BAR(B_FINY));
      if (at == 64) TS(40);
    }
  } else {
    if (INC_KC < 0) asm volatile("setmaxnreg.inc.sync.aligned.u32 " REG_CON ";");
    const int wg = warp >> 2, w = warp & 3, g = lane >> 2, q = lane & 3;
    constexpr bool elect = false;
    uint32_t ca[64];
    const uint32_t ab0 = sb + ((g & 1) ? KT_E : KT_O) + (8 * w + 4 + (g >> 1) - q) * 4;
    auto conv_lda = [&](uint32_t ab, int k0, int k1) {
#pragma unroll
      for (int ks = 15; ks >= 0; ks--) {
        if (ks >= k0 && ks < k1) {
          ca[4 * ks + 0] = lds32(ab + ks * 256);
          ca[4 * ks + 1] = lds32(ab + ks * 256 + 128);
          ca[4 * ks + 2] = lds32(ab + ks * 256 - 16);
          ca[4 * ks + 3] = lds32(ab + ks * 256 + 112);
        }
      }
    };
    {
      float d[108];
      bool stag = false;
      auto g1_release = [&](int kc) { if (lane == 0) mbar_arrive(BAR(kc < 6 ? B_E1 + (kc & 3) : B_FR + kc - 6)); };
      auto g1_wait = [&](int kc) { mbar_wait(BAR(B_F1 + (kc & 3)), (kc >> 2) & 1); };
      auto g1_issue = [&](int kc) {
        const int s = kc & 3;
        if (kc == 0) { if (wg == 1) { mbar_wait(BAR(B_F1), 0); bar_sync(NB_LEAD, 256); } mbar_wait(BAR(B_F0), 0); }
        if (tid == 0) TS(8 + kc);
        const uint32_t st = sc + s * G1_STAGE;
        const uint64_t da = mkdesc(st + wg * 8192, 16, 1024, 1), db = mkdesc(st + 16384, 8192, 1024, 1);
        wg_fence();
#pragma unroll
        for (int k = 0; k < 4; k++) {
          wg_ss_216(d, da + k * 2, db + k * 128, (kc | k) != 0);
          if (k == REL_K || k == 3) wg_commit();
          if (k == REL_K && kc > 0) { wg_wait<1>(); if (kc != STAG_KC + 1 || !stag) g1_release(kc - 1); }
        }
        if (kc == 0 && wg == 0) bar_arrive(NB_LEAD, 256);
      };
      const int t7 = tid & 127, wr = ((t7 >> 3) & 1) * 4 + (t7 >> 4) * 8, wc = 4 * min(ci, 6) + ((t7 >> 1) & 3);
      const uint32_t sa0 = sb + (wg ? 16384 + (wc >> 3) * 8192 + wr * 128 + (((wc ^ wr) & 7) << 4) + (t7 & 1) * 8 : ri * 4096 + t7 * 16);
      float t1 = 0.f, t2 = 0.f, t3 = 0.f, t4 = 0.f;
      auto piece = [&](int i) {
        const uint32_t so = (i & 3) * G1_STAGE;
        if (wg == 0) {
          const uint4 x = lds128(sa0 + so), y = lds128(sa0 + so + 2048);
          const uint32_t xx[4] = {x.x, x.y, x.z, x.w}, yy[4] = {y.x, y.y, y.z, y.w};
#pragma unroll
          for (int e = 0; e < 4; e++) {
            const float u = bf_lo(xx[e]), v = bf_hi(xx[e]), r = bf_lo(yy[e]), z = bf_hi(yy[e]);
            t1 += u; t2 = fmaf(u, u, t2); t3 += r; t4 = fmaf(r, r, t4);
            t1 += v; t2 = fmaf(v, v, t2); t3 += z; t4 = fmaf(z, z, t4);
          }
        } else {
          float2 xx[4];
#pragma unroll
          for (int e = 0; e < 4; e++) xx[e] = lds64f((sa0 ^ (e * 144)) + so);
#pragma unroll
          for (int e = 0; e < 4; e++) {
            const uint32_t u = __float_as_uint(xx[e].x), v = __float_as_uint(xx[e].y);
            t1 += bf_lo(u); t2 += bf_hi(u); t3 += bf_lo(v); t4 += bf_hi(v);
          }
        }
      };
      const int mi = lane >> 3, row = w * 16 + (mi & 1) * 8 + (lane & 7);
      uint32_t ha[4], hx = sb + wg * HST + 24576 + row * 48 + (mi >> 1) * 16, hb = BAR(B_HB + wg * 4), aw0 = ab0 + cv_t(wg);
#pragma unroll
      for (int i = 0; i < 4; i++) ha[i] = sb + wg * HST + row * 128 + (((2 * i + (mi >> 1)) ^ (row & 7)) << 4);
      keep(ha[0]); keep(ha[1]); keep(ha[2]); keep(ha[3]); keep(hx); keep(hb); keep(aw0);
#pragma unroll
      for (int kc = 0; kc < 10; kc++) {
        g1_issue(kc);
        if (kc < 5 && (kc >= COM || kc == dir)) { g1_wait(kc); piece(kc); }
        if (kc == 5 - PEEK) {
          if (dir || COM == 2) { g1_wait(5); piece(5); }
          sts128(sb + (wg ? M_RED1 : M_RED0) + t7 * 16, __float_as_uint(t1), __float_as_uint(t2), __float_as_uint(t3), __float_as_uint(t4));
          __syncwarp();
          if (lane == 0) mbar_arrive(BAR(wg ? B_RED1 : B_RED));
        }
        if (kc == INC_KC) asm volatile("setmaxnreg.inc.sync.aligned.u32 " REG_CON ";");
        if (kc < 9) g1_wait(kc + 1);
        if (kc == STAG_KC && wg == 1 && (STAG_ALL || mbar_test(BAR(B_BX), 0))) {
          if (STAG_REL) { wg_wait<0>(); g1_release(kc); stag = true; }
          mbar_wait(BAR(B_LNI), 0);
        }
      }
      uint2 s0, s1;
      {
        mbar_wait(BAR(B_BX), 0);
        s0.x = lds32(sb + M_STAT + (wg * 64 + w * 16 + g) * 4); s1.x = lds32(sb + M_STAT + (wg * 64 + w * 16 + g + 8) * 4);
        if (tid == 0) TS(46);
        const uint32_t f0 = q == 0 ? ((s0.x & 0xFFFFu) * 0x10001u) ^ 0x80008000u : (q == 1 ? s0.x ^ 0x8000u : 0u);
        const uint32_t f1 = q == 0 ? ((s1.x & 0xFFFFu) * 0x10001u) ^ 0x80008000u : (q == 1 ? s1.x ^ 0x8000u : 0u);
        wg_fence();
        wg_rs_216(d, f0, f1, 0u, 0u, mkdesc(sc + M_BX, 512, 0, 2));
        wg_commit();
        if (wg == 0 && lane == 0) mbar_arrive(BAR(B_LNI));
      }
      wg_wait<1>();
      if (lane == 0) mbar_arrive(BAR(B_FR + 3));
      const float r0 = rcp_fast(bf_hi(s0.x)), r1 = rcp_fast(bf_hi(s1.x));
      constexpr float C1 = 0.7978845608028654f, C2 = 0.7978845608028654f * 0.044715f;
      const float ga0 = C1 * r0, gb0 = C2 * r0 * r0 * r0, ga1 = C1 * r1, gb1 = C2 * r1 * r1 * r1;
      if (wg == 0) mbar_wait(BAR(B_FR + 2), 0);
      wg_wait<0>();
      if (elect) TS(1 + 47 * wg);
      if (wg == 1) bar_sync(NB_GELU, 256);
      sched_fence(sb);
      float u[2][8];
#pragma unroll
      for (int st = -1; st < 15; st++) {
        const int nb = 2 * (st - 1);
        if (st >= 1) {
          uint32_t p[4];
#pragma unroll
          for (int e = 0; e < (nb < 26 ? 4 : 2); e++) {
            const float x = d[4 * nb + 2 * e], y = d[4 * nb + 2 * e + 1];
            p[e] = pack_bf16(fmaf(x, u[(st - 1) & 1][2 * e], x), fmaf(y, u[(st - 1) & 1][2 * e + 1], y));
          }
          if (nb < 24) stsm4(ha[(nb >> 1) & 3] + (nb >> 3) * 8192, p[0], p[1], p[2], p[3]);
          else if (nb == 24) stsm4(hx, p[0], p[1], p[2], p[3]);
          else stsm2(hx + 32, p[0], p[1]);
          if ((nb & 7) == 6 || nb == 26) {
            __syncwarp();
            if (lane == 0) mbar_arrive(hb + 8 * (nb >> 3));
          }
        }
        if (st >= 0 && st < 14) {
#pragma unroll
          for (int i = 0; i < (st < 13 ? 8 : 4); i++) u[st & 1][i] = tanh_fast(u[st & 1][i]);
        }
        if (st + 1 < 14) {
#pragma unroll
          for (int i = 0; i < (st + 1 < 13 ? 8 : 4); i++) {
            const float x = d[8 * (st + 1) + i];
            u[(st + 1) & 1][i] = x * fmaf(x * ((i & 2) ? gb1 : gb0), x, (i & 2) ? ga1 : ga0);
          }
        }
        constexpr int S0 = A_NB0 / 2, NK = CV_OWN ? 16 - CV_RELOADED : 16;
        if (st >= S0 && st < 14) conv_lda(aw0, 16 - (st + 1 - S0) * NK / (14 - S0), 16 - (st - S0) * NK / (14 - S0));
        if (2 * st == GELU_NB && wg == 0) bar_arrive(NB_GELU, 256);
        if (st + 1 == S0) mbar_wait(BAR(B_KT + wg), 0); else if (st < 14 && (st + 1) % SCH == 0) sched_fence(sb);
      }
      if (elect) TS(2 + 47 * wg);
    }
#pragma unroll 1
    for (int c = wg; c < 5; c += 2) {
      float d[128];
      mbar_wait(BAR(B_XF + c), 0);
      if (c < 3) mbar_wait(BAR(B_KT + c + 2), 0);
      const uint64_t db = mkdesc(sc + cv_x(c), 16, 128, 0);
      if (c > 0) { if (wg) bar_sync(NB_TURN + 1, 256); else bar_sync(NB_TURN, 256); }
      wg_fence();
      auto hand = [&]() { if (wg) bar_arrive(NB_TURN, 256); else if (c < 4 || !HAND4) bar_arrive(NB_TURN + 1, 256); };
      const uint32_t ao = ab0 + cv_t(c);
      if (c < 3) conv_chain_1(d, ca, db, ao, ao + 2 * KT_CH, hand, []() {});
      else conv_chain_0(d, ca, db, ao, 0, hand, [&]() { if (lane == 0) mbar_arrive(BAR(B_TD + 1)); });
      if (c == 4 && HAND4) bar_arrive(NB_TURN + 1, 256);
      mbar_wait(BAR(c >= 3 ? B_RF + c - 3 : B_FR + 3), 0);
      wg_wait<0>();
      if (elect) TS(41 + c);
      if (c < 3 && !CV_OWN) conv_lda(ao + 2 * KT_CH, 0, CV_RELOADED);
      const uint32_t wa = sb + cv_p(c) + w * 4096 + lane * 16;
#pragma unroll
      for (int n4 = 0; n4 < 32; n4 += 4) {
        uint32_t p[4];
#pragma unroll
        for (int e = 0; e < 4; e++) {
          const int nb = n4 + e;
          float x = d[4 * nb], y = d[4 * nb + 1];
          if (nb > 0) { x += d[4 * nb - 2]; y += d[4 * nb - 1]; }
          p[e] = pack_bf16(x, y);
        }
        stsm4t(wa + n4 * 128, p[0], p[1], p[2], p[3]);
      }
      __syncwarp();
      if (lane == 0) mbar_arrive(BAR(B_SD + c));
    }
    if (elect) TS(51 + wg);
    {
      float d[80];
      const uint32_t aoff = (wg ^ kh) * 8192;
      const uint64_t boff = (uint64_t)(nt & 1) << 51;
      const uint32_t s0 = lds32(sb + M_STAT + ((wg ^ kh) * 64 + w * 16 + g) * 4), s1 = lds32(sb + M_STAT + ((wg ^ kh) * 64 + w * 16 + g + 8) * 4);
      auto g2_release = [&](int kc) { if (lane == 0) mbar_arrive(BAR(B_E2 + (kc & 3))); };
      auto g2_mma_w = [&](int kc, int first, bool rel, auto side) {
        const int s = kc & 3;
        mbar_wait(BAR(B_F2 + s), (kc >> 2) & 1);
        const uint64_t da = mkdesc(sc + g2_a(s) + aoff, 16, 1024, 1), db = mkdesc(sc + g2_b(s), 8192, 1024, 1) | boff;
        wg_fence();
#pragma unroll
        for (int k = 0; k < 4; k++) {
          wg_ss_160(d, da + k * 2, db + k * 128, k ? 1 : first);
          if ((k == REL_K && rel) || k == 3) wg_commit();
          if (k == REL_K && rel) { wg_wait<1>(); g2_release(kc - 1); }
          side(k);
        }
      };
      auto g2_mma = [&](int kc, int first, bool rel) { g2_mma_w(kc, first, rel, [](int) {}); };
      sched_fence(sb);
      if (wg == 1) bar_sync(NB_TURN + 1, 256);
      g2_mma(0, 0, false);
      if (wg == 0) bar_arrive(NB_LEAD, 256);
#pragma unroll
      for (int kc = 1; kc < XP_KC; kc++) {
        if (tid == 0) TS(17 + kc);
        if (kc == LEAD_KC && wg == 1) bar_sync(NB_LEAD, 256);
        g2_mma(kc, 1, true);
      }
      if (wg == 1) {
        float bi[40];
#pragma unroll
        for (int nb = 0; nb < 20; nb++) { const float2 v = lds64f(sb + M_B2 + nb * 32 + q * 8); bi[2 * nb] = v.x; bi[2 * nb + 1] = v.y; }
        const float c0 = 0.25f * rcp_fast(bf_hi(s0)), c1 = 0.25f * rcp_fast(bf_hi(s1));
#pragma unroll
        for (int kc = XP_KC; kc < NSH; kc++) {
          g2_mma(kc, 1, kc < NST - 3);
          if (kc == END_KC) bar_arrive(NB_END, 256);
        }
        mbar_wait(BAR(B_XR), 0);
        wg_wait<0>();
#pragma unroll
        for (int kc = NSH - 1; kc < NST - 4; kc++) g2_release(kc);
        if (elect) TS(53);
        const uint32_t ra = mapa(sb, kh ^ 1), rbar = ra + M_BAR + 8 * B_XD, dst = ra + (tid & 127) * 16;
#pragma unroll
        for (int i = 0; i < 10; i++) {
          const float *dd = d + 8 * i, *bb = bi + 4 * i;
          st_async128(dst + (i < 5 ? P0 + i * 2048 : P1 + (i - 5) * 2048), pack_bf16(fmaf(dd[0], c0, bb[0]), fmaf(dd[1], c0, bb[1])), pack_bf16(fmaf(dd[2], c1, bb[0]), fmaf(dd[3], c1, bb[1])),
                      pack_bf16(fmaf(dd[4], c0, bb[2]), fmaf(dd[5], c0, bb[3])), pack_bf16(fmaf(dd[6], c1, bb[2]), fmaf(dd[7], c1, bb[3])), rbar + 8 * ((i >= XD_N) + (i >= XD_M)));
          sched_fence(sb);
        }
        if (elect) TS(7);
      } else {
        const int mi = lane >> 3, row = (mi & 1) * 8 + (lane & 7);
        const uint32_t qa = sb + FIN_Q + (w * 16 + row) * 64 + (((mi >> 1) ^ ((row >> 1) & 3)) << 4), qb = qa ^ 32;
        auto q_addr = [&](int np) { return ((np & 1) ? qb : qa) + (np >> 1) * 4096; };
        uint32_t sv[40], xq[40];
        const uint32_t m0 = (s0 & 0xFFFFu) * 0x10001u, m1 = (s1 & 0xFFFFu) * 0x10001u;
        float rs0 = rcp_fast(bf_hi(s0)), rs1 = rcp_fast(bf_hi(s1));
#pragma unroll
        for (int kc = XP_KC; kc < 10; kc++) {
          if (tid == 0) TS(17 + kc);
          g2_mma(kc, 1, true);
          if (kc >= XP_KC && XP_KC < 10) {
            mbar_wait(BAR(B_FINQ), 0);
#pragma unroll
            for (int np = 10 * (kc - XP_KC) / (XP_KC < 10 ? 10 - XP_KC : 1); np < 10 * (kc + 1 - XP_KC) / (XP_KC < 10 ? 10 - XP_KC : 1); np++) {
              ldsm4(q_addr(np), xq[4 * np], xq[4 * np + 1], xq[4 * np + 2], xq[4 * np + 3]);
#pragma unroll
              for (int e = 0; e < 4; e++) {
                const uint32_t dm = bsub2(xq[4 * np + e], (e & 1) ? m1 : m0);
                const float rs = (e & 1) ? rs1 : rs0;
                sv[4 * np + e] = pack_bf16(bf_lo(dm) * rs, bf_hi(dm) * rs);
              }
            }
          }
        }
        const uint32_t ya = sb + (mi >> 1) * 1024 + (lane & 7) * 128 + (((2 * w + (mi & 1)) ^ (lane & 7)) << 4);
        uint32_t y[3][4];
        auto y_step = [&](int i) {
          if (i < 0 || i >= 12) return;
          if (i >= 2) {
#pragma unroll
            for (int e = 0; e < 4; e++) asm volatile("mul.rn.bf16x2 %0, %0, %1;" : "+r"(sv[4 * (i - 2) + e]) : "r"(y[(i - 2) % 3][e]));
          }
          if (i < 10) ldsm4t(ya + fin_y(i), y[i % 3][0], y[i % 3][1], y[i % 3][2], y[i % 3][3]);
          if (YFENCE) sched_fence(sb);
        };
        rs0 *= 0.25f; rs1 *= 0.25f;
        if (tid == 0) TS(27);
#pragma unroll
        for (int kc = 9; kc < NST; kc++) {
          if (kc == YP_KC) mbar_wait(BAR(B_FINY), 0);
          if (kc > 9) g2_mma_w(kc, 1, kc < NST - 3 && kc != HOLD_KC + 1, [&](int k) { y_step(4 * (kc - YP_KC) + k); });
          if (kc == HOLD_KC) {
            if (kc < NST - 4) { wg_wait<0>(); g2_release(kc); }
            if (tid == 0) TS(28);
            bar_sync(NB_END, 256);
          }
        }
        if (tid == 0) TS(29);
#pragma unroll
        for (int i = 4 * (NST - YP_KC); i < 12; i++) y_step(i);
        if (tid == 0) TS(47);
        mbar_wait(BAR(B_XD), 0);
        if (tid == 0) TS(5);
        uint4 v[10];
        auto ld_v = [&](int n0, int n1) {
#pragma unroll
          for (int i = n0; i < n1; i++) v[i] = lds128(sb + tid * 16 + (i < 5 ? P0 + i * 2048 : P1 + (i - 5) * 2048));
        };
        ld_v(0, XD_N);
        wg_wait<0>();
        if (tid == 0) TS(4);
        float t[2][8];
#pragma unroll
        for (int st = -1; st < 11; st++) {
          if (st == XD_N - 3) { mbar_wait(BAR(B_XD + 1), 0); ld_v(XD_N, XD_M); }
          if (st == XD_M - 3) { mbar_wait(BAR(B_XD + 2), 0); ld_v(XD_M, 10); }
          if (st >= 1) {
            const int np = st - 1;
            uint32_t o[4];
#pragma unroll
            for (int e = 0; e < 4; e++) {
              const float h0 = d[8 * np + 2 * e], h1 = d[8 * np + 2 * e + 1];
              o[e] = bfma2(sv[4 * np + e], pack_bf16(fmaf(h0, t[np & 1][2 * e], h0), fmaf(h1, t[np & 1][2 * e + 1], h1)), xq[4 * np + e]);
            }
            stsm4(q_addr(np), o[0], o[1], o[2], o[3]);
            if (np & 1) {
              if (np == 9 && tid == 0) TS(50);
              __syncwarp();
              if (lane == 0) mbar_arrive(BAR(B_OUT + (np >> 1)));
            }
          }
          if (st >= 0 && st < 10) {
#pragma unroll
            for (int i = 0; i < 8; i++) t[st & 1][i] = tanh_fast(d[8 * st + i]);
          }
          if (st + 1 < 10) {
            const int np = st + 1;
            const uint32_t pw[4] = {v[np].x, v[np].y, v[np].z, v[np].w};
#pragma unroll
            for (int e = 0; e < 4; e++) {
              d[8 * np + 2 * e] = fmaf(d[8 * np + 2 * e], (e & 1) ? rs1 : rs0, bf_lo(pw[e]));
              d[8 * np + 2 * e + 1] = fmaf(d[8 * np + 2 * e + 1], (e & 1) ? rs1 : rs0, bf_hi(pw[e]));
            }
          }
          if (SCH2 && (st + 1) % (SCH2 ? SCH2 : 1) == 0) sched_fence(sb);
        }
      }
    }
  }
}

typedef CUresult (*EncFn)(CUtensorMap*, CUtensorMapDataType, cuuint32_t, void*, const cuuint64_t*, const cuuint64_t*, const cuuint32_t*, const cuuint32_t*,
                          CUtensorMapInterleave, CUtensorMapSwizzle, CUtensorMapL2promotion, CUtensorMapFloatOOBfill);

static void make_map(EncFn enc, CUtensorMap* tm, const void* ptr, int cols, int rows, int bc, int br, int grp, CUtensorMapSwizzle sw,
                     CUtensorMapL2promotion promo = CU_TENSOR_MAP_L2_PROMOTION_NONE) {
  cuuint64_t gd[3] = {(cuuint64_t)(grp ? bc : cols), (cuuint64_t)rows, (cuuint64_t)(cols / bc)};
  cuuint64_t gs[2] = {(cuuint64_t)cols * 2, (cuuint64_t)bc * 2};
  cuuint32_t bd[3] = {(cuuint32_t)bc, (cuuint32_t)br, (cuuint32_t)grp};
  cuuint32_t es[3] = {1, 1, 1};
  CUresult r = enc(tm, CU_TENSOR_MAP_DATA_TYPE_BFLOAT16, grp ? 3 : 2, const_cast<void*>(ptr), gd, gs, bd, es, CU_TENSOR_MAP_INTERLEAVE_NONE, sw,
                   promo, CU_TENSOR_MAP_FLOAT_OOB_FILL_NONE);
  (void)r;
}

}

extern "C" void kernel_launch(void* const* d_in, const int* in_sizes, int n_in, void* d_out, int out_size) {
  using namespace h3;
  (void)in_sizes; (void)n_in; (void)out_size;
  static EncFn enc = nullptr;
  static void *p_h = nullptr, *p_yT = nullptr, *p_kvT = nullptr;
  if (!enc) {
    void* fn = nullptr; cudaDriverEntryPointQueryResult qr;
    cudaGetDriverEntryPoint("cuTensorMapEncodeTiled", &fn, cudaEnableDefault, &qr);
    enc = (EncFn)fn;
    cudaGetSymbolAddress(&p_h, g_h);
    cudaGetSymbolAddress(&p_yT, g_yT);
    cudaGetSymbolAddress(&p_kvT, g_kvT);
    cudaFuncSetAttribute(h3_kernel, cudaFuncAttributeMaxDynamicSharedMemorySize, SMEM_BYTES);
  }
  Params P;
  P.q = (const __nv_bfloat16*)d_in[0]; P.k = (const __nv_bfloat16*)d_in[1]; P.v = (const __nv_bfloat16*)d_in[2];
  P.shift_k = (const __nv_bfloat16*)d_in[3]; P.ssm_k = (const __nv_bfloat16*)d_in[4]; P.ssm_D = (const __nv_bfloat16*)d_in[5];
  P.out = (__nv_bfloat16*)d_out;
  P.w1 = (const __nv_bfloat16*)d_in[7]; P.b1 = (const __nv_bfloat16*)d_in[8]; P.w2 = (const __nv_bfloat16*)d_in[9]; P.b2 = (const __nv_bfloat16*)d_in[10];
  const CUtensorMapSwizzle S128 = CU_TENSOR_MAP_SWIZZLE_128B, S64 = CU_TENSOR_MAP_SWIZZLE_64B, S0 = CU_TENSOR_MAP_SWIZZLE_NONE;
  Maps M;
  make_map(enc, &M.q0, P.q, DM, SL, 64, 64, 0, S128);
  make_map(enc, &M.w1, P.w1, FF, DM, 64, 64, 3, S128);
  make_map(enc, &M.w1x, P.w1, FF, DM, 24, 64, 0, S128, WS_PROMO);
  make_map(enc, &M.k, P.k, DM, SL, 64, 19, 0, S0);
  make_map(enc, &M.v, P.v, DM, SL, 64, 16, 0, S0);
  make_map(enc, &M.hs, p_h, FF, SL, 64, 64, 0, S128);
  make_map(enc, &M.hx, p_h, FF, SL, 24, 64, 0, S0);
  make_map(enc, &M.ha, p_h, FF, SL, 64, 128, 0, S128);
  make_map(enc, &M.w2, P.w2, DM, FF, 64, 64, 2, S128);
  make_map(enc, &M.w2x, P.w2, DM, FF, 64, 64, 0, S128);
  make_map(enc, &M.kvs, p_kvT, SL, DM, 16, 64, 0, CU_TENSOR_MAP_SWIZZLE_32B);
  make_map(enc, &M.qf, P.q, DM, SL, 32, 64, 0, S64);
  make_map(enc, &M.y, p_yT, SL, DM, 64, 16, 0, S128);
  make_map(enc, &M.out, d_out, DM, SL, 32, 64, 0, S64);
  h3_kernel<<<NCTA, 384, SMEM_BYTES>>>(M, P);
}
```

```cpp
#include <cuda_runtime.h>
#include <cuda_bf16.h>
#include <cuda.h>
#include <stdint.h>

namespace h3 {

constexpr int SL = 2048, DM = 640, FF = 1728;
constexpr int NCTA = 128;

__device__ __align__(1024) __nv_bfloat16 g_h[SL * FF];
__device__ __align__(1024) __nv_bfloat16 g_kvT[DM * SL];
__device__ __align__(1024) __nv_bfloat16 g_yT[DM * SL];
__device__ __align__(1024) uint2 g_stat[2 * SL];
__device__ __align__(1024) uint32_t g_cs[2 * 8 * 256];
__device__ __align__(1024) unsigned g_cnt[16 * 32];
__device__ __align__(1024) unsigned g_launch[NCTA * 8];
#define RETRY(i)

constexpr int G1_STAGE = 49152, G1_TX = 16384 + 24576 + 3072;
constexpr int HST = 49152;
constexpr int P0 = 81920, P1 = 140288, P2 = 156672;
constexpr int XCH = 4368, XD = 272, X0 = 173056, X4 = 221184;
constexpr int KVS = 196608, KV_BUF = 8960;
constexpr int KT_CH = 8240, KT_O = 16, KT_E = 4144, KT0 = 98304;
constexpr int FIN_Q = X0;
constexpr int MISC = 226816;
constexpr int M_BX = MISC;
constexpr int M_RED0 = M_BX + 2048, M_RED1 = M_BX;
constexpr int M_SK = KVS + 3 * KV_BUF;
constexpr int M_STAT = M_BX + 3584;
constexpr int M_B2 = MISC - 640;
constexpr int M_AUX = M_STAT + 512;
constexpr int M_ZERO = M_AUX + 96;
constexpr int M_BAR = M_ZERO + 16;
constexpr int M_TS = M_BAR + 94 * 8;
constexpr int SMEM_BYTES = M_TS + 272;
__host__ __device__ constexpr int fin_y(int np) {
  return np < 3 ? P0 + 10240 + np * 2048 : (np < 6 ? P1 + 10240 + (np - 3) * 2048 : (np == 6 ? FIN_Q + 20480 : (np < 9 ? X4 + (np - 7) * 2048 : M_BX + 512)));
}
static_assert(fin_y(9) % 1024 == 0 && fin_y(6) % 1024 == 0 && fin_y(6) + 2048 <= KVS && fin_y(7) % 1024 == 0, "smem");
__host__ __device__ constexpr int cv_x(int c) { return c == 4 ? X4 : X0 + c * XCH; }
__host__ __device__ constexpr int cv_p(int c) { return c == 2 ? P2 : ((c == 0 || c == 3) ? P0 : P1); }
__host__ __device__ constexpr int cv_t(int c) { return KT0 + c * KT_CH; }
__host__ __device__ constexpr int g2_a(int s) { return s == 0 ? 0 : (s == 1 ? 40960 : (s == 2 ? 98304 : P2)); }
__host__ __device__ constexpr int g2_b(int s) { return s == 0 ? 16384 : (s == 1 ? 57344 : (s == 2 ? 114688 : KVS)); }
static_assert(M_SK + 2560 <= M_B2 && X4 + XCH <= M_B2 && KVS + 24576 <= X4 && X0 + 4 * XCH <= KVS && FIN_Q + 20480 <= KVS, "smem");
static_assert(KT0 + 5 * KT_CH <= P1 && P1 + 16384 <= P2 && P2 + 16384 <= X0 && SMEM_BYTES <= 232448 && MISC % 512 == 0 && M_BAR % 8 == 0, "smem");
constexpr int B_E1 = 0, B_FR = 4, B_E2 = 8, B_TD = 11  , B_RF = 13;
constexpr int B_HB = 16, B_SD = 24, B_OUT = 29, B_LNI = 34, B_RED = 35, B_RED1 = 36, B_FINY = 37, B_BX = 38, B_KD = 39;
constexpr int B_F2 = 40, B_KRAW = 44, B_RD = 46, B_SK = 47, B_XL = 48, B_KT = 53, B_XF = 58, B_KIN = 63, B_KIN1 = 68, B_YSLOT = 73,
              B_YL = 76, B_XR = 79, B_XD = 80, B_FINQ = 83, B_F1 = 88, B_F0 = 92;
constexpr int NB_INIT = 1, NB_INIT2 = 2, NB_AUX = 3, NB_LEAD = 4, NB_GELU = 5, NB_TURN = 6  , NB_END = 8, NB_INIT3 = 9, NB_WG1 = 10;

#define PRO 1
#define G1U 6
#define P1U 1
constexpr int G1_UNROLL = G1U, P1_UNROLL = P1U;
#define KV_MAP 0x764
#define WS_PROMO CU_TENSOR_MAP_L2_PROMOTION_L2_128B
#define RAW_LATE 0
#define PF_RAW 7
#define REL_K 0
#define CS_WAIT 1
#define GELU_NB 8
#define H_ORD 0x73625410
#define W2_PF 7
#define H_FLY 8
#define TB_MAP 0x01040532u
#define KRAW_N 2
#define XT1 (B_FR + 3)
#define XT2 (B_HB + 1)
#define XT3 (B_HB + 3)
#define XT4 (B_HB + 7)
#define X_TRIG ((XT1) | (XT2) << 8 | (XT3) << 16 | (XT4) << 24)
#define FENCE_KIND 1
#define SCH2 0
#define SCH 2
#define A_NB0 14
#define HAND4 1
#define LEAD_KC 1
#define RED_GATE 3
#define XP_KC 4
#define NSH 12
#define NST (27 - NSH)
#define YP_KC 12
#define YFENCE 1
#define Y_MAP 0x210
#define Y_KC 9
#define XD_N 6
#define XD_M 8
#define HOLD_KC 11
#define END_KC (NSH - 1)
#define REG_AUX "56"
#define REG_CON "224"
#define LDQ ".nc.L1::no_allocate"
#define LDP ""

__device__ __forceinline__ uint32_t s32(const void* p) { return (uint32_t)__cvta_generic_to_shared(p); }
__device__ __forceinline__ uint32_t clk() { uint32_t t; asm volatile("mov.u32 %0, %%clock;" : "=r"(t)); return t; }
__device__ __forceinline__ bool elect_one() {
  uint32_t p; asm volatile("{\n.reg .pred P;\nelect.sync _|P, 0xffffffff;\nselp.u32 %0, 1, 0, P;\n}" : "=r"(p)); return p;
}
#define ONE(...) do { if (elect_one()) { __VA_ARGS__; } __syncwarp(); } while (0)
__device__ __forceinline__ void mbar_init(uint32_t a, int c) { asm volatile("mbarrier.init.shared::cta.b64 [%0], %1;" ::"r"(a), "r"(c) : "memory"); }
__device__ __forceinline__ void mbar_expect(uint32_t a, int b) { asm volatile("mbarrier.arrive.expect_tx.shared::cta.b64 _, [%0], %1;" ::"r"(a), "r"(b) : "memory"); }
__device__ __forceinline__ void mbar_arrive(uint32_t a) { asm volatile("mbarrier.arrive.shared::cta.b64 _, [%0];" ::"r"(a) : "memory"); }
__device__ __forceinline__ bool spin_guard(uint32_t& n, uint32_t) {
  return ++n > (1u << 20);
}
__device__ __forceinline__ void mbar_wait(uint32_t a, int ph) {
  asm volatile("{\n.reg .pred p;\n.reg .u32 n;\nmov.u32 n, 0;\nW:\n.pragma \"nounroll\";\nmbarrier.try_wait.parity.shared::cta.b64 p, [%0], %1;\n"
               "add.u32 n, n, 1;\nsetp.ge.or.u32 p, n, 0x100000, p;\n@!p bra W;\n}" ::"r"(a), "r"(ph) : "memory");
}
__device__ __forceinline__ bool mbar_test(uint32_t a, int ph) {
  uint32_t ok;
  asm volatile("{\n.reg .pred p;\nmbarrier.test_wait.parity.shared::cta.b64 p, [%1], %2;\nselp.u32 %0, 1, 0, p;\n}" : "=r"(ok) : "r"(a), "r"(ph) : "memory");
  return __all_sync(0xffffffffu, ok);
}
__device__ __forceinline__ void sched_fence(uint32_t a) {
  asm volatile("{\n.reg .pred p;\nsetp.eq.u32 p, %0, 0;\n@p exit;\n}" ::"r"(a) : "memory");
}
__device__ __forceinline__ void keep(uint32_t& v) { v = __shfl_sync(0xffffffffu, v, threadIdx.x & 31); }
__device__ __forceinline__ void tma2d(uint32_t dst, const CUtensorMap* tm, int c0, int c1, uint32_t bar) {
  asm volatile("cp.async.bulk.tensor.2d.shared::cluster.global.mbarrier::complete_tx::bytes [%0], [%1, {%3, %4}], [%2];"
               ::"r"(dst), "l"(tm), "r"(bar), "r"(c0), "r"(c1) : "memory");
}
__device__ __forceinline__ void tma3d(uint32_t dst, const CUtensorMap* tm, int c0, int c1, int c2, uint32_t bar) {
  asm volatile("cp.async.bulk.tensor.3d.shared::cluster.global.mbarrier::complete_tx::bytes [%0], [%1, {%3, %4, %5}], [%2];"
               ::"r"(dst), "l"(tm), "r"(bar), "r"(c0), "r"(c1), "r"(c2) : "memory");
}
__device__ __forceinline__ void tma2d_st(const CUtensorMap* tm, int c0, int c1, uint32_t src) {
  asm volatile("cp.async.bulk.tensor.2d.global.shared::cta.bulk_group [%0, {%2, %3}], [%1];" ::"l"(tm), "r"(src), "r"(c0), "r"(c1) : "memory");
}
__device__ __forceinline__ void tma3d_st(const CUtensorMap* tm, int c0, int c1, int c2, uint32_t src) {
  asm volatile("cp.async.bulk.tensor.3d.global.shared::cta.bulk_group [%0, {%2, %3, %4}], [%1];" ::"l"(tm), "r"(src), "r"(c0), "r"(c1), "r"(c2) : "memory");
}
__device__ __forceinline__ void bulk_g2s(uint32_t dst, const void* src, int bytes, uint32_t bar) {
  asm volatile("cp.async.bulk.shared::cluster.global.mbarrier::complete_tx::bytes [%0], [%1], %2, [%3];" ::"r"(dst), "l"(src), "r"(bytes), "r"(bar) : "memory");
}
__device__ __forceinline__ void bulk_commit() { asm volatile("cp.async.bulk.commit_group;" ::: "memory"); }
__device__ __forceinline__ void bulk_wait_read() { asm volatile("cp.async.bulk.wait_group.read 0;" ::: "memory"); }
__device__ __forceinline__ void bulk_wait_all() { asm volatile("cp.async.bulk.wait_group 0;" ::: "memory"); }
__device__ __forceinline__ void fence_async_smem() { asm volatile("fence.proxy.async.shared::cta;" ::: "memory"); }
__device__ __forceinline__ void fence_async_all() { asm volatile("fence.proxy.async;" ::: "memory"); }
__device__ __forceinline__ void fence_gpu() { asm volatile("fence.acq_rel.gpu;" ::: "memory"); }
#define bar_sync(id, n) asm volatile("bar.sync %0, %1;" ::"n"(id), "n"(n) : "memory")
#define bar_arrive(id, n) asm volatile("bar.arrive %0, %1;" ::"n"(id), "n"(n) : "memory")
__device__ __forceinline__ void wg_fence() { asm volatile("wgmma.fence.sync.aligned;" ::: "memory"); }
__device__ __forceinline__ void wg_commit() { asm volatile("wgmma.commit_group.sync.aligned;" ::: "memory"); }
template <int N> __device__ __forceinline__ void wg_wait() { asm volatile("wgmma.wait_group.sync.aligned %0;" ::"n"(N) : "memory"); }
__device__ __forceinline__ uint64_t mkdesc(uint32_t addr, uint32_t lbo, uint32_t sbo, int sw) {
  return (uint64_t)((addr & 0x3FFFF) >> 4) | ((uint64_t)(lbo >> 4) << 16) | ((uint64_t)(sbo >> 4) << 32) | ((uint64_t)sw << 62);
}
__device__ __forceinline__ uint32_t ldg32(const void* p) { uint32_t v; asm volatile("ld.global" LDQ ".b32 %0, [%1];" : "=r"(v) : "l"(p)); return v; }
template <int OFF> __device__ __forceinline__ uint32_t ldg32o(const void* p) { uint32_t v; asm volatile("ld.global" LDQ ".b32 %0, [%1+%2];" : "=r"(v) : "l"(p), "n"(OFF)); return v; }
template <int I> __device__ __forceinline__ void kv_loads(const void* kp, const void* vp, uint32_t (&kk)[16], uint32_t (&o)[16]) {
  kk[I] = ldg32o<I * DM * 2>(kp); o[I] = ldg32o<I * DM * 2>(vp);
  if constexpr (I < 15) kv_loads<I + 1>(kp, vp, kk, o);
}
__device__ __forceinline__ uint4 ldg128(const void* p) {
  uint4 v; asm volatile("ld.global" LDQ LDP ".v4.b32 {%0,%1,%2,%3}, [%4];" : "=r"(v.x), "=r"(v.y), "=r"(v.z), "=r"(v.w) : "l"(p)); return v;
}
__device__ __forceinline__ void stg128(void* p, uint32_t x, uint32_t y, uint32_t z, uint32_t w) {
  asm volatile("st.global.v4.b32 [%0], {%1,%2,%3,%4};" ::"l"(p), "r"(x), "r"(y), "r"(z), "r"(w) : "memory");
}
__device__ __forceinline__ uint4 ld_relaxed128(const void* p) {
  uint4 v; asm volatile("ld.relaxed.gpu.global.v4.b32 {%0,%1,%2,%3}, [%4];" : "=r"(v.x), "=r"(v.y), "=r"(v.z), "=r"(v.w) : "l"(p) : "memory"); return v;
}
__device__ __forceinline__ uint2 ld_relaxed64(const void* p) {
  uint2 v; asm volatile("ld.relaxed.gpu.global.v2.b32 {%0,%1}, [%2];" : "=r"(v.x), "=r"(v.y) : "l"(p) : "memory"); return v;
}
__device__ __forceinline__ uint4 ld_relaxed_b128(const void* p) {
  uint4 v; asm volatile("{\n.reg .b128 t;\nld.relaxed.gpu.global.b128 t, [%4];\nmov.b128 {%0,%1,%2,%3}, t;\n}" : "=r"(v.x), "=r"(v.y), "=r"(v.z), "=r"(v.w) : "l"(p) : "memory"); return v;
}
__device__ __forceinline__ void st_relaxed_b128(void* p, uint32_t x, uint32_t y, uint32_t z, uint32_t w) {
  asm volatile("{\n.reg .b128 t;\nmov.b128 t, {%1,%2,%3,%4};\nst.relaxed.gpu.global.b128 [%0], t;\n}" ::"l"(p), "r"(x), "r"(y), "r"(z), "r"(w) : "memory");
}
__device__ __forceinline__ void st_relaxed64(void* p, uint32_t x, uint32_t y) {
  asm volatile("{\n.reg .b64 t;\nmov.b64 t, {%1,%2};\nst.relaxed.gpu.global.b64 [%0], t;\n}" ::"l"(p), "r"(x), "r"(y) : "memory");
}
__device__ __forceinline__ void st_relaxed32(void* p, uint32_t x) { asm volatile("st.relaxed.gpu.global.b32 [%0], %1;" ::"l"(p), "r"(x) : "memory"); }
__device__ __forceinline__ uint32_t ld_relaxed32(const void* p) { uint32_t v; asm volatile("ld.relaxed.gpu.global.b32 %0, [%1];" : "=r"(v) : "l"(p) : "memory"); return v; }
__device__ __forceinline__ void st_relaxed128(void* p, uint32_t x, uint32_t y, uint32_t z, uint32_t w) {
  asm volatile("{\n.reg .b64 t, u;\nmov.b64 t, {%1,%2};\nmov.b64 u, {%3,%4};\nst.relaxed.gpu.global.v2.b64 [%0], {t, u};\n}" ::"l"(p), "r"(x), "r"(y), "r"(z), "r"(w) : "memory");
}
__device__ __forceinline__ void fence_release() { asm volatile("fence.proxy.async.global;\nfence.release.gpu;" ::: "memory"); }
__device__ __forceinline__ void fence_acquire() { asm volatile("fence.acquire.gpu;\nfence.proxy.async.global;" ::: "memory"); }
__device__ __forceinline__ void signal_cnt(uint32_t* p) { asm volatile("red.relaxed.gpu.global.add.u32 [%0], 1;" ::"l"(p) : "memory"); }
__device__ __forceinline__ void wait_cnt(const uint32_t* p, unsigned target) {
  uint32_t n = 0;
#pragma unroll 1
  while (!__all_sync(0xffffffffu, (int)(ld_relaxed32(p) - target) >= 0)) {
    if (spin_guard(n, 0x100)) break;
  }
  fence_acquire();
}
__device__ __forceinline__ void bulk_s2g(void* dst, uint32_t src, int bytes) {
  asm volatile("cp.async.bulk.global.shared::cta.bulk_group [%0], [%1], %2;" ::"l"(dst), "r"(src), "r"(bytes) : "memory");
}
__device__ __forceinline__ void bulk_add_s2g(void* dst, uint32_t src, int bytes) {
  asm volatile("cp.reduce.async.bulk.global.shared::cta.bulk_group.add.noftz.bf16 [%0], [%1], %2;" ::"l"(dst), "r"(src), "r"(bytes) : "memory");
}
__device__ __forceinline__ void prefetch_l2(const void* p, int bytes) { asm volatile("cp.async.bulk.prefetch.L2.global [%0], %1;" ::"l"(p), "r"(bytes) : "memory"); }
__device__ __forceinline__ void prefetch_tile(const CUtensorMap* tm, int c0, int c1) {
  asm volatile("cp.async.bulk.prefetch.tensor.2d.L2.global.tile [%0, {%1, %2}];" ::"l"(tm), "r"(c0), "r"(c1) : "memory");
}
__device__ __forceinline__ void prefetch_map(const CUtensorMap* tm) { asm volatile("prefetch.tensormap [%0];" ::"l"(tm) : "memory"); }
__device__ __forceinline__ uint32_t pack_bf16(float lo, float hi) {
  uint32_t r; asm("cvt.rn.bf16x2.f32 %0, %1, %2;" : "=r"(r) : "f"(hi), "f"(lo)); return r;
}
__device__ __forceinline__ float bf_lo(uint32_t v) { return __uint_as_float(v << 16); }
__device__ __forceinline__ float bf_hi(uint32_t v) { return __uint_as_float(v & 0xFFFF0000u); }
__device__ __forceinline__ float bf_round(float x) { return __bfloat162float(__float2bfloat16_rn(x)); }
__device__ __forceinline__ uint32_t bmul2(uint32_t a, uint32_t b) { uint32_t r; asm("mul.rn.bf16x2 %0, %1, %2;" : "=r"(r) : "r"(a), "r"(b)); return r; }
__device__ __forceinline__ uint32_t bfma2(uint32_t a, uint32_t b, uint32_t c) { uint32_t r; asm("fma.rn.bf16x2 %0, %1, %2, %3;" : "=r"(r) : "r"(a), "r"(b), "r"(c)); return r; }
__device__ __forceinline__ uint32_t badd2(uint32_t a, uint32_t b) { uint32_t r; asm("add.rn.bf16x2 %0, %1, %2;" : "=r"(r) : "r"(a), "r"(b)); return r; }
__device__ __forceinline__ uint32_t bsub2(uint32_t a, uint32_t b) { uint32_t r; asm("sub.rn.bf16x2 %0, %1, %2;" : "=r"(r) : "r"(a), "r"(b)); return r; }
__device__ __forceinline__ uint32_t tagged(float v, uint32_t ep) { return (__float_as_uint(v) & ~15u) | (ep & 15u); }
__device__ __forceinline__ float tanh_fast(float x) { float r; asm("tanh.approx.f32 %0, %1;" : "=f"(r) : "f"(x)); return r; }
__device__ __forceinline__ float rcp_fast(float x) { float r; asm("rcp.approx.ftz.f32 %0, %1;" : "=f"(r) : "f"(x)); return r; }
__device__ __forceinline__ float sqrt_fast(float x) { float r; asm("sqrt.approx.ftz.f32 %0, %1;" : "=f"(r) : "f"(x)); return r; }
__device__ __forceinline__ uint32_t lds32(uint32_t a) { uint32_t v; asm volatile("ld.shared.b32 %0, [%1];" : "=r"(v) : "r"(a)); return v; }
__device__ __forceinline__ uint4 lds128(uint32_t a) { uint4 v; asm volatile("ld.shared.v4.b32 {%0,%1,%2,%3}, [%4];" : "=r"(v.x), "=r"(v.y), "=r"(v.z), "=r"(v.w) : "r"(a)); return v; }
__device__ __forceinline__ float2 lds64f(uint32_t a) { float2 v; asm volatile("ld.shared.v2.f32 {%0,%1}, [%2];" : "=f"(v.x), "=f"(v.y) : "r"(a)); return v; }
__device__ __forceinline__ void sts64f(uint32_t a, float x, float y) { asm volatile("st.shared.v2.f32 [%0], {%1,%2};" ::"r"(a), "f"(x), "f"(y) : "memory"); }
__device__ __forceinline__ void sts32(uint32_t a, uint32_t x) { asm volatile("st.shared.b32 [%0], %1;" ::"r"(a), "r"(x) : "memory"); }
__device__ __forceinline__ void sts128(uint32_t a, uint32_t x, uint32_t y, uint32_t z, uint32_t w) { asm volatile("st.shared.v4.b32 [%0], {%1,%2,%3,%4};" ::"r"(a), "r"(x), "r"(y), "r"(z), "r"(w) : "memory"); }
__device__ __forceinline__ void stsm4(uint32_t a, uint32_t r0, uint32_t r1, uint32_t r2, uint32_t r3) {
  asm volatile("stmatrix.sync.aligned.m8n8.x4.shared.b16 [%0], {%1,%2,%3,%4};" ::"r"(a), "r"(r0), "r"(r1), "r"(r2), "r"(r3) : "memory");
}
__device__ __forceinline__ void stsm4t(uint32_t a, uint32_t r0, uint32_t r1, uint32_t r2, uint32_t r3) {
  asm volatile("stmatrix.sync.aligned.m8n8.x4.trans.shared.b16 [%0], {%1,%2,%3,%4};" ::"r"(a), "r"(r0), "r"(r1), "r"(r2), "r"(r3) : "memory");
}
__device__ __forceinline__ void stsm2(uint32_t a, uint32_t r0, uint32_t r1) {
  asm volatile("stmatrix.sync.aligned.m8n8.x2.shared.b16 [%0], {%1,%2};" ::"r"(a), "r"(r0), "r"(r1) : "memory");
}
__device__ __forceinline__ void ldsm4(uint32_t a, uint32_t& r0, uint32_t& r1, uint32_t& r2, uint32_t& r3) {
  asm volatile("ldmatrix.sync.aligned.m8n8.x4.shared.b16 {%0,%1,%2,%3}, [%4];" : "=r"(r0), "=r"(r1), "=r"(r2), "=r"(r3) : "r"(a) : "memory");
}
__device__ __forceinline__ void ldsm4t(uint32_t a, uint32_t& r0, uint32_t& r1, uint32_t& r2, uint32_t& r3) {
  asm volatile("ldmatrix.sync.aligned.m8n8.x4.trans.shared.b16 {%0,%1,%2,%3}, [%4];" : "=r"(r0), "=r"(r1), "=r"(r2), "=r"(r3) : "r"(a) : "memory");
}
__device__ __forceinline__ uint32_t mapa(uint32_t a, uint32_t rank) { uint32_t r; asm("mapa.shared::cluster.u32 %0, %1, %2;" : "=r"(r) : "r"(a), "r"(rank)); return r; }
__device__ __forceinline__ void mbar_arrive_remote(uint32_t a) { asm volatile("mbarrier.arrive.relaxed.cluster.shared::cluster.b64 _, [%0];" ::"r"(a) : "memory"); }
__device__ __forceinline__ void st_async128(uint32_t a, uint32_t x, uint32_t y, uint32_t z, uint32_t w, uint32_t bar) {
  asm volatile("st.async.weak.shared::cluster.mbarrier::complete_tx::bytes.v4.b32 [%0], {%1,%2,%3,%4}, [%5];" ::"r"(a), "r"(x), "r"(y), "r"(z), "r"(w), "r"(bar) : "memory");
}
#define TS(i)

#define TSKV
__device__ __forceinline__ void wg_ss_216(float (&d)[108], uint64_t da, uint64_t db, int sd) {
  asm volatile("{\n.reg .pred p;\nsetp.ne.b32 p, %110, 0;\n"
    "wgmma.mma_async.sync.aligned.m64n216k16.f32.bf16.bf16 {%0,%1,%2,%3,%4,%5,%6,%7,%8,%9,%10,%11,%12,%13,%14,%15,%16,%17,%18,%19,%20,%21,%22,%23,%24,%25,%26,%27,%28,%29,%30,%31,%32,%33,%34,%35,%36,%37,%38,%39,%40,%41,%42,%43,%44,%45,%46,%47,%48,%49,%50,%51,%52,%53,%54,%55,%56,%57,%58,%59,%60,%61,%62,%63,%64,%65,%66,%67,%68,%69,%70,%71,%72,%73,%74,%75,%76,%77,%78,%79,%80,%81,%82,%83,%84,%85,%86,%87,%88,%89,%90,%91,%92,%93,%94,%95,%96,%97,%98,%99,%100,%101,%102,%103,%104,%105,%106,%107}, %108, %109, p, 1, 1, 0, 1;\n}\n"
    : "+f"(d[0]),"+f"(d[1]),"+f"(d[2]),"+f"(d[3]),"+f"(d[4]),"+f"(d[5]),"+f"(d[6]),"+f"(d[7]),"+f"(d[8]),"+f"(d[9]),"+f"(d[10]),"+f"(d[11]),"+f"(d[12]),"+f"(d[13]),"+f"(d[14]),"+f"(d[15]),"+f"(d[16]),"+f"(d[17]),"+f"(d[18]),"+f"(d[19]),"+f"(d[20]),"+f"(d[21]),"+f"(d[22]),"+f"(d[23]),"+f"(d[24]),"+f"(d[25]),"+f"(d[26]),"+f"(d[27]),"+f"(d[28]),"+f"(d[29]),"+f"(d[30]),"+f"(d[31]),"+f"(d[32]),"+f"(d[33]),"+f"(d[34]),"+f"(d[35]),"+f"(d[36]),"+f"(d[37]),"+f"(d[38]),"+f"(d[39]),"+f"(d[40]),"+f"(d[41]),"+f"(d[42]),"+f"(d[43]),"+f"(d[44]),"+f"(d[45]),"+f"(d[46]),"+f"(d[47]),"+f"(d[48]),"+f"(d[49]),"+f"(d[50]),"+f"(d[51]),"+f"(d[52]),"+f"(d[53]),"+f"(d[54]),"+f"(d[55]),"+f"(d[56]),"+f"(d[57]),"+f"(d[58]),"+f"(d[59]),"+f"(d[60]),"+f"(d[61]),"+f"(d[62]),"+f"(d[63]),"+f"(d[64]),"+f"(d[65]),"+f"(d[66]),"+f"(d[67]),"+f"(d[68]),"+f"(d[69]),"+f"(d[70]),"+f"(d[71]),"+f"(d[72]),"+f"(d[73]),"+f"(d[74]),"+f"(d[75]),"+f"(d[76]),"+f"(d[77]),"+f"(d[78]),"+f"(d[79]),"+f"(d[80]),"+f"(d[81]),"+f"(d[82]),"+f"(d[83]),"+f"(d[84]),"+f"(d[85]),"+f"(d[86]),"+f"(d[87]),"+f"(d[88]),"+f"(d[89]),"+f"(d[90]),"+f"(d[91]),"+f"(d[92]),"+f"(d[93]),"+f"(d[94]),"+f"(d[95]),"+f"(d[96]),"+f"(d[97]),"+f"(d[98]),"+f"(d[99]),"+f"(d[100]),"+f"(d[101]),"+f"(d[102]),"+f"(d[103]),"+f"(d[104]),"+f"(d[105]),"+f"(d[106]),"+f"(d[107]) : "l"(da), "l"(db), "r"(sd));
}
__device__ __forceinline__ void wg_ss_160(float (&d)[80], uint64_t da, uint64_t db, int sd) {
  asm volatile("{\n.reg .pred p;\nsetp.ne.b32 p, %82, 0;\n"
    "wgmma.mma_async.sync.aligned.m64n160k16.f32.bf16.bf16 {%0,%1,%2,%3,%4,%5,%6,%7,%8,%9,%10,%11,%12,%13,%14,%15,%16,%17,%18,%19,%20,%21,%22,%23,%24,%25,%26,%27,%28,%29,%30,%31,%32,%33,%34,%35,%36,%37,%38,%39,%40,%41,%42,%43,%44,%45,%46,%47,%48,%49,%50,%51,%52,%53,%54,%55,%56,%57,%58,%59,%60,%61,%62,%63,%64,%65,%66,%67,%68,%69,%70,%71,%72,%73,%74,%75,%76,%77,%78,%79}, %80, %81, p, 1, 1, 0, 1;\n}\n"
    : "+f"(d[0]),"+f"(d[1]),"+f"(d[2]),"+f"(d[3]),"+f"(d[4]),"+f"(d[5]),"+f"(d[6]),"+f"(d[7]),"+f"(d[8]),"+f"(d[9]),"+f"(d[10]),"+f"(d[11]),"+f"(d[12]),"+f"(d[13]),"+f"(d[14]),"+f"(d[15]),"+f"(d[16]),"+f"(d[17]),"+f"(d[18]),"+f"(d[19]),"+f"(d[20]),"+f"(d[21]),"+f"(d[22]),"+f"(d[23]),"+f"(d[24]),"+f"(d[25]),"+f"(d[26]),"+f"(d[27]),"+f"(d[28]),"+f"(d[29]),"+f"(d[30]),"+f"(d[31]),"+f"(d[32]),"+f"(d[33]),"+f"(d[34]),"+f"(d[35]),"+f"(d[36]),"+f"(d[37]),"+f"(d[38]),"+f"(d[39]),"+f"(d[40]),"+f"(d[41]),"+f"(d[42]),"+f"(d[43]),"+f"(d[44]),"+f"(d[45]),"+f"(d[46]),"+f"(d[47]),"+f"(d[48]),"+f"(d[49]),"+f"(d[50]),"+f"(d[51]),"+f"(d[52]),"+f"(d[53]),"+f"(d[54]),"+f"(d[55]),"+f"(d[56]),"+f"(d[57]),"+f"(d[58]),"+f"(d[59]),"+f"(d[60]),"+f"(d[61]),"+f"(d[62]),"+f"(d[63]),"+f"(d[64]),"+f"(d[65]),"+f"(d[66]),"+f"(d[67]),"+f"(d[68]),"+f"(d[69]),"+f"(d[70]),"+f"(d[71]),"+f"(d[72]),"+f"(d[73]),"+f"(d[74]),"+f"(d[75]),"+f"(d[76]),"+f"(d[77]),"+f"(d[78]),"+f"(d[79]) : "l"(da), "l"(db), "r"(sd));
}
__device__ __forceinline__ void wg_rs_216(float (&d)[108], uint32_t a0, uint32_t a1, uint32_t a2, uint32_t a3, uint64_t db) {
  asm volatile("{\n.reg .pred p;\nsetp.ne.b32 p, 1, 0;\n"
    "wgmma.mma_async.sync.aligned.m64n216k16.f32.bf16.bf16 {%0,%1,%2,%3,%4,%5,%6,%7,%8,%9,%10,%11,%12,%13,%14,%15,%16,%17,%18,%19,%20,%21,%22,%23,%24,%25,%26,%27,%28,%29,%30,%31,%32,%33,%34,%35,%36,%37,%38,%39,%40,%41,%42,%43,%44,%45,%46,%47,%48,%49,%50,%51,%52,%53,%54,%55,%56,%57,%58,%59,%60,%61,%62,%63,%64,%65,%66,%67,%68,%69,%70,%71,%72,%73,%74,%75,%76,%77,%78,%79,%80,%81,%82,%83,%84,%85,%86,%87,%88,%89,%90,%91,%92,%93,%94,%95,%96,%97,%98,%99,%100,%101,%102,%103,%104,%105,%106,%107}, {%108,%109,%110,%111}, %112, p, 1, 1, 1;\n}\n"
    : "+f"(d[0]),"+f"(d[1]),"+f"(d[2]),"+f"(d[3]),"+f"(d[4]),"+f"(d[5]),"+f"(d[6]),"+f"(d[7]),"+f"(d[8]),"+f"(d[9]),"+f"(d[10]),"+f"(d[11]),"+f"(d[12]),"+f"(d[13]),"+f"(d[14]),"+f"(d[15]),"+f"(d[16]),"+f"(d[17]),"+f"(d[18]),"+f"(d[19]),"+f"(d[20]),"+f"(d[21]),"+f"(d[22]),"+f"(d[23]),"+f"(d[24]),"+f"(d[25]),"+f"(d[26]),"+f"(d[27]),"+f"(d[28]),"+f"(d[29]),"+f"(d[30]),"+f"(d[31]),"+f"(d[32]),"+f"(d[33]),"+f"(d[34]),"+f"(d[35]),"+f"(d[36]),"+f"(d[37]),"+f"(d[38]),"+f"(d[39]),"+f"(d[40]),"+f"(d[41]),"+f"(d[42]),"+f"(d[43]),"+f"(d[44]),"+f"(d[45]),"+f"(d[46]),"+f"(d[47]),"+f"(d[48]),"+f"(d[49]),"+f"(d[50]),"+f"(d[51]),"+f"(d[52]),"+f"(d[53]),"+f"(d[54]),"+f"(d[55]),"+f"(d[56]),"+f"(d[57]),"+f"(d[58]),"+f"(d[59]),"+f"(d[60]),"+f"(d[61]),"+f"(d[62]),"+f"(d[63]),"+f"(d[64]),"+f"(d[65]),"+f"(d[66]),"+f"(d[67]),"+f"(d[68]),"+f"(d[69]),"+f"(d[70]),"+f"(d[71]),"+f"(d[72]),"+f"(d[73]),"+f"(d[74]),"+f"(d[75]),"+f"(d[76]),"+f"(d[77]),"+f"(d[78]),"+f"(d[79]),"+f"(d[80]),"+f"(d[81]),"+f"(d[82]),"+f"(d[83]),"+f"(d[84]),"+f"(d[85]),"+f"(d[86]),"+f"(d[87]),"+f"(d[88]),"+f"(d[89]),"+f"(d[90]),"+f"(d[91]),"+f"(d[92]),"+f"(d[93]),"+f"(d[94]),"+f"(d[95]),"+f"(d[96]),"+f"(d[97]),"+f"(d[98]),"+f"(d[99]),"+f"(d[100]),"+f"(d[101]),"+f"(d[102]),"+f"(d[103]),"+f"(d[104]),"+f"(d[105]),"+f"(d[106]),"+f"(d[107]) : "r"(a0), "r"(a1), "r"(a2), "r"(a3), "l"(db));
}
__device__ __forceinline__ void wg_cv_0_0(float (&d)[128], uint32_t a0, uint32_t a1, uint32_t a2, uint32_t a3, uint32_t db) {
  asm volatile("{\n.reg .pred p;\n.reg .b64 t;\nsetp.ne.b32 p, 0, 0;\nmov.b64 t, {%20, 8};\n"
    "wgmma.mma_async.sync.aligned.m64n32k16.f32.bf16.bf16 {%0,%1,%2,%3,%4,%5,%6,%7,%8,%9,%10,%11,%12,%13,%14,%15}, {%16,%17,%18,%19}, t, p, 1, 1, 0;\n}\n"
    : "+f"(d[0]),"+f"(d[1]),"+f"(d[2]),"+f"(d[3]),"+f"(d[4]),"+f"(d[5]),"+f"(d[6]),"+f"(d[7]),"+f"(d[8]),"+f"(d[9]),"+f"(d[10]),"+f"(d[11]),"+f"(d[12]),"+f"(d[13]),"+f"(d[14]),"+f"(d[15]) : "r"(a0), "r"(a1), "r"(a2), "r"(a3), "r"(db));
}
__device__ __forceinline__ void wg_cv_0_1(float (&d)[128], uint32_t a0, uint32_t a1, uint32_t a2, uint32_t a3, uint32_t db) {
  asm volatile("{\n.reg .pred p;\n.reg .b64 t;\nsetp.ne.b32 p, 1, 0;\nmov.b64 t, {%20, 8};\n"
    "wgmma.mma_async.sync.aligned.m64n32k16.f32.bf16.bf16 {%0,%1,%2,%3,%4,%5,%6,%7,%8,%9,%10,%11,%12,%13,%14,%15}, {%16,%17,%18,%19}, t, p, 1, 1, 0;\n}\n"
    : "+f"(d[0]),"+f"(d[1]),"+f"(d[2]),"+f"(d[3]),"+f"(d[4]),"+f"(d[5]),"+f"(d[6]),"+f"(d[7]),"+f"(d[8]),"+f"(d[9]),"+f"(d[10]),"+f"(d[11]),"+f"(d[12]),"+f"(d[13]),"+f"(d[14]),"+f"(d[15]) : "r"(a0), "r"(a1), "r"(a2), "r"(a3), "r"(db));
}
__device__ __forceinline__ void wg_cv_1_0(float (&d)[128], uint32_t a0, uint32_t a1, uint32_t a2, uint32_t a3, uint32_t db) {
  asm volatile("{\n.reg .pred p;\n.reg .b64 t;\nsetp.ne.b32 p, 0, 0;\nmov.b64 t, {%20, 8};\n"
    "wgmma.mma_async.sync.aligned.m64n32k16.f32.bf16.bf16 {%0,%1,%2,%3,%4,%5,%6,%7,%8,%9,%10,%11,%12,%13,%14,%15}, {%16,%17,%18,%19}, t, p, 1, 1, 0;\n}\n"
    : "+f"(d[16]),"+f"(d[17]),"+f"(d[18]),"+f"(d[19]),"+f"(d[20]),"+f"(d[21]),"+f"(d[22]),"+f"(d[23]),"+f"(d[24]),"+f"(d[25]),"+f"(d[26]),"+f"(d[27]),"+f"(d[28]),"+f"(d[29]),"+f"(d[30]),"+f"(d[31]) : "r"(a0), "r"(a1), "r"(a2), "r"(a3), "r"(db));
}
__device__ __forceinline__ void wg_cv_1_1(float (&d)[128], uint32_t a0, uint32_t a1, uint32_t a2, uint32_t a3, uint32_t db) {
  asm volatile("{\n.reg .pred p;\n.reg .b64 t;\nsetp.ne.b32 p, 1, 0;\nmov.b64 t, {%20, 8};\n"
    "wgmma.mma_async.sync.aligned.m64n32k16.f32.bf16.bf16 {%0,%1,%2,%3,%4,%5,%6,%7,%8,%9,%10,%11,%12,%13,%14,%15}, {%16,%17,%18,%19}, t, p, 1, 1, 0;\n}\n"
    : "+f"(d[16]),"+f"(d[17]),"+f"(d[18]),"+f"(d[19]),"+f"(d[20]),"+f"(d[21]),"+f"(d[22]),"+f"(d[23]),"+f"(d[24]),"+f"(d[25]),"+f"(d[26]),"+f"(d[27]),"+f"(d[28]),"+f"(d[29]),"+f"(d[30]),"+f"(d[31]) : "r"(a0), "r"(a1), "r"(a2), "r"(a3), "r"(db));
}
__device__ __forceinline__ void wg_cv_2_0(float (&d)[128], uint32_t a0, uint32_t a1, uint32_t a2, uint32_t a3, uint32_t db) {
  asm volatile("{\n.reg .pred p;\n.reg .b64 t;\nsetp.ne.b32 p, 0, 0;\nmov.b64 t, {%20, 8};\n"
    "wgmma.mma_async.sync.aligned.m64n32k16.f32.bf16.bf16 {%0,%1,%2,%3,%4,%5,%6,%7,%8,%9,%10,%11,%12,%13,%14,%15}, {%16,%17,%18,%19}, t, p, 1, 1, 0;\n}\n"
    : "+f"(d[32]),"+f"(d[33]),"+f"(d[34]),"+f"(d[35]),"+f"(d[36]),"+f"(d[37]),"+f"(d[38]),"+f"(d[39]),"+f"(d[40]),"+f"(d[41]),"+f"(d[42]),"+f"(d[43]),"+f"(d[44]),"+f"(d[45]),"+f"(d[46]),"+f"(d[47]) : "r"(a0), "r"(a1), "r"(a2), "r"(a3), "r"(db));
}
__device__ __forceinline__ void wg_cv_2_1(float (&d)[128], uint32_t a0, uint32_t a1, uint32_t a2, uint32_t a3, uint32_t db) {
  asm volatile("{\n.reg .pred p;\n.reg .b64 t;\nsetp.ne.b32 p, 1, 0;\nmov.b64 t, {%20, 8};\n"
    "wgmma.mma_async.sync.aligned.m64n32k16.f32.bf16.bf16 {%0,%1,%2,%3,%4,%5,%6,%7,%8,%9,%10,%11,%12,%13,%14,%15}, {%16,%17,%18,%19}, t, p, 1, 1, 0;\n}\n"
    : "+f"(d[32]),"+f"(d[33]),"+f"(d[34]),"+f"(d[35]),"+f"(d[36]),"+f"(d[37]),"+f"(d[38]),"+f"(d[39]),"+f"(d[40]),"+f"(d[41]),"+f"(d[42]),"+f"(d[43]),"+f"(d[44]),"+f"(d[45]),"+f"(d[46]),"+f"(d[47]) : "r"(a0), "r"(a1), "r"(a2), "r"(a3), "r"(db));
}
__device__ __forceinline__ void wg_cv_3_0(float (&d)[128], uint32_t a0, uint32_t a1, uint32_t a2, uint32_t a3, uint32_t db) {
  asm volatile("{\n.reg .pred p;\n.reg .b64 t;\nsetp.ne.b32 p, 0, 0;\nmov.b64 t, {%20, 8};\n"
    "wgmma.mma_async.sync.aligned.m64n32k16.f32.bf16.bf16 {%0,%1,%2,%3,%4,%5,%6,%7,%8,%9,%10,%11,%12,%13,%14,%15}, {%16,%17,%18,%19}, t, p, 1, 1, 0;\n}\n"
    : "+f"(d[48]),"+f"(d[49]),"+f"(d[50]),"+f"(d[51]),"+f"(d[52]),"+f"(d[53]),"+f"(d[54]),"+f"(d[55]),"+f"(d[56]),"+f"(d[57]),"+f"(d[58]),"+f"(d[59]),"+f"(d[60]),"+f"(d[61]),"+f"(d[62]),"+f"(d[63]) : "r"(a0), "r"(a1), "r"(a2), "r"(a3), "r"(db));
}
__device__ __forceinline__ void wg_cv_3_1(float (&d)[128], uint32_t a0, uint32_t a1, uint32_t a2, uint32_t a3, uint32_t db) {
  asm volatile("{\n.reg .pred p;\n.reg .b64 t;\nsetp.ne.b32 p, 1, 0;\nmov.b64 t, {%20, 8};\n"
    "wgmma.mma_async.sync.aligned.m64n32k16.f32.bf16.bf16 {%0,%1,%2,%3,%4,%5,%6,%7,%8,%9,%10,%11,%12,%13,%14,%15}, {%16,%17,%18,%19}, t, p, 1, 1, 0;\n}\n"
    : "+f"(d[48]),"+f"(d[49]),"+f"(d[50]),"+f"(d[51]),"+f"(d[52]),"+f"(d[53]),"+f"(d[54]),"+f"(d[55]),"+f"(d[56]),"+f"(d[57]),"+f"(d[58]),"+f"(d[59]),"+f"(d[60]),"+f"(d[61]),"+f"(d[62]),"+f"(d[63]) : "r"(a0), "r"(a1), "r"(a2), "r"(a3), "r"(db));
}
__device__ __forceinline__ void wg_cv_4_0(float (&d)[128], uint32_t a0, uint32_t a1, uint32_t a2, uint32_t a3, uint32_t db) {
  asm volatile("{\n.reg .pred p;\n.reg .b64 t;\nsetp.ne.b32 p, 0, 0;\nmov.b64 t, {%20, 8};\n"
    "wgmma.mma_async.sync.aligned.m64n32k16.f32.bf16.bf16 {%0,%1,%2,%3,%4,%5,%6,%7,%8,%9,%10,%11,%12,%13,%14,%15}, {%16,%17,%18,%19}, t, p, 1, 1, 0;\n}\n"
    : "+f"(d[64]),"+f"(d[65]),"+f"(d[66]),"+f"(d[67]),"+f"(d[68]),"+f"(d[69]),"+f"(d[70]),"+f"(d[71]),"+f"(d[72]),"+f"(d[73]),"+f"(d[74]),"+f"(d[75]),"+f"(d[76]),"+f"(d[77]),"+f"(d[78]),"+f"(d[79]) : "r"(a0), "r"(a1), "r"(a2), "r"(a3), "r"(db));
}
__device__ __forceinline__ void wg_cv_4_1(float (&d)[128], uint32_t a0, uint32_t a1, uint32_t a2, uint32_t a3, uint32_t db) {
  asm volatile("{\n.reg .pred p;\n.reg .b64 t;\nsetp.ne.b32 p, 1, 0;\nmov.b64 t, {%20, 8};\n"
    "wgmma.mma_async.sync.aligned.m64n32k16.f32.bf16.bf16 {%0,%1,%2,%3,%4,%5,%6,%7,%8,%9,%10,%11,%12,%13,%14,%15}, {%16,%17,%18,%19}, t, p, 1, 1, 0;\n}\n"
    : "+f"(d[64]),"+f"(d[65]),"+f"(d[66]),"+f"(d[67]),"+f"(d[68]),"+f"(d[69]),"+f"(d[70]),"+f"(d[71]),"+f"(d[72]),"+f"(d[73]),"+f"(d[74]),"+f"(d[75]),"+f"(d[76]),"+f"(d[77]),"+f"(d[78]),"+f"(d[79]) : "r"(a0), "r"(a1), "r"(a2), "r"(a3), "r"(db));
}
__device__ __forceinline__ void wg_cv_5_0(float (&d)[128], uint32_t a0, uint32_t a1, uint32_t a2, uint32_t a3, uint32_t db) {
  asm volatile("{\n.reg .pred p;\n.reg .b64 t;\nsetp.ne.b32 p, 0, 0;\nmov.b64 t, {%20, 8};\n"
    "wgmma.mma_async.sync.aligned.m64n32k16.f32.bf16.bf16 {%0,%1,%2,%3,%4,%5,%6,%7,%8,%9,%10,%11,%12,%13,%14,%15}, {%16,%17,%18,%19}, t, p, 1, 1, 0;\n}\n"
    : "+f"(d[80]),"+f"(d[81]),"+f"(d[82]),"+f"(d[83]),"+f"(d[84]),"+f"(d[85]),"+f"(d[86]),"+f"(d[87]),"+f"(d[88]),"+f"(d[89]),"+f"(d[90]),"+f"(d[91]),"+f"(d[92]),"+f"(d[93]),"+f"(d[94]),"+f"(d[95]) : "r"(a0), "r"(a1), "r"(a2), "r"(a3), "r"(db));
}
__device__ __forceinline__ void wg_cv_5_1(float (&d)[128], uint32_t a0, uint32_t a1, uint32_t a2, uint32_t a3, uint32_t db) {
  asm volatile("{\n.reg .pred p;\n.reg .b64 t;\nsetp.ne.b32 p, 1, 0;\nmov.b64 t, {%20, 8};\n"
    "wgmma.mma_async.sync.aligned.m64n32k16.f32.bf16.bf16 {%0,%1,%2,%3,%4,%5,%6,%7,%8,%9,%10,%11,%12,%13,%14,%15}, {%16,%17,%18,%19}, t, p, 1, 1, 0;\n}\n"
    : "+f"(d[80]),"+f"(d[81]),"+f"(d[82]),"+f"(d[83]),"+f"(d[84]),"+f"(d[85]),"+f"(d[86]),"+f"(d[87]),"+f"(d[88]),"+f"(d[89]),"+f"(d[90]),"+f"(d[91]),"+f"(d[92]),"+f"(d[93]),"+f"(d[94]),"+f"(d[95]) : "r"(a0), "r"(a1), "r"(a2), "r"(a3), "r"(db));
}
__device__ __forceinline__ void wg_cv_6_0(float (&d)[128], uint32_t a0, uint32_t a1, uint32_t a2, uint32_t a3, uint32_t db) {
  asm volatile("{\n.reg .pred p;\n.reg .b64 t;\nsetp.ne.b32 p, 0, 0;\nmov.b64 t, {%20, 8};\n"
    "wgmma.mma_async.sync.aligned.m64n32k16.f32.bf16.bf16 {%0,%1,%2,%3,%4,%5,%6,%7,%8,%9,%10,%11,%12,%13,%14,%15}, {%16,%17,%18,%19}, t, p, 1, 1, 0;\n}\n"
    : "+f"(d[96]),"+f"(d[97]),"+f"(d[98]),"+f"(d[99]),"+f"(d[100]),"+f"(d[101]),"+f"(d[102]),"+f"(d[103]),"+f"(d[104]),"+f"(d[105]),"+f"(d[106]),"+f"(d[107]),"+f"(d[108]),"+f"(d[109]),"+f"(d[110]),"+f"(d[111]) : "r"(a0), "r"(a1), "r"(a2), "r"(a3), "r"(db));
}
__device__ __forceinline__ void wg_cv_6_1(float (&d)[128], uint32_t a0, uint32_t a1, uint32_t a2, uint32_t a3, uint32_t db) {
  asm volatile("{\n.reg .pred p;\n.reg .b64 t;\nsetp.ne.b32 p, 1, 0;\nmov.b64 t, {%20, 8};\n"
    "wgmma.mma_async.sync.aligned.m64n32k16.f32.bf16.bf16 {%0,%1,%2,%3,%4,%5,%6,%7,%8,%9,%10,%11,%12,%13,%14,%15}, {%16,%17,%18,%19}, t, p, 1, 1, 0;\n}\n"
    : "+f"(d[96]),"+f"(d[97]),"+f"(d[98]),"+f"(d[99]),"+f"(d[100]),"+f"(d[101]),"+f"(d[102]),"+f"(d[103]),"+f"(d[104]),"+f"(d[105]),"+f"(d[106]),"+f"(d[107]),"+f"(d[108]),"+f"(d[109]),"+f"(d[110]),"+f"(d[111]) : "r"(a0), "r"(a1), "r"(a2), "r"(a3), "r"(db));
}
__device__ __forceinline__ void wg_cv_7_0(float (&d)[128], uint32_t a0, uint32_t a1, uint32_t a2, uint32_t a3, uint32_t db) {
  asm volatile("{\n.reg .pred p;\n.reg .b64 t;\nsetp.ne.b32 p, 0, 0;\nmov.b64 t, {%20, 8};\n"
    "wgmma.mma_async.sync.aligned.m64n32k16.f32.bf16.bf16 {%0,%1,%2,%3,%4,%5,%6,%7,%8,%9,%10,%11,%12,%13,%14,%15}, {%16,%17,%18,%19}, t, p, 1, 1, 0;\n}\n"
    : "+f"(d[112]),"+f"(d[113]),"+f"(d[114]),"+f"(d[115]),"+f"(d[116]),"+f"(d[117]),"+f"(d[118]),"+f"(d[119]),"+f"(d[120]),"+f"(d[121]),"+f"(d[122]),"+f"(d[123]),"+f"(d[124]),"+f"(d[125]),"+f"(d[126]),"+f"(d[127]) : "r"(a0), "r"(a1), "r"(a2), "r"(a3), "r"(db));
}
__device__ __forceinline__ void wg_cv_7_1(float (&d)[128], uint32_t a0, uint32_t a1, uint32_t a2, uint32_t a3, uint32_t db) {
  asm volatile("{\n.reg .pred p;\n.reg .b64 t;\nsetp.ne.b32 p, 1, 0;\nmov.b64 t, {%20, 8};\n"
    "wgmma.mma_async.sync.aligned.m64n32k16.f32.bf16.bf16 {%0,%1,%2,%3,%4,%5,%6,%7,%8,%9,%10,%11,%12,%13,%14,%15}, {%16,%17,%18,%19}, t, p, 1, 1, 0;\n}\n"
    : "+f"(d[112]),"+f"(d[113]),"+f"(d[114]),"+f"(d[115]),"+f"(d[116]),"+f"(d[117]),"+f"(d[118]),"+f"(d[119]),"+f"(d[120]),"+f"(d[121]),"+f"(d[122]),"+f"(d[123]),"+f"(d[124]),"+f"(d[125]),"+f"(d[126]),"+f"(d[127]) : "r"(a0), "r"(a1), "r"(a2), "r"(a3), "r"(db));
}
template <class F, class T> __device__ __forceinline__ void conv_chain_1(float (&d)[128], uint32_t (&a)[64], uint32_t db, uint32_t ao, uint32_t ab, F hand, T dead) {
  wg_cv_7_0(d, a[60], a[61], a[62], a[63], db + 0);
  wg_cv_6_0(d, a[52], a[53], a[54], a[55], db + 0);
  dead();
  wg_cv_7_1(d, a[56], a[57], a[58], a[59], db + 16);
  wg_cv_5_0(d, a[44], a[45], a[46], a[47], db + 0);
  wg_cv_6_1(d, a[48], a[49], a[50], a[51], db + 16);
  wg_cv_7_1(d, a[52], a[53], a[54], a[55], db + 32);
  wg_cv_5_1(d, a[40], a[41], a[42], a[43], db + 16);
  wg_cv_6_1(d, a[44], a[45], a[46], a[47], db + 32);
  wg_cv_7_1(d, a[48], a[49], a[50], a[51], db + 48);
  wg_cv_6_1(d, a[40], a[41], a[42], a[43], db + 48);
  wg_cv_7_1(d, a[44], a[45], a[46], a[47], db + 64);
  wg_cv_7_1(d, a[40], a[41], a[42], a[43], db + 80);
  wg_commit();
  wg_cv_7_1(d, a[36], a[37], a[38], a[39], db + 96);
  wg_cv_6_1(d, a[36], a[37], a[38], a[39], db + 64);
  wg_cv_5_1(d, a[36], a[37], a[38], a[39], db + 32);
  wg_cv_4_0(d, a[36], a[37], a[38], a[39], db + 0);
  wg_commit(); wg_wait<1>();
  wg_cv_7_1(d, a[32], a[33], a[34], a[35], db + 112);
  wg_cv_6_1(d, a[32], a[33], a[34], a[35], db + 80);
  wg_cv_5_1(d, a[32], a[33], a[34], a[35], db + 48);
  a[60] = lds32(ab + (3840));
  a[61] = lds32(ab + (3968));
  a[62] = lds32(ab + (3824));
  a[63] = lds32(ab + (3952));
  wg_cv_4_1(d, a[32], a[33], a[34], a[35], db + 16);
  wg_cv_7_1(d, a[28], a[29], a[30], a[31], db + 128);
  wg_cv_6_1(d, a[28], a[29], a[30], a[31], db + 96);
  wg_cv_5_1(d, a[28], a[29], a[30], a[31], db + 64);
  a[56] = lds32(ab + (3584));
  a[57] = lds32(ab + (3712));
  a[58] = lds32(ab + (3568));
  a[59] = lds32(ab + (3696));
  wg_cv_4_1(d, a[28], a[29], a[30], a[31], db + 32);
  wg_cv_3_0(d, a[28], a[29], a[30], a[31], db + 0);
  wg_cv_7_1(d, a[24], a[25], a[26], a[27], db + 144);
  wg_cv_6_1(d, a[24], a[25], a[26], a[27], db + 112);
  a[52] = lds32(ab + (3328));
  a[53] = lds32(ab + (3456));
  a[54] = lds32(ab + (3312));
  a[55] = lds32(ab + (3440));
  wg_cv_5_1(d, a[24], a[25], a[26], a[27], db + 80);
  wg_cv_4_1(d, a[24], a[25], a[26], a[27], db + 48);
  wg_cv_3_1(d, a[24], a[25], a[26], a[27], db + 16);
  wg_commit();
  wg_cv_7_1(d, a[20], a[21], a[22], a[23], db + 160);
  wg_cv_6_1(d, a[20], a[21], a[22], a[23], db + 128);
  wg_cv_5_1(d, a[20], a[21], a[22], a[23], db + 96);
  wg_cv_4_1(d, a[20], a[21], a[22], a[23], db + 64);
  wg_commit(); wg_wait<1>();
  a[48] = lds32(ab + (3072));
  a[49] = lds32(ab + (3200));
  a[50] = lds32(ab + (3056));
  a[51] = lds32(ab + (3184));
  wg_cv_3_1(d, a[20], a[21], a[22], a[23], db + 32);
  wg_cv_2_0(d, a[20], a[21], a[22], a[23], db + 0);
  wg_cv_7_1(d, a[16], a[17], a[18], a[19], db + 176);
  wg_cv_6_1(d, a[16], a[17], a[18], a[19], db + 144);
  a[44] = lds32(ab + (2816));
  a[45] = lds32(ab + (2944));
  a[46] = lds32(ab + (2800));
  a[47] = lds32(ab + (2928));
  wg_cv_5_1(d, a[16], a[17], a[18], a[19], db + 112);
  wg_cv_4_1(d, a[16], a[17], a[18], a[19], db + 80);
  wg_cv_3_1(d, a[16], a[17], a[18], a[19], db + 48);
  wg_cv_2_1(d, a[16], a[17], a[18], a[19], db + 16);
  a[40] = lds32(ab + (2560));
  a[41] = lds32(ab + (2688));
  a[42] = lds32(ab + (2544));
  a[43] = lds32(ab + (2672));
  wg_cv_7_1(d, a[12], a[13], a[14], a[15], db + 192);
  wg_cv_6_1(d, a[12], a[13], a[14], a[15], db + 160);
  wg_cv_5_1(d, a[12], a[13], a[14], a[15], db + 128);
  wg_cv_4_1(d, a[12], a[13], a[14], a[15], db + 96);
  a[36] = lds32(ab + (2304));
  a[37] = lds32(ab + (2432));
  a[38] = lds32(ab + (2288));
  a[39] = lds32(ab + (2416));
  wg_cv_3_1(d, a[12], a[13], a[14], a[15], db + 64);
  wg_cv_2_1(d, a[12], a[13], a[14], a[15], db + 32);
  wg_cv_1_0(d, a[12], a[13], a[14], a[15], db + 0);
  wg_cv_7_1(d, a[8], a[9], a[10], a[11], db + 208);
  a[32] = lds32(ab + (2048));
  a[33] = lds32(ab + (2176));
  a[34] = lds32(ab + (2032));
  a[35] = lds32(ab + (2160));
  wg_cv_6_1(d, a[8], a[9], a[10], a[11], db + 176);
  wg_cv_5_1(d, a[8], a[9], a[10], a[11], db + 144);
  wg_cv_4_1(d, a[8], a[9], a[10], a[11], db + 112);
  wg_cv_3_1(d, a[8], a[9], a[10], a[11], db + 80);
  a[28] = lds32(ab + (1792));
  a[29] = lds32(ab + (1920));
  a[30] = lds32(ab + (1776));
  a[31] = lds32(ab + (1904));
  wg_cv_2_1(d, a[8], a[9], a[10], a[11], db + 48);
  wg_cv_1_1(d, a[8], a[9], a[10], a[11], db + 16);
  wg_commit();
  wg_cv_7_1(d, a[4], a[5], a[6], a[7], db + 224);
  wg_cv_6_1(d, a[4], a[5], a[6], a[7], db + 192);
  wg_cv_5_1(d, a[4], a[5], a[6], a[7], db + 160);
  wg_cv_4_1(d, a[4], a[5], a[6], a[7], db + 128);
  wg_commit(); wg_wait<1>();
  a[24] = lds32(ab + (1536));
  a[25] = lds32(ab + (1664));
  a[26] = lds32(ab + (1520));
  a[27] = lds32(ab + (1648));
  hand();
  wg_cv_3_1(d, a[4], a[5], a[6], a[7], db + 96);
  wg_cv_2_1(d, a[4], a[5], a[6], a[7], db + 64);
  wg_cv_1_1(d, a[4], a[5], a[6], a[7], db + 32);
  wg_cv_0_0(d, a[4], a[5], a[6], a[7], db + 0);
  a[20] = lds32(ab + (1280));
  a[21] = lds32(ab + (1408));
  a[22] = lds32(ab + (1264));
  a[23] = lds32(ab + (1392));
  wg_cv_7_1(d, a[0], a[1], a[2], a[3], db + 240);
  wg_cv_6_1(d, a[0], a[1], a[2], a[3], db + 208);
  wg_cv_5_1(d, a[0], a[1], a[2], a[3], db + 176);
  wg_cv_4_1(d, a[0], a[1], a[2], a[3], db + 144);
  a[16] = lds32(ab + (1024));
  a[17] = lds32(ab + (1152));
  a[18] = lds32(ab + (1008));
  a[19] = lds32(ab + (1136));
  wg_cv_3_1(d, a[0], a[1], a[2], a[3], db + 112);
  wg_cv_2_1(d, a[0], a[1], a[2], a[3], db + 80);
  wg_cv_1_1(d, a[0], a[1], a[2], a[3], db + 48);
  wg_cv_0_1(d, a[0], a[1], a[2], a[3], db + 16);
  wg_commit();
  a[12] = lds32(ab + (768));
  a[13] = lds32(ab + (896));
  a[14] = lds32(ab + (752));
  a[15] = lds32(ab + (880));
  a[8] = lds32(ab + (512));
  a[9] = lds32(ab + (640));
  a[10] = lds32(ab + (496));
  a[11] = lds32(ab + (624));
}
template <class F, class T> __device__ __forceinline__ void conv_chain_0(float (&d)[128], uint32_t (&a)[64], uint32_t db, uint32_t ao, uint32_t ab, F hand, T dead) {
  wg_cv_7_0(d, a[60], a[61], a[62], a[63], db + 0);
  wg_cv_6_0(d, a[52], a[53], a[54], a[55], db + 0);
  dead();
  wg_cv_7_1(d, a[56], a[57], a[58], a[59], db + 16);
  wg_cv_5_0(d, a[44], a[45], a[46], a[47], db + 0);
  wg_cv_6_1(d, a[48], a[49], a[50], a[51], db + 16);
  wg_cv_7_1(d, a[52], a[53], a[54], a[55], db + 32);
  wg_cv_5_1(d, a[40], a[41], a[42], a[43], db + 16);
  wg_cv_6_1(d, a[44], a[45], a[46], a[47], db + 32);
  wg_cv_7_1(d, a[48], a[49], a[50], a[51], db + 48);
  wg_cv_6_1(d, a[40], a[41], a[42], a[43], db + 48);
  wg_cv_7_1(d, a[44], a[45], a[46], a[47], db + 64);
  wg_cv_7_1(d, a[40], a[41], a[42], a[43], db + 80);
  wg_commit();
  wg_cv_7_1(d, a[36], a[37], a[38], a[39], db + 96);
  wg_cv_6_1(d, a[36], a[37], a[38], a[39], db + 64);
  wg_cv_5_1(d, a[36], a[37], a[38], a[39], db + 32);
  wg_cv_4_0(d, a[36], a[37], a[38], a[39], db + 0);
  wg_cv_7_1(d, a[32], a[33], a[34], a[35], db + 112);
  wg_cv_6_1(d, a[32], a[33], a[34], a[35], db + 80);
  wg_cv_5_1(d, a[32], a[33], a[34], a[35], db + 48);
  wg_cv_4_1(d, a[32], a[33], a[34], a[35], db + 16);
  wg_cv_7_1(d, a[28], a[29], a[30], a[31], db + 128);
  wg_cv_6_1(d, a[28], a[29], a[30], a[31], db + 96);
  wg_cv_5_1(d, a[28], a[29], a[30], a[31], db + 64);
  wg_cv_4_1(d, a[28], a[29], a[30], a[31], db + 32);
  wg_cv_3_0(d, a[28], a[29], a[30], a[31], db + 0);
  wg_cv_7_1(d, a[24], a[25], a[26], a[27], db + 144);
  wg_cv_6_1(d, a[24], a[25], a[26], a[27], db + 112);
  wg_cv_5_1(d, a[24], a[25], a[26], a[27], db + 80);
  wg_cv_4_1(d, a[24], a[25], a[26], a[27], db + 48);
  wg_cv_3_1(d, a[24], a[25], a[26], a[27], db + 16);
  wg_commit();
  wg_cv_7_1(d, a[20], a[21], a[22], a[23], db + 160);
  wg_cv_6_1(d, a[20], a[21], a[22], a[23], db + 128);
  wg_cv_5_1(d, a[20], a[21], a[22], a[23], db + 96);
  wg_cv_4_1(d, a[20], a[21], a[22], a[23], db + 64);
  wg_cv_3_1(d, a[20], a[21], a[22], a[23], db + 32);
  wg_cv_2_0(d, a[20], a[21], a[22], a[23], db + 0);
  wg_cv_7_1(d, a[16], a[17], a[18], a[19], db + 176);
  wg_cv_6_1(d, a[16], a[17], a[18], a[19], db + 144);
  wg_cv_5_1(d, a[16], a[17], a[18], a[19], db + 112);
  wg_cv_4_1(d, a[16], a[17], a[18], a[19], db + 80);
  wg_cv_3_1(d, a[16], a[17], a[18], a[19], db + 48);
  wg_cv_2_1(d, a[16], a[17], a[18], a[19], db + 16);
  wg_cv_7_1(d, a[12], a[13], a[14], a[15], db + 192);
  wg_cv_6_1(d, a[12], a[13], a[14], a[15], db + 160);
  wg_cv_5_1(d, a[12], a[13], a[14], a[15], db + 128);
  wg_cv_4_1(d, a[12], a[13], a[14], a[15], db + 96);
  wg_cv_3_1(d, a[12], a[13], a[14], a[15], db + 64);
  wg_cv_2_1(d, a[12], a[13], a[14], a[15], db + 32);
  wg_cv_1_0(d, a[12], a[13], a[14], a[15], db + 0);
  wg_cv_7_1(d, a[8], a[9], a[10], a[11], db + 208);
  wg_cv_6_1(d, a[8], a[9], a[10], a[11], db + 176);
  wg_cv_5_1(d, a[8], a[9], a[10], a[11], db + 144);
  wg_cv_4_1(d, a[8], a[9], a[10], a[11], db + 112);
  wg_cv_3_1(d, a[8], a[9], a[10], a[11], db + 80);
  wg_cv_2_1(d, a[8], a[9], a[10], a[11], db + 48);
  wg_cv_1_1(d, a[8], a[9], a[10], a[11], db + 16);
  wg_commit();
  wg_cv_7_1(d, a[4], a[5], a[6], a[7], db + 224);
  wg_cv_6_1(d, a[4], a[5], a[6], a[7], db + 192);
  wg_cv_5_1(d, a[4], a[5], a[6], a[7], db + 160);
  wg_cv_4_1(d, a[4], a[5], a[6], a[7], db + 128);
  hand();
  wg_cv_3_1(d, a[4], a[5], a[6], a[7], db + 96);
  wg_cv_2_1(d, a[4], a[5], a[6], a[7], db + 64);
  wg_cv_1_1(d, a[4], a[5], a[6], a[7], db + 32);
  wg_cv_0_0(d, a[4], a[5], a[6], a[7], db + 0);
  wg_cv_7_1(d, a[0], a[1], a[2], a[3], db + 240);
  wg_cv_6_1(d, a[0], a[1], a[2], a[3], db + 208);
  wg_cv_5_1(d, a[0], a[1], a[2], a[3], db + 176);
  wg_cv_4_1(d, a[0], a[1], a[2], a[3], db + 144);
  wg_cv_3_1(d, a[0], a[1], a[2], a[3], db + 112);
  wg_cv_2_1(d, a[0], a[1], a[2], a[3], db + 80);
  wg_cv_1_1(d, a[0], a[1], a[2], a[3], db + 48);
  wg_cv_0_1(d, a[0], a[1], a[2], a[3], db + 16);
  wg_commit();
}
constexpr bool CV_OWN = false;
constexpr int CV_RELOADED = 2;

struct Params {
  const __nv_bfloat16 *q, *w1, *shift_k, *ssm_k, *ssm_D, *b1, *w2, *b2;
  __nv_bfloat16 *kvT, *yT;
  uint2* stat;
  uint32_t *cs, *cnt, *launch;
};
struct Maps { CUtensorMap q0, w1, w1x, k, v, hs, hx, ha, w2, w2x, kvs, qf, y, out; };

__global__ void __cluster_dims__(2, 1, 1) __launch_bounds__(384, 1) h3_kernel(const Params P, const __grid_constant__ Maps M) {
  extern __shared__ __align__(1024) uint8_t smem_raw[];
  constexpr uint32_t sc = 1024;
  const int tid = threadIdx.x, lane = tid & 31;
  auto pf0 = [&]() {
    const int l = min((int)blockIdx.x * 30 + lane, 3775);
    const char* p = l < 2048 ? reinterpret_cast<const char*>(P.q) + l * (DM * 2) : reinterpret_cast<const char*>(P.w1) + (l - 2048) * 128;
    asm volatile("prefetch.global.L2 [%0];" ::"l"(p));
  };
  if (tid < 32) { pf0(); if (tid == 0) { prefetch_map(&M.q0); prefetch_map(&M.w1); prefetch_map(&M.w1x); } }
  const int warp = __shfl_sync(0xffffffffu, tid >> 5, 0);
  const uint32_t sb = __shfl_sync(0xffffffffu, s32(smem_raw), 0);
  const int b = blockIdx.x, pr = b >> 1;
  const int pq = pr < 4 ? 32 + 8 * pr : (pr < 36 ? pr - 4 : pr - 3 + (((pr - 36) * 37) >> 8)), G = pq & 7, gi = pq >> 3;
  const int kh = b & 1, nt = (G & 1) * 2 + (gi & 1), rb = (G >> 1) * 4 + (gi >> 1);
  const int dir = (G ^ (G >> 1)) & 1, ri = (gi & 1) * 2 + kh, ci = (G >> 2) * 4 + (gi >> 1);
  const uint32_t gmap = (nt & 1) ? 0x03412u : 0x43210u;
  const int j = kh * 4 + nt;
  const uint32_t bar = sb + M_BAR;
  auto BAR = [&](int i) { return bar + 8 * i; };
  auto g1_load = [&](int kc) {
    const uint32_t st = sb + (kc & 3) * G1_STAGE, fb = BAR(B_F1 + (kc & 3));
    const int k0 = dir && kc >= 2 ? 704 - kc * 64 : kc * 64;
    mbar_expect(fb, G1_TX);
    tma2d(st, &M.q0, k0, rb * 128, fb); tma2d(st + 8192, &M.q0, k0, rb * 128 + 64, fb);
    tma3d(st + 16384, &M.w1, 0, k0, 3 * j, fb);
    tma2d(st + 40960, &M.w1x, 1536 + 24 * j, k0, fb);
  };
  auto kv_load = [&](int r, int hf) {
    const uint32_t st = sb + KVS + (r < 3 ? r : r - 3) * KV_BUF, fb = BAR((hf ? B_KIN1 : B_KIN) + r);
    mbar_expect(fb, KV_BUF / 2);
    tma2d(st + 4096 + hf * 2432, &M.k, 128 * r + 64 * (b & 1), 32 * (b >> 1) + 16 * hf - 3, fb);
    tma2d(st + hf * 2048, &M.v, 128 * r + 64 * (b & 1), 32 * (b >> 1) + 16 * hf, fb);
  };
  auto conv_sum = [&](int c, int ck, bool third, uint32_t ep) {
    const uint32_t ra = sb + cv_p(c) + ck * 16;
    __nv_bfloat16* yp = P.yT + (size_t)(128 * c + b) * SL + ck * 8;
    uint4 p[2][4];
    auto ld = [&](int u) {
#pragma unroll
      for (int w = 0; w < 4; w++) p[u & 1][w] = lds128((u == 0 && ck < 2 * w) ? sb + M_ZERO : ra + u * 512 + w * (4096 - 32));
    };
    auto st = [&](int u) {
      auto sum = [&](uint32_t a0, uint32_t a1, uint32_t a2, uint32_t a3) { return badd2(badd2(badd2(a3, a2), a1), a0); };
      const uint4* r = p[u & 1];
      const uint32_t m = ~ck & 1u;
      stg128(yp + u * 256, (sum(r[0].x, r[1].x, r[2].x, r[3].x) & ~m) | (ep & m), sum(r[0].y, r[1].y, r[2].y, r[3].y), sum(r[0].z, r[1].z, r[2].z, r[3].z), sum(r[0].w, r[1].w, r[2].w, r[3].w));
    };
    ld(0); ld(1); st(0);
    if (third) ld(2);
    st(1);
    if (third) st(2);
  };
  if (warp == 8) {
    if (lane == 0) {
      TS(0);
      mbar_init(BAR(B_F0), 1); mbar_init(BAR(B_F1), 1);
    }
    __syncwarp();
    ONE(mbar_expect(BAR(B_F0), G1_TX - 8192);
        tma2d(sb, &M.q0, 0, rb * 128, BAR(B_F0));
        tma3d(sb + 16384, &M.w1, 0, 0, 3 * j, BAR(B_F0));
        tma2d(sb + 40960, &M.w1x, 1536 + 24 * j, 0, BAR(B_F0));
        mbar_expect(BAR(B_F1), 8192);
        tma2d(sb + 8192, &M.q0, 0, rb * 128 + 64, BAR(B_F1));
        for (int s = 1; s < 4; s++) mbar_init(BAR(B_F1 + s), 1));
    bar_arrive(NB_INIT, 384);
    ONE(for (int s = 1; s <= PRO; s++) g1_load(s));
  } else {
    const int blk = warp - (warp > 8);
    ONE(for (int i = 0; i < 8; i++) mbar_init(BAR(8 * blk + i), blk < 2 ? 8 : (blk < 5 ? 4 : 1));
        asm volatile("fence.mbarrier_init.release.cluster;" ::: "memory"));
    bar_sync(NB_INIT, 384);
  }
  if ((sb & 0xFFFFFFu) != sc) { if (warp == 8) { mbar_wait(BAR(B_F0), 0); for (int s = 0; s <= PRO; s++) mbar_wait(BAR(B_F1 + s), 0); } return; }

  if (warp >= 8) {
    asm volatile("setmaxnreg.dec.sync.aligned.u32 " REG_AUX ";");
    auto table = [&](int c, int aw) {
      const uint32_t kb = sb + cv_t(c);
      const uint32_t dd = lds32(sb + M_AUX + aw * 32 + c * 4);
      if (lane < 2) sts128(kb + lane * (KT_E - 16), 0u, 0u, 0u, 0u);
      uint4 r[8];
#pragma unroll
      for (int it = 0; it < 8; it++) r[it] = lds128(kb + KT_E + (it * 32 + lane) * 16);
      if (lane == 0) { r[0].x = __byte_perm(badd2(r[0].x, dd), r[0].x, 0x7610); sts32(kb + KT_E, r[0].x); }
#pragma unroll
      for (int it = 0; it < 8; it++) {
        const uint32_t pv = __shfl_sync(0xffffffffu, lane == 31 ? (it ? r[it ? it - 1 : 0].w : 0u) : r[it].w, lane - 1);
        sts128(kb + KT_O + (it * 32 + lane) * 16, __byte_perm(pv, r[it].x, 0x5432), __byte_perm(r[it].x, r[it].y, 0x5432),
               __byte_perm(r[it].y, r[it].z, 0x5432), __byte_perm(r[it].z, r[it].w, 0x5432));
      }
      __syncwarp();
      if (lane == 0) mbar_arrive(BAR(B_KT + c));
    };
    const int aw = warp - 9, at = tid - 288;
    auto x_load = [&](int c) { mbar_expect(BAR(B_XL + c), 4096); bulk_g2s(sb + cv_x(c) + XD, P.kvT + (size_t)(128 * c + b) * SL, 4096, BAR(B_XL + c)); };
    auto x_pad = [&](int c0, int c1) {
      if (lane < 17) for (int c = c0; c < c1; c++) sts128(sb + cv_x(c) + lane * 16, 0u, 0u, 0u, 0u);
      fence_async_smem();
      __syncwarp();
    };
    if (warp == 8) {
      if (PRO < 3) ONE(for (int s = PRO + 1; s < 4; s++) g1_load(s));
      bar_sync(NB_INIT2, 64);
      unsigned ep;
#pragma unroll P1_UNROLL
      for (int kc = 4; kc < 10; kc++) {
        if (kc == 9) {
          bar_sync(NB_INIT3, 64);
          ep = lds32(sb + M_AUX + 20);
          mbar_wait(BAR(B_RED), 0);
          float2 u[8];
#pragma unroll
          for (int i = 0; i < 8; i++) u[i] = lds64f(sb + M_RED0 + (lane & 15) * 128 + ((i + lane) & 7) * 16 + (lane >> 4) * 8);
          const float c = bf_round(u[0].x * (1.f / 40)), cc = 40.f * c * c;
          float s1 = 0.f, s2 = 0.f;
#pragma unroll
          for (int i = 0; i < 8; i++) { s1 += fmaf(-40.f, c, u[i].x); s2 += fmaf(-2.f * c, u[i].x, u[i].y) + cc; }
          const float dm = s1 * (1.f / 320);
          st_relaxed64(&P.stat[dir * SL + rb * 128 + ri * 32 + lane], tagged(c + dm, ep), tagged(fmaf(-dm, s1, s2), ep));
          ONE(mbar_arrive(BAR(B_RD)));
        }
        mbar_wait(BAR(B_E1 + (kc & 3)), (kc >> 3) & 1);
        ONE(g1_load(kc));
        const int r = kc == (KV_MAP & 15) ? 0 : (kc == ((KV_MAP >> 4) & 15) ? 1 : (kc == (KV_MAP >> 8) ? 2 : -1));
        if (r >= 0) ONE(kv_load(r, 0); kv_load(r, 1));
        if (kc == PF_RAW) ONE(prefetch_l2(P.ssm_k + (size_t)b * SL, 4096));
      }
      ONE(prefetch_map(&M.hs); prefetch_map(&M.hx); prefetch_map(&M.ha); prefetch_map(&M.w2); prefetch_map(&M.w2x));
      {
        mbar_wait(BAR(CS_WAIT ? B_FR : B_F1), 0);
        uint32_t x[16], n = 0;
#pragma unroll 1
        while (true) {
          uint32_t bad = 0;
#pragma unroll
          for (int i = 0; i < 4; i++) {
            const uint4 v = ld_relaxed128(P.stat + (i >> 1) * SL + rb * 128 + lane * 4 + (i & 1) * 2);
            x[4 * i] = v.x; x[4 * i + 1] = v.y; x[4 * i + 2] = v.z; x[4 * i + 3] = v.w;
          }
#pragma unroll
          for (int i = 0; i < 16; i++) { x[i] ^= ep & 15u; bad |= x[i]; }
          if (__all_sync(0xffffffffu, (bad & 15u) == 0) || spin_guard(n, 0x132)) break;
          RETRY(9);
        }
        uint32_t st[4];
#pragma unroll
        for (int i = 0; i < 4; i++) {
          const float ma = __uint_as_float(x[2 * i]), mb = __uint_as_float(x[8 + 2 * i]), dl = ma - mb;
          const float m2 = fmaf(dl * dl, 160.f, __uint_as_float(x[1 + 2 * i]) + __uint_as_float(x[9 + 2 * i]));
          const float vb = bf_round(fmaxf(m2, 0.f) * (1.f / DM));
          st[i] = pack_bf16(0.5f * (ma + mb), sqrt_fast(bf_round(vb + 1e-5f)));
        }
        sts128(sb + M_STAT + lane * 16, st[0], st[1], st[2], st[3]);
        __syncwarp();
        if (lane < 2) mbar_arrive(BAR(B_BX));
      }
    } else {
      if (aw == 0) bar_arrive(NB_INIT2, 64);
      if (aw == 2) ONE(mbar_expect(BAR(B_XD), XD_N * 2048); mbar_expect(BAR(B_XD + 1), (XD_M - XD_N) * 2048); mbar_expect(BAR(B_XD + 2), (10 - XD_M) * 2048));
      if (aw == 1) mbar_wait(BAR(B_F0), 0);
      if (aw == 1) ONE(prefetch_map(&M.kvs); prefetch_map(&M.k); prefetch_map(&M.v); mbar_expect(BAR(B_SK), 2560);
                       for (int r = 0; r < 5; r++) bulk_g2s(sb + M_SK + r * 512, P.shift_k + (128 * r + 64 * (b & 1)) * 4, 512, BAR(B_SK)));
      const uint32_t dv0 = ld_relaxed32(lane < 5 ? static_cast<const void*>(P.ssm_D + 128 * lane + (b & ~1)) : &P.launch[b * 8]);
      const uint32_t b2v = ldg32(reinterpret_cast<const uint32_t*>(P.b2 + nt * 160) + ((gmap >> (4 * (min(at, 79) >> 4))) & 7) * 16 + (at & 15));
      const int l27 = min(lane, 26), col = l27 < 24 ? 192 * j + 8 * l27 : 1536 + 24 * j + 8 * (l27 - 24);
      uint4 bb;
      if (aw == 2) bb = ldg128(P.b1 + col);
      if (lane < 4) sts32(sb + M_ZERO + lane * 4, 0u);
      if (lane < 8) sts32(sb + M_AUX + aw * 32 + lane * 4, lane >= 5 ? dv0 + 1 : ((b & 1) ? dv0 >> 16 : dv0 & 0xFFFFu));
      if (at < 80) sts64f(sb + M_B2 + at * 8, 0.5f * bf_lo(b2v), 0.5f * bf_hi(b2v));
      __syncwarp();
      if (aw == 0) bar_arrive(NB_INIT3, 64);
      if (aw == 2) {
        const unsigned ep = lds32(sb + M_AUX + 64 + 20);
        const uint32_t ba = sb + M_BX + (l27 >> 2) * 512 + ((l27 & 3) << 4);
        mbar_wait(BAR(B_RED1), 0);
        const uint32_t tg = ep & 15u;
        float c0 = 0.f, c1 = 0.f;
#pragma unroll
        for (int i = 0; i < 16; i += 2) { c0 += __uint_as_float(lds32(sb + M_RED1 + i * 128 + lane * 4)); c1 += __uint_as_float(lds32(sb + M_RED1 + i * 128 + 128 + lane * 4)); }
        st_relaxed32(&P.cs[(dir * 8 + j) * 256 + ci * 32 + lane], tagged(c0 + c1, ep));
        if (lane == 0) TS(30);
        mbar_wait(BAR(B_RD), 0);
        sts128((ba + 128) ^ 16, 0u, 0u, 0u, 0u); sts128((ba + 192) ^ 16, bb.x, bb.y, bb.z, bb.w);
#pragma unroll
        for (int i = 4; i < 8; i++) sts128((ba + i * 64) ^ ((i >> 1) << 4), 0u, 0u, 0u, 0u);
        mbar_wait(BAR(CS_WAIT ? B_FR : B_F1), 0);
        auto raw_load = [&]() {
          if (!CS_WAIT) mbar_wait(BAR(B_FR), 0);
          ONE(mbar_expect(BAR(B_KRAW), KRAW_N * 4096); mbar_expect(BAR(B_KRAW + 1), (5 - KRAW_N) * 4096);
              for (int c = 0; c < 5; c++) bulk_g2s(sb + cv_t(c) + KT_E, P.ssm_k + (size_t)(128 * c + b) * SL, 4096, BAR(B_KRAW + (c >= KRAW_N))));
        };
        uint32_t x[16], n = 0;
#pragma unroll 1
        while (true) {
#pragma unroll
          for (int i = 0; i < 4; i++) {
            const uint4 v = ld_relaxed128(P.cs + ((i >> 1) * 8 + j) * 256 + l27 * 8 + (i & 1) * 4);
            x[4 * i] = v.x; x[4 * i + 1] = v.y; x[4 * i + 2] = v.z; x[4 * i + 3] = v.w;
          }
          if (!RAW_LATE && n == 0) raw_load();
          uint32_t bad = 0;
#pragma unroll
          for (int i = 0; i < 16; i++) { x[i] ^= tg; bad |= x[i]; }
          if (__all_sync(0xffffffffu, (bad & 15u) == 0) || spin_guard(n, 0x131)) break;
          RETRY(8);
        }
        if (RAW_LATE) raw_load();
        uint32_t hi[4], lo[4];
#pragma unroll
        for (int i = 0; i < 4; i++) {
          const float x0 = __uint_as_float(x[2 * i]) + __uint_as_float(x[8 + 2 * i]), x1 = __uint_as_float(x[2 * i + 1]) + __uint_as_float(x[9 + 2 * i]);
          hi[i] = pack_bf16(x0, x1); lo[i] = pack_bf16(x0 - bf_lo(hi[i]), x1 - bf_hi(hi[i]));
        }
        sts128(ba, hi[0], hi[1], hi[2], hi[3]); sts128(ba + 64, lo[0], lo[1], lo[2], lo[3]);
        fence_async_smem();
        __syncwarp();
        if (lane < 2) mbar_arrive(BAR(B_BX));
        if (lane == 0) TS(54);
      }
      if (aw < 2) {
        auto done = [&](int r) {
          bulk_wait_read();
          ONE(kv_load(r + 3, aw); TSKV);
        };
        const uint32_t par = lds32(sb + M_AUX + aw * 32 + 20) & 1u;
        bool pend = false;
        mbar_wait(BAR(B_SK), 0);
#pragma unroll 1
        for (int r = 0; r < 5; r++) {
          const int c0 = 128 * r + 64 * (b & 1);
          const uint32_t buf = sb + KVS + (r < 3 ? r : r - 3) * KV_BUF, stg = buf + aw * 2048, vb = stg + lane * 4, kb = buf + 4096 + aw * 2432 + lane * 4;
          const uint4 sk = lds128(sb + M_SK + r * 512 + lane * 16);
          const uint32_t w0 = __byte_perm(sk.x, sk.z, 0x5410), w1 = __byte_perm(sk.x, sk.z, 0x7632);
          const uint32_t w2 = __byte_perm(sk.y, sk.w, 0x5410), w3 = __byte_perm(sk.y, sk.w, 0x7632);
          mbar_wait(BAR((aw ? B_KIN1 : B_KIN) + r), 0);
          if (at == 0 && r == 0) TS(56);
          uint32_t kk[19], o[16];
#pragma unroll
          for (int i = 0; i < 19; i++) { kk[i] = lds32(kb + i * 128); if (i >= 3) o[i - 3] = lds32(vb + (i - 3) * 128); }
#pragma unroll
          for (int i = 0; i < 16; i++) o[i] = bmul2(bfma2(kk[i + 3], w0, bfma2(kk[i + 2], w1, bfma2(kk[i + 1], w2, bmul2(kk[i], w3)))), o[i]);
          __syncwarp();
          const uint32_t a0 = stg + lane * 64 + ((lane & 6) << 3);
          const uint32_t s0 = (lane & 4) ? 0x7632 : 0x5410, s1 = s0 ^ 0x2222;
#pragma unroll
          for (int hh = 0; hh < 2; hh++) {
            const uint32_t* u = o + 8 * hh;
            const uint32_t a = a0 ^ (hh << 4);
            auto nz = [&](uint32_t x) { return hh ? x : (x & ~1u) | par; };
            sts128(a, nz(__byte_perm(u[1], u[0], s0)), __byte_perm(u[3], u[2], s0), __byte_perm(u[5], u[4], s0), __byte_perm(u[7], u[6], s0));
            sts128(a ^ 32, nz(__byte_perm(u[1], u[0], s1)), __byte_perm(u[3], u[2], s1), __byte_perm(u[5], u[4], s1), __byte_perm(u[7], u[6], s1));
          }
          if (pend) done(r - 1);
          fence_async_smem();
          __syncwarp();
          ONE(tma2d_st(&M.kvs, 32 * (b >> 1) + 16 * aw, c0, stg); bulk_commit());
          pend = r < 2 && mbar_test(BAR((aw ? B_KIN1 : B_KIN) + r + 1), 0);
          if (!pend && r < 2) done(r);
        }
      }
      if (aw == 2) {
        mbar_wait(BAR(B_FR + 1), 0);
        ONE(x_load(0));
        x_pad(0, 4);
      }
    }
#pragma unroll 1
    for (uint32_t t = (TB_MAP >> (8 * (warp - 8))) & 255; t & 15; t >>= 4) {
      const int c = (t & 15) - 1;
      mbar_wait(BAR(B_KRAW + (c >= KRAW_N)), 0);
      if (lane == 0 && c == 1) TS(35);
      table(c, max(aw, 0));
      if (lane == 0 && c == 2) TS(55);
    }
    const unsigned ep = lds32(sb + M_AUX + max(aw, 0) * 32 + 20);
    if (warp == 8) {
      const int hc = j * 192, hx = 1536 + j * 24;
#pragma unroll 1
      for (int n = 0; n < 32; n += 4) {
        const int i = (H_ORD >> n) & 7, hw = i >> 2, blk = i & 3;
        if (n == 4 * W2_PF) ONE(prefetch_l2(P.w2 + (size_t)b * (FF * DM / NCTA), FF * DM / NCTA * 2));
        mbar_wait(BAR(B_HB + i), 0);
        fence_async_smem();
        asm volatile("cp.async.bulk.wait_group %0;" ::"n"(H_FLY - 1) : "memory");
        ONE(tma2d_st(blk < 3 ? &M.hs : &M.hx, blk < 3 ? hc + blk * 64 : hx, rb * 128 + hw * 64, sb + hw * HST + blk * 8192); bulk_commit());
      }
      const int cf = (nt * 160 + (nt & 1) * 32) >> 6, ch = (nt >> 1) * 320 + 128;
      auto g2_k = [&](int kc) { return (kc < NSH ? kh * NSH + kc : NSH + kc) * 64; };
      auto g2_load_b = [&](int kc) {
        const int s = kc & 3;
        const uint32_t fb = BAR(B_F2 + s);
        mbar_expect(fb, kc >= NSH ? 8192 + 24576 : 16384 + 24576);
        tma3d(sb + g2_b(s), &M.w2, 0, g2_k(kc), cf, fb);
        tma2d(sb + g2_b(s) + 16384, &M.w2x, ch, g2_k(kc), fb);
      };
      auto g2_load_a = [&](int kc) {
        const int s = kc & 3, o = kc >= NSH ? kh : 0;
        tma2d(sb + g2_a(s) + o * 8192, kc >= NSH ? &M.hs : &M.ha, g2_k(kc), rb * 128 + o * 64, BAR(B_F2 + s));
      };
      bulk_wait_all();
      ONE(g2_load_b(0); g2_load_b(1));
      fence_release();
      ONE(signal_cnt(P.cnt + rb * 32); TS(37));
      wait_cnt(P.cnt + rb * 32, 8 * ep);
      ONE(TS(39); g2_load_a(0); g2_load_a(1); prefetch_map(&M.qf); prefetch_map(&M.y); prefetch_map(&M.out));
      mbar_wait(BAR(B_KD), 0);
      ONE(g2_load_b(3));
      mbar_wait(BAR(B_TD + 1), 0);
      fence_async_smem();
      ONE(g2_load_b(2); g2_load_a(2));
      mbar_wait(BAR(B_SD + 3), 0);
      ONE(mbar_expect(BAR(B_FINQ), 20480);
          for (int i = 0; i < 5; i++) tma2d(sb + FIN_Q + i * 4096, &M.qf, nt * 160 + ((gmap >> (4 * i)) & 7) * 32, rb * 128 + kh * 64, BAR(B_FINQ)));
      mbar_wait(BAR(B_RF + 2), 0);
      ONE(g2_load_a(3); TS(38));
#pragma unroll 1
      for (int kc = 4; kc < NST; kc++) {
        mbar_wait(BAR(B_E2 + (kc & 3)), ((kc >> 2) - 1) & 1);
                ONE(g2_load_a(kc); g2_load_b(kc); if (kc >= Y_KC && kc < Y_KC + 3) mbar_arrive(BAR(B_YSLOT + kc - Y_KC)));
      }
      if (lane == 0) P.launch[b * 8] = ep;
#pragma unroll 1
      for (int i = 0; i < 5; i++) {
        const int gi = (gmap >> (4 * i)) & 7;
        mbar_wait(BAR(B_OUT + i), 0);
        fence_async_smem();
        ONE(tma2d_st(&M.out, nt * 160 + gi * 32, rb * 128 + kh * 64, sb + FIN_Q + i * 4096));
      }
      ONE(bulk_commit());
      bulk_wait_read();
    } else {
      if (aw < 2) { bulk_wait_read(); __syncwarp(); if (lane < 2) mbar_arrive(BAR(B_KD)); if (at == 0) TS(34); }
      if (aw == 2) {
#pragma unroll 1
        for (int c = 0, n = 0; c < 5;) {
          if (n == 0 && c < 4) {
            mbar_wait(BAR((X_TRIG >> (8 * c)) & 255), 0);
            if (c == 3) { mbar_wait(BAR(B_KD), 0); x_pad(4, 5); }
          }
          if (n || c < 4) ONE(x_load(n ? c : c + 1));
          mbar_wait(BAR(B_XL + c), n & 1);
          const uint32_t a = sb + cv_x(c) + XD + lane * 32;
          const uint32_t v = ((lds32(a) ^ ep) | (lds32(a + 1024) ^ ep) | (lds32(a + 2048) ^ ep) | (lds32(a + 3072) ^ ep)) & 1u;
          if (__all_sync(0xffffffffu, v == 0) || n > 100000) {
            ONE(mbar_arrive(BAR(B_XF + c)); if (c == 0) TS(36); if (c >= 3) TS(28 + c));
            c++; n = 0;
          } else {
            n++;
            RETRY(c);
          }
        }
      }
      if (RED_GATE) mbar_wait(BAR(RED_GATE == 1 ? B_TD + 1 : B_SD + RED_GATE - 1), 0);
#pragma unroll 1
      for (int c = 0; c < 5; c++) {
        mbar_wait(BAR(B_SD + c), 0);
        conv_sum(c, aw * 96 + lane, aw < 2, ep);
        __syncwarp();
        if (c < 3 && lane < 3 - (aw >> 1)) mbar_arrive(BAR(B_RF + c));
        if (at == 0) TS(59 + c);
      }
      bar_sync(NB_AUX, 96);
      if (aw == 0) ONE(mbar_arrive_remote(mapa(BAR(B_XR), kh ^ 1)); TS(3));
      auto ytab = [](int a) { return (uint32_t)(fin_y(3 * a) >> 10 | fin_y(3 * a + 1) >> 10 << 8 | fin_y(3 * a + 2) >> 10 << 16 | fin_y(a == 2 ? 9 : 3 * a) >> 10 << 24); };
      const uint32_t yt = aw == 0 ? ytab(0) : (aw == 1 ? ytab(1) : ytab(2));
      mbar_wait(BAR(B_YSLOT + ((Y_MAP >> (4 * aw)) & 3)), 0);
#pragma unroll 1
      for (int n = 0;; n++) {
        ONE(mbar_expect(BAR(B_YL + aw), aw == 2 ? 8192 : 6144));
#pragma unroll 1
        for (int i = 0; i < (aw == 2 ? 4 : 3); i++) {
          const int np = 3 * aw + i;
          ONE(tma2d(sb + (((yt >> (8 * i)) & 255) << 10), &M.y, rb * 128 + kh * 64, nt * 160 + ((gmap >> (4 * (np >> 1))) & 7) * 32 + (np & 1) * 16, BAR(B_YL + aw)));
        }
        mbar_wait(BAR(B_YL + aw), n & 1);
        uint32_t bad = 0;
#pragma unroll
        for (int i = 0; i < 4; i++) {
          const uint32_t a = sb + (((yt >> (8 * i)) & 255) << 10) + (lane >> 2) * 128 + ((((lane & 3) * 2) ^ (lane >> 2)) << 4);
          bad |= (lds32(a) ^ ep) | (lds32(a + 1024) ^ ep);
        }
        if (__all_sync(0xffffffffu, (bad & 1u) == 0) || n > 100000) break;
        RETRY(5 + aw);
        if (lane == 0) TS(33);
      }
      if (lane <= (aw >> 1)) mbar_arrive(BAR(B_FINY));
      if (at == 64) TS(40);
    }
  } else {
    const int wg = warp >> 2, w = warp & 3, g = lane >> 2, q = lane & 3;
    constexpr bool elect = false;
    uint32_t ca[64];
    const uint32_t ab0 = sb + ((g & 1) ? KT_E : KT_O) + (8 * w + 4 + (g >> 1) - q) * 4;
    auto conv_lda = [&](uint32_t ab, int k0, int k1) {
#pragma unroll
      for (int ks = 15; ks >= 0; ks--) {
        if (ks >= k0 && ks < k1) {
          ca[4 * ks + 0] = lds32(ab + ks * 256);
          ca[4 * ks + 1] = lds32(ab + ks * 256 + 128);
          ca[4 * ks + 2] = lds32(ab + ks * 256 - 16);
          ca[4 * ks + 3] = lds32(ab + ks * 256 + 112);
        }
      }
    };
    {
      float d[108];
      auto g1_release = [&](int kc) { if (lane == 0) mbar_arrive(BAR(kc < 6 ? B_E1 + (kc & 3) : B_FR + kc - 6)); };
      auto g1_wait = [&](int kc) { mbar_wait(BAR(B_F1 + (kc & 3)), (kc >> 2) & 1); };
      auto g1_issue = [&](int kc) {
        const int s = kc & 3;
        if (tid == 0) TS(8 + kc);
        const uint32_t st = sc + s * G1_STAGE;
        const uint64_t da = mkdesc(st + wg * 8192, 16, 1024, 1), db = mkdesc(st + 16384, 8192, 1024, 1);
        wg_fence();
#pragma unroll
        for (int k = 0; k < 4; k++) {
          wg_ss_216(d, da + k * 2, db + k * 128, (kc | k) != 0);
          if (k == REL_K || k == 3) wg_commit();
          if (k == REL_K) { wg_wait<1>(); if (kc > 0) g1_release(kc - 1); }
        }
      };
      const int t7 = tid & 127, wr = ((t7 >> 3) & 1) * 4 + (t7 >> 4) * 8, wc = 4 * min(ci, 6) + ((t7 >> 1) & 3);
      const uint32_t sa0 = sb + (wg ? 16384 + (wc >> 3) * 8192 + wr * 128 + (((wc ^ wr) & 7) << 4) + (t7 & 1) * 8 : ri * 4096 + t7 * 16);
      float t1 = 0.f, t2 = 0.f, t3 = 0.f, t4 = 0.f;
      auto piece = [&](int i) {
        const uint32_t so = (i & 3) * G1_STAGE;
        if (wg == 0) {
          const uint4 x = lds128(sa0 + so), y = lds128(sa0 + so + 2048);
          const uint32_t xx[4] = {x.x, x.y, x.z, x.w}, yy[4] = {y.x, y.y, y.z, y.w};
#pragma unroll
          for (int e = 0; e < 4; e++) {
            const float u = bf_lo(xx[e]), v = bf_hi(xx[e]), r = bf_lo(yy[e]), z = bf_hi(yy[e]);
            t1 += u; t2 = fmaf(u, u, t2); t3 += r; t4 = fmaf(r, r, t4);
            t1 += v; t2 = fmaf(v, v, t2); t3 += z; t4 = fmaf(z, z, t4);
          }
        } else {
          float2 xx[4];
#pragma unroll
          for (int e = 0; e < 4; e++) xx[e] = lds64f((sa0 ^ (e * 144)) + so);
#pragma unroll
          for (int e = 0; e < 4; e++) {
            const uint32_t u = __float_as_uint(xx[e].x), v = __float_as_uint(xx[e].y);
            t1 += bf_lo(u); t2 += bf_hi(u); t3 += bf_lo(v); t4 += bf_hi(v);
          }
        }
      };
      const int mi = lane >> 3, row = w * 16 + (mi & 1) * 8 + (lane & 7);
      uint32_t ha[4], hx = sb + wg * HST + 24576 + row * 48 + (mi >> 1) * 16, hb = BAR(B_HB + wg * 4), aw0 = ab0 + cv_t(wg);
#pragma unroll
      for (int i = 0; i < 4; i++) ha[i] = sb + wg * HST + row * 128 + (((2 * i + (mi >> 1)) ^ (row & 7)) << 4);
      keep(ha[0]); keep(ha[1]); keep(ha[2]); keep(ha[3]); keep(hx); keep(hb); keep(aw0);
      if (wg == 1) { g1_wait(0); bar_sync(NB_LEAD, 256); }
      mbar_wait(BAR(B_F0), 0);
#pragma unroll G1_UNROLL
      for (int kc = 0; kc < 6; kc++) {
        g1_issue(kc);
        if (kc == 0 && wg == 0) bar_arrive(NB_LEAD, 256);
        if (kc >= 2 || kc == dir) { g1_wait(kc); piece(kc); }
        if (kc < 5) g1_wait(kc + 1);
      }
      sts128(sb + (wg ? M_RED1 : M_RED0) + t7 * 16, __float_as_uint(t1), __float_as_uint(t2), __float_as_uint(t3), __float_as_uint(t4));
      __syncwarp();
      if (lane == 0) mbar_arrive(BAR(wg ? B_RED1 : B_RED));
      asm volatile("setmaxnreg.inc.sync.aligned.u32 " REG_CON ";");
#pragma unroll G1_UNROLL
      for (int kc = 6; kc < 10; kc++) {
        g1_wait(kc);
        if (kc == 9 && wg == 1) mbar_wait(BAR(B_LNI), 0);
        g1_issue(kc);
      }
      uint2 s0, s1;
      {
        mbar_wait(BAR(B_BX), 0);
        s0.x = lds32(sb + M_STAT + (wg * 64 + w * 16 + g) * 4); s1.x = lds32(sb + M_STAT + (wg * 64 + w * 16 + g + 8) * 4);
        if (tid == 0) TS(46);
        const uint32_t f0 = q == 0 ? ((s0.x & 0xFFFFu) * 0x10001u) ^ 0x80008000u : (q == 1 ? s0.x ^ 0x8000u : 0u);
        const uint32_t f1 = q == 0 ? ((s1.x & 0xFFFFu) * 0x10001u) ^ 0x80008000u : (q == 1 ? s1.x ^ 0x8000u : 0u);
        wg_fence();
        wg_rs_216(d, f0, f1, 0u, 0u, mkdesc(sc + M_BX, 512, 0, 2));
        wg_commit();
        if (wg == 0 && lane == 0) mbar_arrive(BAR(B_LNI));
      }
      wg_wait<1>();
      if (lane == 0) mbar_arrive(BAR(B_FR + 3));
      const float r0 = rcp_fast(bf_hi(s0.x)), r1 = rcp_fast(bf_hi(s1.x));
      constexpr float C1 = 0.7978845608028654f, C2 = 0.7978845608028654f * 0.044715f;
      const float ga0 = C1 * r0, gb0 = C2 * r0 * r0 * r0, ga1 = C1 * r1, gb1 = C2 * r1 * r1 * r1;
      if (wg == 0) mbar_wait(BAR(B_FR + 2), 0);
      wg_wait<0>();
      if (elect) TS(1 + 47 * wg);
      if (wg == 1) bar_sync(NB_GELU, 256);
      sched_fence(sb);
      float u[2][8];
#pragma unroll
      for (int st = -1; st < 15; st++) {
        const int nb = 2 * (st - 1);
        if (st >= 1) {
          uint32_t p[4];
#pragma unroll
          for (int e = 0; e < (nb < 26 ? 4 : 2); e++) {
            const float x = d[4 * nb + 2 * e], y = d[4 * nb + 2 * e + 1];
            p[e] = pack_bf16(fmaf(x, u[(st - 1) & 1][2 * e], x), fmaf(y, u[(st - 1) & 1][2 * e + 1], y));
          }
          if (nb < 24) stsm4(ha[(nb >> 1) & 3] + (nb >> 3) * 8192, p[0], p[1], p[2], p[3]);
          else if (nb == 24) stsm4(hx, p[0], p[1], p[2], p[3]);
          else stsm2(hx + 32, p[0], p[1]);
          if ((nb & 7) == 6 || nb == 26) {
            __syncwarp();
            if (lane == 0) mbar_arrive(hb + 8 * (nb >> 3));
          }
        }
        if (st >= 0 && st < 14) {
#pragma unroll
          for (int i = 0; i < (st < 13 ? 8 : 4); i++) u[st & 1][i] = tanh_fast(u[st & 1][i]);
        }
        if (st + 1 < 14) {
#pragma unroll
          for (int i = 0; i < (st + 1 < 13 ? 8 : 4); i++) {
            const float x = d[8 * (st + 1) + i];
            u[(st + 1) & 1][i] = x * fmaf(x * ((i & 2) ? gb1 : gb0), x, (i & 2) ? ga1 : ga0);
          }
        }
        constexpr int S0 = A_NB0 / 2, NK = CV_OWN ? 16 - CV_RELOADED : 16;
        if (st >= S0 && st < 14) conv_lda(aw0, 16 - (st + 1 - S0) * NK / (14 - S0), 16 - (st - S0) * NK / (14 - S0));
        if (2 * st == GELU_NB && wg == 0) bar_arrive(NB_GELU, 256);
        if (st + 1 == S0) mbar_wait(BAR(B_KT + wg), 0); else if (st < 14 && (st + 1) % SCH == 0) sched_fence(sb);
      }
      if (elect) TS(2 + 47 * wg);
    }
#pragma unroll 1
    for (int c = wg; c < 5; c += 2) {
      float d[128];
      mbar_wait(BAR(B_XF + c), 0);
      if (c < 3) mbar_wait(BAR(B_KT + c + 2), 0);
      const uint64_t db = mkdesc(sc + cv_x(c), 16, 128, 0);
      if (c > 0) { if (wg) bar_sync(NB_TURN + 1, 256); else bar_sync(NB_TURN, 256); }
      wg_fence();
      auto hand = [&]() { if (wg) bar_arrive(NB_TURN, 256); else if (c < 4 || !HAND4) bar_arrive(NB_TURN + 1, 256); };
      const uint32_t ao = ab0 + cv_t(c);
      if (c < 3) conv_chain_1(d, ca, db, ao, ao + 2 * KT_CH, hand, []() {});
      else conv_chain_0(d, ca, db, ao, 0, hand, [&]() { if (lane == 0) mbar_arrive(BAR(B_TD + 1)); });
      if (c == 4 && HAND4) bar_arrive(NB_TURN + 1, 256);
      mbar_wait(BAR(c >= 3 ? B_RF + c - 3 : B_FR + 3), 0);
      wg_wait<0>();
      if (elect) TS(41 + c);
      if (c < 3 && !CV_OWN) conv_lda(ao + 2 * KT_CH, 0, CV_RELOADED);
      const uint32_t wa = sb + cv_p(c) + w * 4096 + lane * 16;
#pragma unroll
      for (int n4 = 0; n4 < 32; n4 += 4) {
        uint32_t p[4];
#pragma unroll
        for (int e = 0; e < 4; e++) {
          const int nb = n4 + e;
          float x = d[4 * nb], y = d[4 * nb + 1];
          if (nb > 0) { x += d[4 * nb - 2]; y += d[4 * nb - 1]; }
          p[e] = pack_bf16(x, y);
        }
        stsm4t(wa + n4 * 128, p[0], p[1], p[2], p[3]);
      }
      __syncwarp();
      if (lane == 0) mbar_arrive(BAR(B_SD + c));
    }
    if (elect) TS(51 + wg);
    {
      float d[80];
      const uint32_t aoff = (wg ^ kh) * 8192;
      const uint64_t boff = (uint64_t)(nt & 1) << 51;
      const uint32_t s0 = lds32(sb + M_STAT + ((wg ^ kh) * 64 + w * 16 + g) * 4), s1 = lds32(sb + M_STAT + ((wg ^ kh) * 64 + w * 16 + g + 8) * 4);
      auto g2_release = [&](int kc) { if (lane == 0) mbar_arrive(BAR(B_E2 + (kc & 3))); };
      auto g2_mma_w = [&](int kc, int first, bool rel, auto side) {
        const int s = kc & 3;
        mbar_wait(BAR(B_F2 + s), (kc >> 2) & 1);
        const uint64_t da = mkdesc(sc + g2_a(s) + aoff, 16, 1024, 1), db = mkdesc(sc + g2_b(s), 8192, 1024, 1) | boff;
        wg_fence();
#pragma unroll
        for (int k = 0; k < 4; k++) {
          wg_ss_160(d, da + k * 2, db + k * 128, k ? 1 : first);
          if ((k == REL_K && rel) || k == 3) wg_commit();
          if (k == REL_K && rel) { wg_wait<1>(); g2_release(kc - 1); }
          side(k);
        }
      };
      auto g2_mma = [&](int kc, int first, bool rel) { g2_mma_w(kc, first, rel, [](int) {}); };
      sched_fence(sb);
      if (wg == 1) bar_sync(NB_TURN + 1, 256);
      g2_mma(0, 0, false);
      if (wg == 0) bar_arrive(NB_LEAD, 256);
#pragma unroll
      for (int kc = 1; kc < XP_KC; kc++) {
        if (tid == 0) TS(17 + kc);
        if (kc == LEAD_KC && wg == 1) bar_sync(NB_LEAD, 256);
        g2_mma(kc, 1, true);
      }
      if (wg == 1) {
        float bi[40];
#pragma unroll
        for (int nb = 0; nb < 20; nb++) { const float2 v = lds64f(sb + M_B2 + nb * 32 + q * 8); bi[2 * nb] = v.x; bi[2 * nb + 1] = v.y; }
        const float c0 = 0.25f * rcp_fast(bf_hi(s0)), c1 = 0.25f * rcp_fast(bf_hi(s1));
#pragma unroll
        for (int kc = XP_KC; kc < NSH; kc++) {
          g2_mma(kc, 1, kc < NST - 3);
          if (kc == END_KC) bar_arrive(NB_END, 256);
        }
        mbar_wait(BAR(B_XR), 0);
        wg_wait<0>();
#pragma unroll
        for (int kc = NSH - 1; kc < NST - 4; kc++) g2_release(kc);
        if (elect) TS(53);
        const uint32_t ra = mapa(sb, kh ^ 1), rbar = ra + M_BAR + 8 * B_XD, dst = ra + (tid & 127) * 16;
#pragma unroll
        for (int i = 0; i < 10; i++) {
          const float *dd = d + 8 * i, *bb = bi + 4 * i;
          st_async128(dst + (i < 5 ? P0 + i * 2048 : P1 + (i - 5) * 2048), pack_bf16(fmaf(dd[0], c0, bb[0]), fmaf(dd[1], c0, bb[1])), pack_bf16(fmaf(dd[2], c1, bb[0]), fmaf(dd[3], c1, bb[1])),
                      pack_bf16(fmaf(dd[4], c0, bb[2]), fmaf(dd[5], c0, bb[3])), pack_bf16(fmaf(dd[6], c1, bb[2]), fmaf(dd[7], c1, bb[3])), rbar + 8 * ((i >= XD_N) + (i >= XD_M)));
          sched_fence(sb);
        }
        if (elect) TS(7);
      } else {
        const int mi = lane >> 3, row = (mi & 1) * 8 + (lane & 7);
        const uint32_t qa = sb + FIN_Q + (w * 16 + row) * 64 + (((mi >> 1) ^ ((row >> 1) & 3)) << 4), qb = qa ^ 32;
        auto q_addr = [&](int np) { return ((np & 1) ? qb : qa) + (np >> 1) * 4096; };
        uint32_t sv[40], xq[40];
        const uint32_t m0 = (s0 & 0xFFFFu) * 0x10001u, m1 = (s1 & 0xFFFFu) * 0x10001u;
        float rs0 = rcp_fast(bf_hi(s0)), rs1 = rcp_fast(bf_hi(s1));
#pragma unroll
        for (int kc = XP_KC; kc < 10; kc++) {
          if (tid == 0) TS(17 + kc);
          g2_mma(kc, 1, true);
          if (kc >= XP_KC && XP_KC < 10) {
            mbar_wait(BAR(B_FINQ), 0);
#pragma unroll
            for (int np = 10 * (kc - XP_KC) / (XP_KC < 10 ? 10 - XP_KC : 1); np < 10 * (kc + 1 - XP_KC) / (XP_KC < 10 ? 10 - XP_KC : 1); np++) {
              ldsm4(q_addr(np), xq[4 * np], xq[4 * np + 1], xq[4 * np + 2], xq[4 * np + 3]);
#pragma unroll
              for (int e = 0; e < 4; e++) {
                const uint32_t dm = bsub2(xq[4 * np + e], (e & 1) ? m1 : m0);
                const float rs = (e & 1) ? rs1 : rs0;
                sv[4 * np + e] = pack_bf16(bf_lo(dm) * rs, bf_hi(dm) * rs);
              }
            }
          }
        }
        const uint32_t ya = sb + (mi >> 1) * 1024 + (lane & 7) * 128 + (((2 * w + (mi & 1)) ^ (lane & 7)) << 4);
        uint32_t y[3][4];
        auto y_step = [&](int i) {
          if (i < 0 || i >= 12) return;
          if (i >= 2) {
#pragma unroll
            for (int e = 0; e < 4; e++) asm volatile("mul.rn.bf16x2 %0, %0, %1;" : "+r"(sv[4 * (i - 2) + e]) : "r"(y[(i - 2) % 3][e]));
          }
          if (i < 10) ldsm4t(ya + fin_y(i), y[i % 3][0], y[i % 3][1], y[i % 3][2], y[i % 3][3]);
          if (YFENCE) sched_fence(sb);
        };
        rs0 *= 0.25f; rs1 *= 0.25f;
        if (tid == 0) TS(27);
#pragma unroll
        for (int kc = 9; kc < NST; kc++) {
          if (kc == YP_KC) mbar_wait(BAR(B_FINY), 0);
          if (kc > 9) g2_mma_w(kc, 1, kc < NST - 3 && kc != HOLD_KC + 1, [&](int k) { y_step(4 * (kc - YP_KC) + k); });
          if (kc == HOLD_KC) {
            if (kc < NST - 4) { wg_wait<0>(); g2_release(kc); }
            if (tid == 0) TS(28);
            bar_sync(NB_END, 256);
          }
        }
        if (tid == 0) TS(29);
#pragma unroll
        for (int i = 4 * (NST - YP_KC); i < 12; i++) y_step(i);
        if (tid == 0) TS(47);
        mbar_wait(BAR(B_XD), 0);
        if (tid == 0) TS(5);
        uint4 v[10];
        auto ld_v = [&](int n0, int n1) {
#pragma unroll
          for (int i = n0; i < n1; i++) v[i] = lds128(sb + tid * 16 + (i < 5 ? P0 + i * 2048 : P1 + (i - 5) * 2048));
        };
        ld_v(0, XD_N);
        wg_wait<0>();
        if (tid == 0) TS(4);
        float t[2][8];
#pragma unroll
        for (int st = -1; st < 11; st++) {
          if (st == XD_N - 3) { mbar_wait(BAR(B_XD + 1), 0); ld_v(XD_N, XD_M); }
          if (st == XD_M - 3) { mbar_wait(BAR(B_XD + 2), 0); ld_v(XD_M, 10); }
          if (st >= 1) {
            const int np = st - 1;
            uint32_t o[4];
#pragma unroll
            for (int e = 0; e < 4; e++) {
              const float h0 = d[8 * np + 2 * e], h1 = d[8 * np + 2 * e + 1];
              o[e] = bfma2(sv[4 * np + e], pack_bf16(fmaf(h0, t[np & 1][2 * e], h0), fmaf(h1, t[np & 1][2 * e + 1], h1)), xq[4 * np + e]);
            }
            stsm4(q_addr(np), o[0], o[1], o[2], o[3]);
            if (np & 1) {
              if (np == 9 && tid == 0) TS(50);
              __syncwarp();
              if (lane == 0) mbar_arrive(BAR(B_OUT + (np >> 1)));
            }
          }
          if (st >= 0 && st < 10) {
#pragma unroll
            for (int i = 0; i < 8; i++) t[st & 1][i] = tanh_fast(d[8 * st + i]);
          }
          if (st + 1 < 10) {
            const int np = st + 1;
            const uint32_t pw[4] = {v[np].x, v[np].y, v[np].z, v[np].w};
#pragma unroll
            for (int e = 0; e < 4; e++) {
              d[8 * np + 2 * e] = fmaf(d[8 * np + 2 * e], (e & 1) ? rs1 : rs0, bf_lo(pw[e]));
              d[8 * np + 2 * e + 1] = fmaf(d[8 * np + 2 * e + 1], (e & 1) ? rs1 : rs0, bf_hi(pw[e]));
            }
          }
          if (SCH2 && (st + 1) % (SCH2 ? SCH2 : 1) == 0) sched_fence(sb);
        }
      }
    }
  }
}

typedef CUresult (*EncFn)(CUtensorMap*, CUtensorMapDataType, cuuint32_t, void*, const cuuint64_t*, const cuuint64_t*, const cuuint32_t*, const cuuint32_t*,
                          CUtensorMapInterleave, CUtensorMapSwizzle, CUtensorMapL2promotion, CUtensorMapFloatOOBfill);

static void make_map(EncFn enc, CUtensorMap* tm, const void* ptr, int cols, int rows, int bc, int br, int grp, CUtensorMapSwizzle sw,
                     CUtensorMapL2promotion promo = CU_TENSOR_MAP_L2_PROMOTION_NONE) {
  cuuint64_t gd[3] = {(cuuint64_t)(grp ? bc : cols), (cuuint64_t)rows, (cuuint64_t)(cols / bc)};
  cuuint64_t gs[2] = {(cuuint64_t)cols * 2, (cuuint64_t)bc * 2};
  cuuint32_t bd[3] = {(cuuint32_t)bc, (cuuint32_t)br, (cuuint32_t)grp};
  cuuint32_t es[3] = {1, 1, 1};
  CUresult r = enc(tm, CU_TENSOR_MAP_DATA_TYPE_BFLOAT16, grp ? 3 : 2, const_cast<void*>(ptr), gd, gs, bd, es, CU_TENSOR_MAP_INTERLEAVE_NONE, sw,
                   promo, CU_TENSOR_MAP_FLOAT_OOB_FILL_NONE);
  (void)r;
}

}

extern "C" void kernel_launch(void* const* d_in, const int* in_sizes, int n_in, void* d_out, int out_size) {
  using namespace h3;
  (void)in_sizes; (void)n_in; (void)out_size;
  static EncFn enc = nullptr;
  static void *p_h, *p_yT, *p_kvT, *p_stat, *p_cs, *p_cnt, *p_launch;
  if (!enc) {
    void* fn = nullptr; cudaDriverEntryPointQueryResult qr;
    cudaGetDriverEntryPoint("cuTensorMapEncodeTiled", &fn, cudaEnableDefault, &qr);
    enc = (EncFn)fn;
    cudaGetSymbolAddress(&p_h, g_h); cudaGetSymbolAddress(&p_yT, g_yT); cudaGetSymbolAddress(&p_kvT, g_kvT); cudaGetSymbolAddress(&p_stat, g_stat);
    cudaGetSymbolAddress(&p_cs, g_cs); cudaGetSymbolAddress(&p_cnt, g_cnt); cudaGetSymbolAddress(&p_launch, g_launch);
    cudaFuncSetAttribute(h3_kernel, cudaFuncAttributeMaxDynamicSharedMemorySize, SMEM_BYTES);
  }
  const void *q = d_in[0], *k = d_in[1], *v = d_in[2], *w1 = d_in[7];
  Params P;
  P.q = (const __nv_bfloat16*)q; P.w1 = (const __nv_bfloat16*)w1;
  P.shift_k = (const __nv_bfloat16*)d_in[3]; P.ssm_k = (const __nv_bfloat16*)d_in[4]; P.ssm_D = (const __nv_bfloat16*)d_in[5];
  P.b1 = (const __nv_bfloat16*)d_in[8]; P.w2 = (const __nv_bfloat16*)d_in[9]; P.b2 = (const __nv_bfloat16*)d_in[10];
  P.kvT = (__nv_bfloat16*)p_kvT; P.yT = (__nv_bfloat16*)p_yT; P.stat = (uint2*)p_stat;
  P.cs = (uint32_t*)p_cs; P.cnt = (uint32_t*)p_cnt; P.launch = (uint32_t*)p_launch;
  const CUtensorMapSwizzle S128 = CU_TENSOR_MAP_SWIZZLE_128B, S64 = CU_TENSOR_MAP_SWIZZLE_64B, S0 = CU_TENSOR_MAP_SWIZZLE_NONE;
  Maps M;
  make_map(enc, &M.q0, q, DM, SL, 64, 64, 0, S128);
  make_map(enc, &M.w1, w1, FF, DM, 64, 64, 3, S128);
  make_map(enc, &M.w1x, w1, FF, DM, 24, 64, 0, S128, WS_PROMO);
  make_map(enc, &M.k, k, DM, SL, 64, 19, 0, S0);
  make_map(enc, &M.v, v, DM, SL, 64, 16, 0, S0);
  make_map(enc, &M.hs, p_h, FF, SL, 64, 64, 0, S128);
  make_map(enc, &M.hx, p_h, FF, SL, 24, 64, 0, S0);
  make_map(enc, &M.ha, p_h, FF, SL, 64, 128, 0, S128);
  make_map(enc, &M.w2, P.w2, DM, FF, 64, 64, 2, S128);
  make_map(enc, &M.w2x, P.w2, DM, FF, 64, 64, 0, S128);
  make_map(enc, &M.kvs, p_kvT, SL, DM, 16, 64, 0, CU_TENSOR_MAP_SWIZZLE_32B);
  make_map(enc, &M.qf, q, DM, SL, 32, 64, 0, S64);
  make_map(enc, &M.y, p_yT, SL, DM, 64, 16, 0, S128);
  make_map(enc, &M.out, d_out, DM, SL, 32, 64, 0, S64);
  h3_kernel<<<NCTA, 384, SMEM_BYTES>>>(P, M);
}
```

```cpp
#include <cuda_runtime.h>
#include <cuda_bf16.h>
#include <cuda.h>
#include <stdint.h>

namespace h3 {

constexpr int SL = 2048, DM = 640, FF = 1728;
constexpr int NCTA = 128;

__device__ __align__(1024) __nv_bfloat16 g_h[SL * FF];
__device__ __align__(1024) __nv_bfloat16 g_kvT[DM * SL];
__device__ __align__(1024) __nv_bfloat16 g_yT[DM * SL];
__device__ __align__(1024) uint2 g_stat[2 * SL];
__device__ __align__(1024) uint32_t g_cs[2 * 8 * 256];
__device__ __align__(1024) unsigned g_cnt[16 * 32];
__device__ __align__(1024) unsigned g_launch[NCTA * 8];
#define RETRY(i)

constexpr int G1_STAGE = 49152, G1_TX = 16384 + 24576 + 3072;
constexpr int HST = 49152;
constexpr int P0 = 81920, P1 = 140288, P2 = 156672;
constexpr int XCH = 4368, XD = 272, X0 = 173056, X4 = 221184;
constexpr int KVS = 196608, KV_BUF = 8960;
constexpr int KT_CH = 8240, KT_O = 16, KT_E = 4144, KT0 = 98304;
constexpr int FIN_Q = X0;
constexpr int MISC = 226816;
constexpr int M_BX = MISC;
constexpr int M_RED0 = M_BX + 2048, M_RED1 = M_BX;
constexpr int M_SK = KVS + 3 * KV_BUF;
constexpr int M_STAT = M_BX + 3584;
constexpr int M_B2 = MISC - 640;
constexpr int M_AUX = M_STAT + 512;
constexpr int M_ZERO = M_AUX + 96;
constexpr int M_BAR = M_ZERO + 16;
constexpr int M_TS = M_BAR + 94 * 8;
constexpr int SMEM_BYTES = M_TS + 272;
__host__ __device__ constexpr int fin_y(int np) {
  return np < 3 ? P0 + 10240 + np * 2048 : (np < 6 ? P1 + 10240 + (np - 3) * 2048 : (np == 6 ? FIN_Q + 20480 : (np < 9 ? X4 + (np - 7) * 2048 : M_BX + 512)));
}
static_assert(fin_y(9) % 1024 == 0 && fin_y(6) % 1024 == 0 && fin_y(6) + 2048 <= KVS && fin_y(7) % 1024 == 0, "smem");
#define STAG_KC 8
__host__ __device__ constexpr int hst(int w) { return w ? HST : (STAG_KC == 9 ? 0 : P1); }
__host__ __device__ constexpr int cv_x(int c) { return c == 4 ? X4 : X0 + c * XCH; }
__host__ __device__ constexpr int cv_p(int c) { return c == 2 ? P2 : ((c == 0 || c == 3) ? P0 : P1); }
__host__ __device__ constexpr int cv_t(int c) { return KT0 + c * KT_CH; }
__host__ __device__ constexpr int g2_a(int s) { return s == 0 ? 0 : (s == 1 ? 40960 : (s == 2 ? 98304 : P2)); }
__host__ __device__ constexpr int g2_b(int s) { return s == 0 ? 16384 : (s == 1 ? 57344 : (s == 2 ? 114688 : KVS)); }
static_assert(M_SK + 2560 <= M_B2 && X4 + XCH <= M_B2 && KVS + 24576 <= X4 && X0 + 4 * XCH <= KVS && FIN_Q + 20480 <= KVS, "smem");
static_assert(KT0 + 5 * KT_CH <= P1 && P1 + 16384 <= P2 && P2 + 16384 <= X0 && SMEM_BYTES <= 232448 && MISC % 512 == 0 && M_BAR % 8 == 0, "smem");
constexpr int B_E1 = 0, B_FR = 4, B_E2 = 8, B_TD = 11  , B_RF = 13;
constexpr int B_HB = 16, B_SD = 24, B_OUT = 29, B_LNI = 34, B_RED = 35, B_RED1 = 36, B_FINY = 37, B_BX = 38, B_KD = 39;
constexpr int B_F2 = 40, B_KRAW = 44, B_RD = 46, B_SK = 47, B_XL = 48, B_KT = 53, B_XF = 58, B_KIN = 63, B_KIN1 = 68, B_YSLOT = 73,
              B_YL = 76, B_XR = 79, B_XD = 80, B_FINQ = 83, B_HD = 84, B_F1 = 88, B_F0 = 92;
constexpr int NB_INIT = 1, NB_INIT2 = 2, NB_AUX = 3, NB_LEAD = 4, NB_GELU = 5, NB_TURN = 6  , NB_END = 8, NB_INIT3 = 9, NB_WG1 = 10;

#define PRO 2
#define G1U 6
#define P1U 1
constexpr int G1_UNROLL = G1U, P1_UNROLL = P1U;
#define KV_MAP 0x764
#define WS_PROMO CU_TENSOR_MAP_L2_PROMOTION_L2_128B
#define RAW_LATE 0
#define PF_RAW 7
#define REL_K 0
#define CS_WAIT 1
#define GELU_NB 8
#define H_ORD 0x73625410
#define W2_PF 4
#define H_FLY 2
#define TB_MAP 0x01040532u
#define KRAW_N 2
#define XT1 (B_FR + 3)
#define XT2 (B_HB + 1)
#define XT3 (B_HB + 3)
#define XT4 (B_HB + 7)
#define X_TRIG ((XT1) | (XT2) << 8 | (XT3) << 16 | (XT4) << 24)
#define FENCE_KIND 1
#define SCH2 2
#define SCH 2
#define A_NB0 14
#define HAND4 1
#define LEAD_KC 1
#define RED_GATE 2
#define XP_KC 5
#define NSH 12
#define NST (27 - NSH)
#define YP_KC 12
#define YFENCE 1
#define Y_MAP 0x210
#define Y_KC 8
#define XD_N 6
#define XD_M 8
#define HOLD_KC 11
#define END_KC (NSH - 1)
#define REG_AUX "56"
#define REG_CON "224"
#define LDQ ".nc.L1::no_allocate"
#define LDP ""

static_assert((H_ORD & 0xff) == 0x10 && H_FLY <= 6, "the staging buffer of warpgroup 0 is released in two steps");
__device__ __forceinline__ uint32_t s32(const void* p) { return (uint32_t)__cvta_generic_to_shared(p); }
__device__ __forceinline__ uint32_t clk() { uint32_t t; asm volatile("mov.u32 %0, %%clock;" : "=r"(t)); return t; }
__device__ __forceinline__ bool elect_one() {
  uint32_t p; asm volatile("{\n.reg .pred P;\nelect.sync _|P, 0xffffffff;\nselp.u32 %0, 1, 0, P;\n}" : "=r"(p)); return p;
}
#define ONE(...) do { if (elect_one()) { __VA_ARGS__; } __syncwarp(); } while (0)
__device__ __forceinline__ void mbar_init(uint32_t a, int c) { asm volatile("mbarrier.init.shared::cta.b64 [%0], %1;" ::"r"(a), "r"(c) : "memory"); }
__device__ __forceinline__ void mbar_expect(uint32_t a, int b) { asm volatile("mbarrier.arrive.expect_tx.shared::cta.b64 _, [%0], %1;" ::"r"(a), "r"(b) : "memory"); }
__device__ __forceinline__ void mbar_arrive(uint32_t a) { asm volatile("mbarrier.arrive.shared::cta.b64 _, [%0];" ::"r"(a) : "memory"); }
__device__ __forceinline__ bool spin_guard(uint32_t& n, uint32_t) {
  return ++n > (1u << 20);
}
__device__ __forceinline__ void mbar_wait(uint32_t a, int ph) {
  asm volatile("{\n.reg .pred p;\n.reg .u32 n;\nmov.u32 n, 0;\nW:\n.pragma \"nounroll\";\nmbarrier.try_wait.parity.shared::cta.b64 p, [%0], %1;\n"
               "add.u32 n, n, 1;\nsetp.ge.or.u32 p, n, 0x100000, p;\n@!p bra W;\n}" ::"r"(a), "r"(ph) : "memory");
}
__device__ __forceinline__ bool mbar_test(uint32_t a, int ph) {
  uint32_t ok;
  asm volatile("{\n.reg .pred p;\nmbarrier.test_wait.parity.shared::cta.b64 p, [%1], %2;\nselp.u32 %0, 1, 0, p;\n}" : "=r"(ok) : "r"(a), "r"(ph) : "memory");
  return __all_sync(0xffffffffu, ok);
}
__device__ __forceinline__ void sched_fence(uint32_t a) {
  asm volatile("{\n.reg .pred p;\nsetp.eq.u32 p, %0, 0;\n@p exit;\n}" ::"r"(a) : "memory");
}
__device__ __forceinline__ void keep(uint32_t& v) { v = __shfl_sync(0xffffffffu, v, threadIdx.x & 31); }
__device__ __forceinline__ void tma2d(uint32_t dst, const CUtensorMap* tm, int c0, int c1, uint32_t bar) {
  asm volatile("cp.async.bulk.tensor.2d.shared::cluster.global.mbarrier::complete_tx::bytes [%0], [%1, {%3, %4}], [%2];"
               ::"r"(dst), "l"(tm), "r"(bar), "r"(c0), "r"(c1) : "memory");
}
__device__ __forceinline__ void tma3d(uint32_t dst, const CUtensorMap* tm, int c0, int c1, int c2, uint32_t bar) {
  asm volatile("cp.async.bulk.tensor.3d.shared::cluster.global.mbarrier::complete_tx::bytes [%0], [%1, {%3, %4, %5}], [%2];"
               ::"r"(dst), "l"(tm), "r"(bar), "r"(c0), "r"(c1), "r"(c2) : "memory");
}
__device__ __forceinline__ void tma2d_st(const CUtensorMap* tm, int c0, int c1, uint32_t src) {
  asm volatile("cp.async.bulk.tensor.2d.global.shared::cta.bulk_group [%0, {%2, %3}], [%1];" ::"l"(tm), "r"(src), "r"(c0), "r"(c1) : "memory");
}
__device__ __forceinline__ void tma3d_st(const CUtensorMap* tm, int c0, int c1, int c2, uint32_t src) {
  asm volatile("cp.async.bulk.tensor.3d.global.shared::cta.bulk_group [%0, {%2, %3, %4}], [%1];" ::"l"(tm), "r"(src), "r"(c0), "r"(c1), "r"(c2) : "memory");
}
__device__ __forceinline__ void bulk_g2s(uint32_t dst, const void* src, int bytes, uint32_t bar) {
  asm volatile("cp.async.bulk.shared::cluster.global.mbarrier::complete_tx::bytes [%0], [%1], %2, [%3];" ::"r"(dst), "l"(src), "r"(bytes), "r"(bar) : "memory");
}
__device__ __forceinline__ void bulk_commit() { asm volatile("cp.async.bulk.commit_group;" ::: "memory"); }
__device__ __forceinline__ void bulk_wait_read() { asm volatile("cp.async.bulk.wait_group.read 0;" ::: "memory"); }
__device__ __forceinline__ void bulk_wait_all() { asm volatile("cp.async.bulk.wait_group 0;" ::: "memory"); }
__device__ __forceinline__ void fence_async_smem() { asm volatile("fence.proxy.async.shared::cta;" ::: "memory"); }
__device__ __forceinline__ void fence_async_all() { asm volatile("fence.proxy.async;" ::: "memory"); }
__device__ __forceinline__ void fence_gpu() { asm volatile("fence.acq_rel.gpu;" ::: "memory"); }
#define bar_sync(id, n) asm volatile("bar.sync %0, %1;" ::"n"(id), "n"(n) : "memory")
#define bar_arrive(id, n) asm volatile("bar.arrive %0, %1;" ::"n"(id), "n"(n) : "memory")
__device__ __forceinline__ void wg_fence() { asm volatile("wgmma.fence.sync.aligned;" ::: "memory"); }
__device__ __forceinline__ void wg_commit() { asm volatile("wgmma.commit_group.sync.aligned;" ::: "memory"); }
template <int N> __device__ __forceinline__ void wg_wait() { asm volatile("wgmma.wait_group.sync.aligned %0;" ::"n"(N) : "memory"); }
__device__ __forceinline__ uint64_t mkdesc(uint32_t addr, uint32_t lbo, uint32_t sbo, int sw) {
  return (uint64_t)((addr & 0x3FFFF) >> 4) | ((uint64_t)(lbo >> 4) << 16) | ((uint64_t)(sbo >> 4) << 32) | ((uint64_t)sw << 62);
}
__device__ __forceinline__ uint32_t ldg32(const void* p) { uint32_t v; asm volatile("ld.global" LDQ ".b32 %0, [%1];" : "=r"(v) : "l"(p)); return v; }
template <int OFF> __device__ __forceinline__ uint32_t ldg32o(const void* p) { uint32_t v; asm volatile("ld.global" LDQ ".b32 %0, [%1+%2];" : "=r"(v) : "l"(p), "n"(OFF)); return v; }
template <int I> __device__ __forceinline__ void kv_loads(const void* kp, const void* vp, uint32_t (&kk)[16], uint32_t (&o)[16]) {
  kk[I] = ldg32o<I * DM * 2>(kp); o[I] = ldg32o<I * DM * 2>(vp);
  if constexpr (I < 15) kv_loads<I + 1>(kp, vp, kk, o);
}
__device__ __forceinline__ uint4 ldg128(const void* p) {
  uint4 v; asm volatile("ld.global" LDQ LDP ".v4.b32 {%0,%1,%2,%3}, [%4];" : "=r"(v.x), "=r"(v.y), "=r"(v.z), "=r"(v.w) : "l"(p)); return v;
}
__device__ __forceinline__ void stg128(void* p, uint32_t x, uint32_t y, uint32_t z, uint32_t w) {
  asm volatile("st.global.v4.b32 [%0], {%1,%2,%3,%4};" ::"l"(p), "r"(x), "r"(y), "r"(z), "r"(w) : "memory");
}
__device__ __forceinline__ uint4 ld_relaxed128(const void* p) {
  uint4 v; asm volatile("ld.relaxed.gpu.global.v4.b32 {%0,%1,%2,%3}, [%4];" : "=r"(v.x), "=r"(v.y), "=r"(v.z), "=r"(v.w) : "l"(p) : "memory"); return v;
}
__device__ __forceinline__ uint2 ld_relaxed64(const void* p) {
  uint2 v; asm volatile("ld.relaxed.gpu.global.v2.b32 {%0,%1}, [%2];" : "=r"(v.x), "=r"(v.y) : "l"(p) : "memory"); return v;
}
__device__ __forceinline__ uint4 ld_relaxed_b128(const void* p) {
  uint4 v; asm volatile("{\n.reg .b128 t;\nld.relaxed.gpu.global.b128 t, [%4];\nmov.b128 {%0,%1,%2,%3}, t;\n}" : "=r"(v.x), "=r"(v.y), "=r"(v.z), "=r"(v.w) : "l"(p) : "memory"); return v;
}
__device__ __forceinline__ void st_relaxed_b128(void* p, uint32_t x, uint32_t y, uint32_t z, uint32_t w) {
  asm volatile("{\n.reg .b128 t;\nmov.b128 t, {%1,%2,%3,%4};\nst.relaxed.gpu.global.b128 [%0], t;\n}" ::"l"(p), "r"(x), "r"(y), "r"(z), "r"(w) : "memory");
}
__device__ __forceinline__ void st_relaxed64(void* p, uint32_t x, uint32_t y) {
  asm volatile("{\n.reg .b64 t;\nmov.b64 t, {%1,%2};\nst.relaxed.gpu.global.b64 [%0], t;\n}" ::"l"(p), "r"(x), "r"(y) : "memory");
}
__device__ __forceinline__ void st_relaxed32(void* p, uint32_t x) { asm volatile("st.relaxed.gpu.global.b32 [%0], %1;" ::"l"(p), "r"(x) : "memory"); }
__device__ __forceinline__ uint32_t ld_relaxed32(const void* p) { uint32_t v; asm volatile("ld.relaxed.gpu.global.b32 %0, [%1];" : "=r"(v) : "l"(p) : "memory"); return v; }
__device__ __forceinline__ void st_relaxed128(void* p, uint32_t x, uint32_t y, uint32_t z, uint32_t w) {
  asm volatile("{\n.reg .b64 t, u;\nmov.b64 t, {%1,%2};\nmov.b64 u, {%3,%4};\nst.relaxed.gpu.global.v2.b64 [%0], {t, u};\n}" ::"l"(p), "r"(x), "r"(y), "r"(z), "r"(w) : "memory");
}
__device__ __forceinline__ void fence_release() { asm volatile("fence.proxy.async.global;\nfence.release.gpu;" ::: "memory"); }
__device__ __forceinline__ void fence_acquire() { asm volatile("fence.acquire.gpu;\nfence.proxy.async.global;" ::: "memory"); }
__device__ __forceinline__ void signal_cnt(uint32_t* p) { asm volatile("red.relaxed.gpu.global.add.u32 [%0], 1;" ::"l"(p) : "memory"); }
__device__ __forceinline__ void wait_cnt(const uint32_t* p, unsigned target) {
  uint32_t n = 0;
#pragma unroll 1
  while (!__all_sync(0xffffffffu, (int)(ld_relaxed32(p) - target) >= 0)) {
    if (spin_guard(n, 0x100)) break;
  }
  fence_acquire();
}
__device__ __forceinline__ void bulk_s2g(void* dst, uint32_t src, int bytes) {
  asm volatile("cp.async.bulk.global.shared::cta.bulk_group [%0], [%1], %2;" ::"l"(dst), "r"(src), "r"(bytes) : "memory");
}
__device__ __forceinline__ void bulk_add_s2g(void* dst, uint32_t src, int bytes) {
  asm volatile("cp.reduce.async.bulk.global.shared::cta.bulk_group.add.noftz.bf16 [%0], [%1], %2;" ::"l"(dst), "r"(src), "r"(bytes) : "memory");
}
__device__ __forceinline__ void prefetch_l2(const void* p, int bytes) { asm volatile("cp.async.bulk.prefetch.L2.global [%0], %1;" ::"l"(p), "r"(bytes) : "memory"); }
__device__ __forceinline__ void prefetch_tile(const CUtensorMap* tm, int c0, int c1) {
  asm volatile("cp.async.bulk.prefetch.tensor.2d.L2.global.tile [%0, {%1, %2}];" ::"l"(tm), "r"(c0), "r"(c1) : "memory");
}
__device__ __forceinline__ void prefetch_map(const CUtensorMap* tm) { asm volatile("prefetch.tensormap [%0];" ::"l"(tm) : "memory"); }
__device__ __forceinline__ uint32_t pack_bf16(float lo, float hi) {
  uint32_t r; asm("cvt.rn.bf16x2.f32 %0, %1, %2;" : "=r"(r) : "f"(hi), "f"(lo)); return r;
}
__device__ __forceinline__ float bf_lo(uint32_t v) { return __uint_as_float(v << 16); }
__device__ __forceinline__ float bf_hi(uint32_t v) { return __uint_as_float(v & 0xFFFF0000u); }
__device__ __forceinline__ float bf_round(float x) { return __bfloat162float(__float2bfloat16_rn(x)); }
__device__ __forceinline__ uint32_t bmul2(uint32_t a, uint32_t b) { uint32_t r; asm("mul.rn.bf16x2 %0, %1, %2;" : "=r"(r) : "r"(a), "r"(b)); return r; }
__device__ __forceinline__ uint32_t bfma2(uint32_t a, uint32_t b, uint32_t c) { uint32_t r; asm("fma.rn.bf16x2 %0, %1, %2, %3;" : "=r"(r) : "r"(a), "r"(b), "r"(c)); return r; }
__device__ __forceinline__ uint32_t badd2(uint32_t a, uint32_t b) { uint32_t r; asm("add.rn.bf16x2 %0, %1, %2;" : "=r"(r) : "r"(a), "r"(b)); return r; }
__device__ __forceinline__ uint32_t bsub2(uint32_t a, uint32_t b) { uint32_t r; asm("sub.rn.bf16x2 %0, %1, %2;" : "=r"(r) : "r"(a), "r"(b)); return r; }
__device__ __forceinline__ uint32_t tagged(float v, uint32_t ep) { return (__float_as_uint(v) & ~15u) | (ep & 15u); }
__device__ __forceinline__ float tanh_fast(float x) { float r; asm("tanh.approx.f32 %0, %1;" : "=f"(r) : "f"(x)); return r; }
__device__ __forceinline__ float rcp_fast(float x) { float r; asm("rcp.approx.ftz.f32 %0, %1;" : "=f"(r) : "f"(x)); return r; }
__device__ __forceinline__ float sqrt_fast(float x) { float r; asm("sqrt.approx.ftz.f32 %0, %1;" : "=f"(r) : "f"(x)); return r; }
__device__ __forceinline__ uint32_t lds32(uint32_t a) { uint32_t v; asm volatile("ld.shared.b32 %0, [%1];" : "=r"(v) : "r"(a)); return v; }
__device__ __forceinline__ uint4 lds128(uint32_t a) { uint4 v; asm volatile("ld.shared.v4.b32 {%0,%1,%2,%3}, [%4];" : "=r"(v.x), "=r"(v.y), "=r"(v.z), "=r"(v.w) : "r"(a)); return v; }
__device__ __forceinline__ float2 lds64f(uint32_t a) { float2 v; asm volatile("ld.shared.v2.f32 {%0,%1}, [%2];" : "=f"(v.x), "=f"(v.y) : "r"(a)); return v; }
__device__ __forceinline__ void sts64f(uint32_t a, float x, float y) { asm volatile("st.shared.v2.f32 [%0], {%1,%2};" ::"r"(a), "f"(x), "f"(y) : "memory"); }
__device__ __forceinline__ void sts32(uint32_t a, uint32_t x) { asm volatile("st.shared.b32 [%0], %1;" ::"r"(a), "r"(x) : "memory"); }
__device__ __forceinline__ void sts128(uint32_t a, uint32_t x, uint32_t y, uint32_t z, uint32_t w) { asm volatile("st.shared.v4.b32 [%0], {%1,%2,%3,%4};" ::"r"(a), "r"(x), "r"(y), "r"(z), "r"(w) : "memory"); }
__device__ __forceinline__ void stsm4(uint32_t a, uint32_t r0, uint32_t r1, uint32_t r2, uint32_t r3) {
  asm volatile("stmatrix.sync.aligned.m8n8.x4.shared.b16 [%0], {%1,%2,%3,%4};" ::"r"(a), "r"(r0), "r"(r1), "r"(r2), "r"(r3) : "memory");
}
__device__ __forceinline__ void stsm4t(uint32_t a, uint32_t r0, uint32_t r1, uint32_t r2, uint32_t r3) {
  asm volatile("stmatrix.sync.aligned.m8n8.x4.trans.shared.b16 [%0], {%1,%2,%3,%4};" ::"r"(a), "r"(r0), "r"(r1), "r"(r2), "r"(r3) : "memory");
}
__device__ __forceinline__ void stsm2(uint32_t a, uint32_t r0, uint32_t r1) {
  asm volatile("stmatrix.sync.aligned.m8n8.x2.shared.b16 [%0], {%1,%2};" ::"r"(a), "r"(r0), "r"(r1) : "memory");
}
__device__ __forceinline__ void ldsm4(uint32_t a, uint32_t& r0, uint32_t& r1, uint32_t& r2, uint32_t& r3) {
  asm volatile("ldmatrix.sync.aligned.m8n8.x4.shared.b16 {%0,%1,%2,%3}, [%4];" : "=r"(r0), "=r"(r1), "=r"(r2), "=r"(r3) : "r"(a) : "memory");
}
__device__ __forceinline__ void ldsm4t(uint32_t a, uint32_t& r0, uint32_t& r1, uint32_t& r2, uint32_t& r3) {
  asm volatile("ldmatrix.sync.aligned.m8n8.x4.trans.shared.b16 {%0,%1,%2,%3}, [%4];" : "=r"(r0), "=r"(r1), "=r"(r2), "=r"(r3) : "r"(a) : "memory");
}
__device__ __forceinline__ uint32_t mapa(uint32_t a, uint32_t rank) { uint32_t r; asm("mapa.shared::cluster.u32 %0, %1, %2;" : "=r"(r) : "r"(a), "r"(rank)); return r; }
__device__ __forceinline__ void mbar_arrive_remote(uint32_t a) { asm volatile("mbarrier.arrive.relaxed.cluster.shared::cluster.b64 _, [%0];" ::"r"(a) : "memory"); }
__device__ __forceinline__ void st_async128(uint32_t a, uint32_t x, uint32_t y, uint32_t z, uint32_t w, uint32_t bar) {
  asm volatile("st.async.weak.shared::cluster.mbarrier::complete_tx::bytes.v4.b32 [%0], {%1,%2,%3,%4}, [%5];" ::"r"(a), "r"(x), "r"(y), "r"(z), "r"(w), "r"(bar) : "memory");
}
#define TS(i)

#define TSKV
__device__ __forceinline__ void wg_ss_216(float (&d)[108], uint64_t da, uint64_t db, int sd) {
  asm volatile("{\n.reg .pred p;\nsetp.ne.b32 p, %110, 0;\n"
    "wgmma.mma_async.sync.aligned.m64n216k16.f32.bf16.bf16 {%0,%1,%2,%3,%4,%5,%6,%7,%8,%9,%10,%11,%12,%13,%14,%15,%16,%17,%18,%19,%20,%21,%22,%23,%24,%25,%26,%27,%28,%29,%30,%31,%32,%33,%34,%35,%36,%37,%38,%39,%40,%41,%42,%43,%44,%45,%46,%47,%48,%49,%50,%51,%52,%53,%54,%55,%56,%57,%58,%59,%60,%61,%62,%63,%64,%65,%66,%67,%68,%69,%70,%71,%72,%73,%74,%75,%76,%77,%78,%79,%80,%81,%82,%83,%84,%85,%86,%87,%88,%89,%90,%91,%92,%93,%94,%95,%96,%97,%98,%99,%100,%101,%102,%103,%104,%105,%106,%107}, %108, %109, p, 1, 1, 0, 1;\n}\n"
    : "+f"(d[0]),"+f"(d[1]),"+f"(d[2]),"+f"(d[3]),"+f"(d[4]),"+f"(d[5]),"+f"(d[6]),"+f"(d[7]),"+f"(d[8]),"+f"(d[9]),"+f"(d[10]),"+f"(d[11]),"+f"(d[12]),"+f"(d[13]),"+f"(d[14]),"+f"(d[15]),"+f"(d[16]),"+f"(d[17]),"+f"(d[18]),"+f"(d[19]),"+f"(d[20]),"+f"(d[21]),"+f"(d[22]),"+f"(d[23]),"+f"(d[24]),"+f"(d[25]),"+f"(d[26]),"+f"(d[27]),"+f"(d[28]),"+f"(d[29]),"+f"(d[30]),"+f"(d[31]),"+f"(d[32]),"+f"(d[33]),"+f"(d[34]),"+f"(d[35]),"+f"(d[36]),"+f"(d[37]),"+f"(d[38]),"+f"(d[39]),"+f"(d[40]),"+f"(d[41]),"+f"(d[42]),"+f"(d[43]),"+f"(d[44]),"+f"(d[45]),"+f"(d[46]),"+f"(d[47]),"+f"(d[48]),"+f"(d[49]),"+f"(d[50]),"+f"(d[51]),"+f"(d[52]),"+f"(d[53]),"+f"(d[54]),"+f"(d[55]),"+f"(d[56]),"+f"(d[57]),"+f"(d[58]),"+f"(d[59]),"+f"(d[60]),"+f"(d[61]),"+f"(d[62]),"+f"(d[63]),"+f"(d[64]),"+f"(d[65]),"+f"(d[66]),"+f"(d[67]),"+f"(d[68]),"+f"(d[69]),"+f"(d[70]),"+f"(d[71]),"+f"(d[72]),"+f"(d[73]),"+f"(d[74]),"+f"(d[75]),"+f"(d[76]),"+f"(d[77]),"+f"(d[78]),"+f"(d[79]),"+f"(d[80]),"+f"(d[81]),"+f"(d[82]),"+f"(d[83]),"+f"(d[84]),"+f"(d[85]),"+f"(d[86]),"+f"(d[87]),"+f"(d[88]),"+f"(d[89]),"+f"(d[90]),"+f"(d[91]),"+f"(d[92]),"+f"(d[93]),"+f"(d[94]),"+f"(d[95]),"+f"(d[96]),"+f"(d[97]),"+f"(d[98]),"+f"(d[99]),"+f"(d[100]),"+f"(d[101]),"+f"(d[102]),"+f"(d[103]),"+f"(d[104]),"+f"(d[105]),"+f"(d[106]),"+f"(d[107]) : "l"(da), "l"(db), "r"(sd));
}
__device__ __forceinline__ void wg_ss_160(float (&d)[80], uint64_t da, uint64_t db, int sd) {
  asm volatile("{\n.reg .pred p;\nsetp.ne.b32 p, %82, 0;\n"
    "wgmma.mma_async.sync.aligned.m64n160k16.f32.bf16.bf16 {%0,%1,%2,%3,%4,%5,%6,%7,%8,%9,%10,%11,%12,%13,%14,%15,%16,%17,%18,%19,%20,%21,%22,%23,%24,%25,%26,%27,%28,%29,%30,%31,%32,%33,%34,%35,%36,%37,%38,%39,%40,%41,%42,%43,%44,%45,%46,%47,%48,%49,%50,%51,%52,%53,%54,%55,%56,%57,%58,%59,%60,%61,%62,%63,%64,%65,%66,%67,%68,%69,%70,%71,%72,%73,%74,%75,%76,%77,%78,%79}, %80, %81, p, 1, 1, 0, 1;\n}\n"
    : "+f"(d[0]),"+f"(d[1]),"+f"(d[2]),"+f"(d[3]),"+f"(d[4]),"+f"(d[5]),"+f"(d[6]),"+f"(d[7]),"+f"(d[8]),"+f"(d[9]),"+f"(d[10]),"+f"(d[11]),"+f"(d[12]),"+f"(d[13]),"+f"(d[14]),"+f"(d[15]),"+f"(d[16]),"+f"(d[17]),"+f"(d[18]),"+f"(d[19]),"+f"(d[20]),"+f"(d[21]),"+f"(d[22]),"+f"(d[23]),"+f"(d[24]),"+f"(d[25]),"+f"(d[26]),"+f"(d[27]),"+f"(d[28]),"+f"(d[29]),"+f"(d[30]),"+f"(d[31]),"+f"(d[32]),"+f"(d[33]),"+f"(d[34]),"+f"(d[35]),"+f"(d[36]),"+f"(d[37]),"+f"(d[38]),"+f"(d[39]),"+f"(d[40]),"+f"(d[41]),"+f"(d[42]),"+f"(d[43]),"+f"(d[44]),"+f"(d[45]),"+f"(d[46]),"+f"(d[47]),"+f"(d[48]),"+f"(d[49]),"+f"(d[50]),"+f"(d[51]),"+f"(d[52]),"+f"(d[53]),"+f"(d[54]),"+f"(d[55]),"+f"(d[56]),"+f"(d[57]),"+f"(d[58]),"+f"(d[59]),"+f"(d[60]),"+f"(d[61]),"+f"(d[62]),"+f"(d[63]),"+f"(d[64]),"+f"(d[65]),"+f"(d[66]),"+f"(d[67]),"+f"(d[68]),"+f"(d[69]),"+f"(d[70]),"+f"(d[71]),"+f"(d[72]),"+f"(d[73]),"+f"(d[74]),"+f"(d[75]),"+f"(d[76]),"+f"(d[77]),"+f"(d[78]),"+f"(d[79]) : "l"(da), "l"(db), "r"(sd));
}
__device__ __forceinline__ void wg_rs_216(float (&d)[108], uint32_t a0, uint32_t a1, uint32_t a2, uint32_t a3, uint64_t db) {
  asm volatile("{\n.reg .pred p;\nsetp.ne.b32 p, 1, 0;\n"
    "wgmma.mma_async.sync.aligned.m64n216k16.f32.bf16.bf16 {%0,%1,%2,%3,%4,%5,%6,%7,%8,%9,%10,%11,%12,%13,%14,%15,%16,%17,%18,%19,%20,%21,%22,%23,%24,%25,%26,%27,%28,%29,%30,%31,%32,%33,%34,%35,%36,%37,%38,%39,%40,%41,%42,%43,%44,%45,%46,%47,%48,%49,%50,%51,%52,%53,%54,%55,%56,%57,%58,%59,%60,%61,%62,%63,%64,%65,%66,%67,%68,%69,%70,%71,%72,%73,%74,%75,%76,%77,%78,%79,%80,%81,%82,%83,%84,%85,%86,%87,%88,%89,%90,%91,%92,%93,%94,%95,%96,%97,%98,%99,%100,%101,%102,%103,%104,%105,%106,%107}, {%108,%109,%110,%111}, %112, p, 1, 1, 1;\n}\n"
    : "+f"(d[0]),"+f"(d[1]),"+f"(d[2]),"+f"(d[3]),"+f"(d[4]),"+f"(d[5]),"+f"(d[6]),"+f"(d[7]),"+f"(d[8]),"+f"(d[9]),"+f"(d[10]),"+f"(d[11]),"+f"(d[12]),"+f"(d[13]),"+f"(d[14]),"+f"(d[15]),"+f"(d[16]),"+f"(d[17]),"+f"(d[18]),"+f"(d[19]),"+f"(d[20]),"+f"(d[21]),"+f"(d[22]),"+f"(d[23]),"+f"(d[24]),"+f"(d[25]),"+f"(d[26]),"+f"(d[27]),"+f"(d[28]),"+f"(d[29]),"+f"(d[30]),"+f"(d[31]),"+f"(d[32]),"+f"(d[33]),"+f"(d[34]),"+f"(d[35]),"+f"(d[36]),"+f"(d[37]),"+f"(d[38]),"+f"(d[39]),"+f"(d[40]),"+f"(d[41]),"+f"(d[42]),"+f"(d[43]),"+f"(d[44]),"+f"(d[45]),"+f"(d[46]),"+f"(d[47]),"+f"(d[48]),"+f"(d[49]),"+f"(d[50]),"+f"(d[51]),"+f"(d[52]),"+f"(d[53]),"+f"(d[54]),"+f"(d[55]),"+f"(d[56]),"+f"(d[57]),"+f"(d[58]),"+f"(d[59]),"+f"(d[60]),"+f"(d[61]),"+f"(d[62]),"+f"(d[63]),"+f"(d[64]),"+f"(d[65]),"+f"(d[66]),"+f"(d[67]),"+f"(d[68]),"+f"(d[69]),"+f"(d[70]),"+f"(d[71]),"+f"(d[72]),"+f"(d[73]),"+f"(d[74]),"+f"(d[75]),"+f"(d[76]),"+f"(d[77]),"+f"(d[78]),"+f"(d[79]),"+f"(d[80]),"+f"(d[81]),"+f"(d[82]),"+f"(d[83]),"+f"(d[84]),"+f"(d[85]),"+f"(d[86]),"+f"(d[87]),"+f"(d[88]),"+f"(d[89]),"+f"(d[90]),"+f"(d[91]),"+f"(d[92]),"+f"(d[93]),"+f"(d[94]),"+f"(d[95]),"+f"(d[96]),"+f"(d[97]),"+f"(d[98]),"+f"(d[99]),"+f"(d[100]),"+f"(d[101]),"+f"(d[102]),"+f"(d[103]),"+f"(d[104]),"+f"(d[105]),"+f"(d[106]),"+f"(d[107]) : "r"(a0), "r"(a1), "r"(a2), "r"(a3), "l"(db));
}
__device__ __forceinline__ void wg_cv_0_0(float (&d)[128], uint32_t a0, uint32_t a1, uint32_t a2, uint32_t a3, uint32_t db) {
  asm volatile("{\n.reg .pred p;\n.reg .b64 t;\nsetp.ne.b32 p, 0, 0;\nmov.b64 t, {%20, 8};\n"
    "wgmma.mma_async.sync.aligned.m64n32k16.f32.bf16.bf16 {%0,%1,%2,%3,%4,%5,%6,%7,%8,%9,%10,%11,%12,%13,%14,%15}, {%16,%17,%18,%19}, t, p, 1, 1, 0;\n}\n"
    : "+f"(d[0]),"+f"(d[1]),"+f"(d[2]),"+f"(d[3]),"+f"(d[4]),"+f"(d[5]),"+f"(d[6]),"+f"(d[7]),"+f"(d[8]),"+f"(d[9]),"+f"(d[10]),"+f"(d[11]),"+f"(d[12]),"+f"(d[13]),"+f"(d[14]),"+f"(d[15]) : "r"(a0), "r"(a1), "r"(a2), "r"(a3), "r"(db));
}
__device__ __forceinline__ void wg_cv_0_1(float (&d)[128], uint32_t a0, uint32_t a1, uint32_t a2, uint32_t a3, uint32_t db) {
  asm volatile("{\n.reg .pred p;\n.reg .b64 t;\nsetp.ne.b32 p, 1, 0;\nmov.b64 t, {%20, 8};\n"
    "wgmma.mma_async.sync.aligned.m64n32k16.f32.bf16.bf16 {%0,%1,%2,%3,%4,%5,%6,%7,%8,%9,%10,%11,%12,%13,%14,%15}, {%16,%17,%18,%19}, t, p, 1, 1, 0;\n}\n"
    : "+f"(d[0]),"+f"(d[1]),"+f"(d[2]),"+f"(d[3]),"+f"(d[4]),"+f"(d[5]),"+f"(d[6]),"+f"(d[7]),"+f"(d[8]),"+f"(d[9]),"+f"(d[10]),"+f"(d[11]),"+f"(d[12]),"+f"(d[13]),"+f"(d[14]),"+f"(d[15]) : "r"(a0), "r"(a1), "r"(a2), "r"(a3), "r"(db));
}
__device__ __forceinline__ void wg_cv_1_0(float (&d)[128], uint32_t a0, uint32_t a1, uint32_t a2, uint32_t a3, uint32_t db) {
  asm volatile("{\n.reg .pred p;\n.reg .b64 t;\nsetp.ne.b32 p, 0, 0;\nmov.b64 t, {%20, 8};\n"
    "wgmma.mma_async.sync.aligned.m64n32k16.f32.bf16.bf16 {%0,%1,%2,%3,%4,%5,%6,%7,%8,%9,%10,%11,%12,%13,%14,%15}, {%16,%17,%18,%19}, t, p, 1, 1, 0;\n}\n"
    : "+f"(d[16]),"+f"(d[17]),"+f"(d[18]),"+f"(d[19]),"+f"(d[20]),"+f"(d[21]),"+f"(d[22]),"+f"(d[23]),"+f"(d[24]),"+f"(d[25]),"+f"(d[26]),"+f"(d[27]),"+f"(d[28]),"+f"(d[29]),"+f"(d[30]),"+f"(d[31]) : "r"(a0), "r"(a1), "r"(a2), "r"(a3), "r"(db));
}
__device__ __forceinline__ void wg_cv_1_1(float (&d)[128], uint32_t a0, uint32_t a1, uint32_t a2, uint32_t a3, uint32_t db) {
  asm volatile("{\n.reg .pred p;\n.reg .b64 t;\nsetp.ne.b32 p, 1, 0;\nmov.b64 t, {%20, 8};\n"
    "wgmma.mma_async.sync.aligned.m64n32k16.f32.bf16.bf16 {%0,%1,%2,%3,%4,%5,%6,%7,%8,%9,%10,%11,%12,%13,%14,%15}, {%16,%17,%18,%19}, t, p, 1, 1, 0;\n}\n"
    : "+f"(d[16]),"+f"(d[17]),"+f"(d[18]),"+f"(d[19]),"+f"(d[20]),"+f"(d[21]),"+f"(d[22]),"+f"(d[23]),"+f"(d[24]),"+f"(d[25]),"+f"(d[26]),"+f"(d[27]),"+f"(d[28]),"+f"(d[29]),"+f"(d[30]),"+f"(d[31]) : "r"(a0), "r"(a1), "r"(a2), "r"(a3), "r"(db));
}
__device__ __forceinline__ void wg_cv_2_0(float (&d)[128], uint32_t a0, uint32_t a1, uint32_t a2, uint32_t a3, uint32_t db) {
  asm volatile("{\n.reg .pred p;\n.reg .b64 t;\nsetp.ne.b32 p, 0, 0;\nmov.b64 t, {%20, 8};\n"
    "wgmma.mma_async.sync.aligned.m64n32k16.f32.bf16.bf16 {%0,%1,%2,%3,%4,%5,%6,%7,%8,%9,%10,%11,%12,%13,%14,%15}, {%16,%17,%18,%19}, t, p, 1, 1, 0;\n}\n"
    : "+f"(d[32]),"+f"(d[33]),"+f"(d[34]),"+f"(d[35]),"+f"(d[36]),"+f"(d[37]),"+f"(d[38]),"+f"(d[39]),"+f"(d[40]),"+f"(d[41]),"+f"(d[42]),"+f"(d[43]),"+f"(d[44]),"+f"(d[45]),"+f"(d[46]),"+f"(d[47]) : "r"(a0), "r"(a1), "r"(a2), "r"(a3), "r"(db));
}
__device__ __forceinline__ void wg_cv_2_1(float (&d)[128], uint32_t a0, uint32_t a1, uint32_t a2, uint32_t a3, uint32_t db) {
  asm volatile("{\n.reg .pred p;\n.reg .b64 t;\nsetp.ne.b32 p, 1, 0;\nmov.b64 t, {%20, 8};\n"
    "wgmma.mma_async.sync.aligned.m64n32k16.f32.bf16.bf16 {%0,%1,%2,%3,%4,%5,%6,%7,%8,%9,%10,%11,%12,%13,%14,%15}, {%16,%17,%18,%19}, t, p, 1, 1, 0;\n}\n"
    : "+f"(d[32]),"+f"(d[33]),"+f"(d[34]),"+f"(d[35]),"+f"(d[36]),"+f"(d[37]),"+f"(d[38]),"+f"(d[39]),"+f"(d[40]),"+f"(d[41]),"+f"(d[42]),"+f"(d[43]),"+f"(d[44]),"+f"(d[45]),"+f"(d[46]),"+f"(d[47]) : "r"(a0), "r"(a1), "r"(a2), "r"(a3), "r"(db));
}
__device__ __forceinline__ void wg_cv_3_0(float (&d)[128], uint32_t a0, uint32_t a1, uint32_t a2, uint32_t a3, uint32_t db) {
  asm volatile("{\n.reg .pred p;\n.reg .b64 t;\nsetp.ne.b32 p, 0, 0;\nmov.b64 t, {%20, 8};\n"
    "wgmma.mma_async.sync.aligned.m64n32k16.f32.bf16.bf16 {%0,%1,%2,%3,%4,%5,%6,%7,%8,%9,%10,%11,%12,%13,%14,%15}, {%16,%17,%18,%19}, t, p, 1, 1, 0;\n}\n"
    : "+f"(d[48]),"+f"(d[49]),"+f"(d[50]),"+f"(d[51]),"+f"(d[52]),"+f"(d[53]),"+f"(d[54]),"+f"(d[55]),"+f"(d[56]),"+f"(d[57]),"+f"(d[58]),"+f"(d[59]),"+f"(d[60]),"+f"(d[61]),"+f"(d[62]),"+f"(d[63]) : "r"(a0), "r"(a1), "r"(a2), "r"(a3), "r"(db));
}
__device__ __forceinline__ void wg_cv_3_1(float (&d)[128], uint32_t a0, uint32_t a1, uint32_t a2, uint32_t a3, uint32_t db) {
  asm volatile("{\n.reg .pred p;\n.reg .b64 t;\nsetp.ne.b32 p, 1, 0;\nmov.b64 t, {%20, 8};\n"
    "wgmma.mma_async.sync.aligned.m64n32k16.f32.bf16.bf16 {%0,%1,%2,%3,%4,%5,%6,%7,%8,%9,%10,%11,%12,%13,%14,%15}, {%16,%17,%18,%19}, t, p, 1, 1, 0;\n}\n"
    : "+f"(d[48]),"+f"(d[49]),"+f"(d[50]),"+f"(d[51]),"+f"(d[52]),"+f"(d[53]),"+f"(d[54]),"+f"(d[55]),"+f"(d[56]),"+f"(d[57]),"+f"(d[58]),"+f"(d[59]),"+f"(d[60]),"+f"(d[61]),"+f"(d[62]),"+f"(d[63]) : "r"(a0), "r"(a1), "r"(a2), "r"(a3), "r"(db));
}
__device__ __forceinline__ void wg_cv_4_0(float (&d)[128], uint32_t a0, uint32_t a1, uint32_t a2, uint32_t a3, uint32_t db) {
  asm volatile("{\n.reg .pred p;\n.reg .b64 t;\nsetp.ne.b32 p, 0, 0;\nmov.b64 t, {%20, 8};\n"
    "wgmma.mma_async.sync.aligned.m64n32k16.f32.bf16.bf16 {%0,%1,%2,%3,%4,%5,%6,%7,%8,%9,%10,%11,%12,%13,%14,%15}, {%16,%17,%18,%19}, t, p, 1, 1, 0;\n}\n"
    : "+f"(d[64]),"+f"(d[65]),"+f"(d[66]),"+f"(d[67]),"+f"(d[68]),"+f"(d[69]),"+f"(d[70]),"+f"(d[71]),"+f"(d[72]),"+f"(d[73]),"+f"(d[74]),"+f"(d[75]),"+f"(d[76]),"+f"(d[77]),"+f"(d[78]),"+f"(d[79]) : "r"(a0), "r"(a1), "r"(a2), "r"(a3), "r"(db));
}
__device__ __forceinline__ void wg_cv_4_1(float (&d)[128], uint32_t a0, uint32_t a1, uint32_t a2, uint32_t a3, uint32_t db) {
  asm volatile("{\n.reg .pred p;\n.reg .b64 t;\nsetp.ne.b32 p, 1, 0;\nmov.b64 t, {%20, 8};\n"
    "wgmma.mma_async.sync.aligned.m64n32k16.f32.bf16.bf16 {%0,%1,%2,%3,%4,%5,%6,%7,%8,%9,%10,%11,%12,%13,%14,%15}, {%16,%17,%18,%19}, t, p, 1, 1, 0;\n}\n"
    : "+f"(d[64]),"+f"(d[65]),"+f"(d[66]),"+f"(d[67]),"+f"(d[68]),"+f"(d[69]),"+f"(d[70]),"+f"(d[71]),"+f"(d[72]),"+f"(d[73]),"+f"(d[74]),"+f"(d[75]),"+f"(d[76]),"+f"(d[77]),"+f"(d[78]),"+f"(d[79]) : "r"(a0), "r"(a1), "r"(a2), "r"(a3), "r"(db));
}
__device__ __forceinline__ void wg_cv_5_0(float (&d)[128], uint32_t a0, uint32_t a1, uint32_t a2, uint32_t a3, uint32_t db) {
  asm volatile("{\n.reg .pred p;\n.reg .b64 t;\nsetp.ne.b32 p, 0, 0;\nmov.b64 t, {%20, 8};\n"
    "wgmma.mma_async.sync.aligned.m64n32k16.f32.bf16.bf16 {%0,%1,%2,%3,%4,%5,%6,%7,%8,%9,%10,%11,%12,%13,%14,%15}, {%16,%17,%18,%19}, t, p, 1, 1, 0;\n}\n"
    : "+f"(d[80]),"+f"(d[81]),"+f"(d[82]),"+f"(d[83]),"+f"(d[84]),"+f"(d[85]),"+f"(d[86]),"+f"(d[87]),"+f"(d[88]),"+f"(d[89]),"+f"(d[90]),"+f"(d[91]),"+f"(d[92]),"+f"(d[93]),"+f"(d[94]),"+f"(d[95]) : "r"(a0), "r"(a1), "r"(a2), "r"(a3), "r"(db));
}
__device__ __forceinline__ void wg_cv_5_1(float (&d)[128], uint32_t a0, uint32_t a1, uint32_t a2, uint32_t a3, uint32_t db) {
  asm volatile("{\n.reg .pred p;\n.reg .b64 t;\nsetp.ne.b32 p, 1, 0;\nmov.b64 t, {%20, 8};\n"
    "wgmma.mma_async.sync.aligned.m64n32k16.f32.bf16.bf16 {%0,%1,%2,%3,%4,%5,%6,%7,%8,%9,%10,%11,%12,%13,%14,%15}, {%16,%17,%18,%19}, t, p, 1, 1, 0;\n}\n"
    : "+f"(d[80]),"+f"(d[81]),"+f"(d[82]),"+f"(d[83]),"+f"(d[84]),"+f"(d[85]),"+f"(d[86]),"+f"(d[87]),"+f"(d[88]),"+f"(d[89]),"+f"(d[90]),"+f"(d[91]),"+f"(d[92]),"+f"(d[93]),"+f"(d[94]),"+f"(d[95]) : "r"(a0), "r"(a1), "r"(a2), "r"(a3), "r"(db));
}
__device__ __forceinline__ void wg_cv_6_0(float (&d)[128], uint32_t a0, uint32_t a1, uint32_t a2, uint32_t a3, uint32_t db) {
  asm volatile("{\n.reg .pred p;\n.reg .b64 t;\nsetp.ne.b32 p, 0, 0;\nmov.b64 t, {%20, 8};\n"
    "wgmma.mma_async.sync.aligned.m64n32k16.f32.bf16.bf16 {%0,%1,%2,%3,%4,%5,%6,%7,%8,%9,%10,%11,%12,%13,%14,%15}, {%16,%17,%18,%19}, t, p, 1, 1, 0;\n}\n"
    : "+f"(d[96]),"+f"(d[97]),"+f"(d[98]),"+f"(d[99]),"+f"(d[100]),"+f"(d[101]),"+f"(d[102]),"+f"(d[103]),"+f"(d[104]),"+f"(d[105]),"+f"(d[106]),"+f"(d[107]),"+f"(d[108]),"+f"(d[109]),"+f"(d[110]),"+f"(d[111]) : "r"(a0), "r"(a1), "r"(a2), "r"(a3), "r"(db));
}
__device__ __forceinline__ void wg_cv_6_1(float (&d)[128], uint32_t a0, uint32_t a1, uint32_t a2, uint32_t a3, uint32_t db) {
  asm volatile("{\n.reg .pred p;\n.reg .b64 t;\nsetp.ne.b32 p, 1, 0;\nmov.b64 t, {%20, 8};\n"
    "wgmma.mma_async.sync.aligned.m64n32k16.f32.bf16.bf16 {%0,%1,%2,%3,%4,%5,%6,%7,%8,%9,%10,%11,%12,%13,%14,%15}, {%16,%17,%18,%19}, t, p, 1, 1, 0;\n}\n"
    : "+f"(d[96]),"+f"(d[97]),"+f"(d[98]),"+f"(d[99]),"+f"(d[100]),"+f"(d[101]),"+f"(d[102]),"+f"(d[103]),"+f"(d[104]),"+f"(d[105]),"+f"(d[106]),"+f"(d[107]),"+f"(d[108]),"+f"(d[109]),"+f"(d[110]),"+f"(d[111]) : "r"(a0), "r"(a1), "r"(a2), "r"(a3), "r"(db));
}
__device__ __forceinline__ void wg_cv_7_0(float (&d)[128], uint32_t a0, uint32_t a1, uint32_t a2, uint32_t a3, uint32_t db) {
  asm volatile("{\n.reg .pred p;\n.reg .b64 t;\nsetp.ne.b32 p, 0, 0;\nmov.b64 t, {%20, 8};\n"
    "wgmma.mma_async.sync.aligned.m64n32k16.f32.bf16.bf16 {%0,%1,%2,%3,%4,%5,%6,%7,%8,%9,%10,%11,%12,%13,%14,%15}, {%16,%17,%18,%19}, t, p, 1, 1, 0;\n}\n"
    : "+f"(d[112]),"+f"(d[113]),"+f"(d[114]),"+f"(d[115]),"+f"(d[116]),"+f"(d[117]),"+f"(d[118]),"+f"(d[119]),"+f"(d[120]),"+f"(d[121]),"+f"(d[122]),"+f"(d[123]),"+f"(d[124]),"+f"(d[125]),"+f"(d[126]),"+f"(d[127]) : "r"(a0), "r"(a1), "r"(a2), "r"(a3), "r"(db));
}
__device__ __forceinline__ void wg_cv_7_1(float (&d)[128], uint32_t a0, uint32_t a1, uint32_t a2, uint32_t a3, uint32_t db) {
  asm volatile("{\n.reg .pred p;\n.reg .b64 t;\nsetp.ne.b32 p, 1, 0;\nmov.b64 t, {%20, 8};\n"
    "wgmma.mma_async.sync.aligned.m64n32k16.f32.bf16.bf16 {%0,%1,%2,%3,%4,%5,%6,%7,%8,%9,%10,%11,%12,%13,%14,%15}, {%16,%17,%18,%19}, t, p, 1, 1, 0;\n}\n"
    : "+f"(d[112]),"+f"(d[113]),"+f"(d[114]),"+f"(d[115]),"+f"(d[116]),"+f"(d[117]),"+f"(d[118]),"+f"(d[119]),"+f"(d[120]),"+f"(d[121]),"+f"(d[122]),"+f"(d[123]),"+f"(d[124]),"+f"(d[125]),"+f"(d[126]),"+f"(d[127]) : "r"(a0), "r"(a1), "r"(a2), "r"(a3), "r"(db));
}
template <class F, class T> __device__ __forceinline__ void conv_chain_1(float (&d)[128], uint32_t (&a)[64], uint32_t db, uint32_t ao, uint32_t ab, F hand, T dead) {
  wg_cv_7_0(d, a[60], a[61], a[62], a[63], db + 0);
  wg_cv_6_0(d, a[52], a[53], a[54], a[55], db + 0);
  dead();
  wg_cv_7_1(d, a[56], a[57], a[58], a[59], db + 16);
  wg_cv_5_0(d, a[44], a[45], a[46], a[47], db + 0);
  wg_cv_6_1(d, a[48], a[49], a[50], a[51], db + 16);
  wg_cv_7_1(d, a[52], a[53], a[54], a[55], db + 32);
  wg_cv_5_1(d, a[40], a[41], a[42], a[43], db + 16);
  wg_cv_6_1(d, a[44], a[45], a[46], a[47], db + 32);
  wg_cv_7_1(d, a[48], a[49], a[50], a[51], db + 48);
  wg_cv_6_1(d, a[40], a[41], a[42], a[43], db + 48);
  wg_cv_7_1(d, a[44], a[45], a[46], a[47], db + 64);
  wg_cv_7_1(d, a[40], a[41], a[42], a[43], db + 80);
  wg_commit();
  wg_cv_7_1(d, a[36], a[37], a[38], a[39], db + 96);
  wg_cv_6_1(d, a[36], a[37], a[38], a[39], db + 64);
  wg_cv_5_1(d, a[36], a[37], a[38], a[39], db + 32);
  wg_cv_4_0(d, a[36], a[37], a[38], a[39], db + 0);
  wg_commit(); wg_wait<1>();
  wg_cv_7_1(d, a[32], a[33], a[34], a[35], db + 112);
  wg_cv_6_1(d, a[32], a[33], a[34], a[35], db + 80);
  wg_cv_5_1(d, a[32], a[33], a[34], a[35], db + 48);
  a[60] = lds32(ab + (3840));
  a[61] = lds32(ab + (3968));
  a[62] = lds32(ab + (3824));
  a[63] = lds32(ab + (3952));
  wg_cv_4_1(d, a[32], a[33], a[34], a[35], db + 16);
  wg_cv_7_1(d, a[28], a[29], a[30], a[31], db + 128);
  wg_cv_6_1(d, a[28], a[29], a[30], a[31], db + 96);
  wg_cv_5_1(d, a[28], a[29], a[30], a[31], db + 64);
  a[56] = lds32(ab + (3584));
  a[57] = lds32(ab + (3712));
  a[58] = lds32(ab + (3568));
  a[59] = lds32(ab + (3696));
  wg_cv_4_1(d, a[28], a[29], a[30], a[31], db + 32);
  wg_cv_3_0(d, a[28], a[29], a[30], a[31], db + 0);
  wg_cv_7_1(d, a[24], a[25], a[26], a[27], db + 144);
  wg_cv_6_1(d, a[24], a[25], a[26], a[27], db + 112);
  a[52] = lds32(ab + (3328));
  a[53] = lds32(ab + (3456));
  a[54] = lds32(ab + (3312));
  a[55] = lds32(ab + (3440));
  wg_cv_5_1(d, a[24], a[25], a[26], a[27], db + 80);
  wg_cv_4_1(d, a[24], a[25], a[26], a[27], db + 48);
  wg_cv_3_1(d, a[24], a[25], a[26], a[27], db + 16);
  wg_commit();
  wg_cv_7_1(d, a[20], a[21], a[22], a[23], db + 160);
  wg_cv_6_1(d, a[20], a[21], a[22], a[23], db + 128);
  wg_cv_5_1(d, a[20], a[21], a[22], a[23], db + 96);
  wg_cv_4_1(d, a[20], a[21], a[22], a[23], db + 64);
  wg_commit(); wg_wait<1>();
  a[48] = lds32(ab + (3072));
  a[49] = lds32(ab + (3200));
  a[50] = lds32(ab + (3056));
  a[51] = lds32(ab + (3184));
  wg_cv_3_1(d, a[20], a[21], a[22], a[23], db + 32);
  wg_cv_2_0(d, a[20], a[21], a[22], a[23], db + 0);
  wg_cv_7_1(d, a[16], a[17], a[18], a[19], db + 176);
  wg_cv_6_1(d, a[16], a[17], a[18], a[19], db + 144);
  a[44] = lds32(ab + (2816));
  a[45] = lds32(ab + (2944));
  a[46] = lds32(ab + (2800));
  a[47] = lds32(ab + (2928));
  wg_cv_5_1(d, a[16], a[17], a[18], a[19], db + 112);
  wg_cv_4_1(d, a[16], a[17], a[18], a[19], db + 80);
  wg_cv_3_1(d, a[16], a[17], a[18], a[19], db + 48);
  wg_cv_2_1(d, a[16], a[17], a[18], a[19], db + 16);
  a[40] = lds32(ab + (2560));
  a[41] = lds32(ab + (2688));
  a[42] = lds32(ab + (2544));
  a[43] = lds32(ab + (2672));
  wg_cv_7_1(d, a[12], a[13], a[14], a[15], db + 192);
  wg_cv_6_1(d, a[12], a[13], a[14], a[15], db + 160);
  wg_cv_5_1(d, a[12], a[13], a[14], a[15], db + 128);
  wg_cv_4_1(d, a[12], a[13], a[14], a[15], db + 96);
  a[36] = lds32(ab + (2304));
  a[37] = lds32(ab + (2432));
  a[38] = lds32(ab + (2288));
  a[39] = lds32(ab + (2416));
  wg_cv_3_1(d, a[12], a[13], a[14], a[15], db + 64);
  wg_cv_2_1(d, a[12], a[13], a[14], a[15], db + 32);
  wg_cv_1_0(d, a[12], a[13], a[14], a[15], db + 0);
  wg_cv_7_1(d, a[8], a[9], a[10], a[11], db + 208);
  a[32] = lds32(ab + (2048));
  a[33] = lds32(ab + (2176));
  a[34] = lds32(ab + (2032));
  a[35] = lds32(ab + (2160));
  wg_cv_6_1(d, a[8], a[9], a[10], a[11], db + 176);
  wg_cv_5_1(d, a[8], a[9], a[10], a[11], db + 144);
  wg_cv_4_1(d, a[8], a[9], a[10], a[11], db + 112);
  wg_cv_3_1(d, a[8], a[9], a[10], a[11], db + 80);
  a[28] = lds32(ab + (1792));
  a[29] = lds32(ab + (1920));
  a[30] = lds32(ab + (1776));
  a[31] = lds32(ab + (1904));
  wg_cv_2_1(d, a[8], a[9], a[10], a[11], db + 48);
  wg_cv_1_1(d, a[8], a[9], a[10], a[11], db + 16);
  wg_commit();
  wg_cv_7_1(d, a[4], a[5], a[6], a[7], db + 224);
  wg_cv_6_1(d, a[4], a[5], a[6], a[7], db + 192);
  wg_cv_5_1(d, a[4], a[5], a[6], a[7], db + 160);
  wg_cv_4_1(d, a[4], a[5], a[6], a[7], db + 128);
  wg_commit(); wg_wait<1>();
  a[24] = lds32(ab + (1536));
  a[25] = lds32(ab + (1664));
  a[26] = lds32(ab + (1520));
  a[27] = lds32(ab + (1648));
  hand();
  wg_cv_3_1(d, a[4], a[5], a[6], a[7], db + 96);
  wg_cv_2_1(d, a[4], a[5], a[6], a[7], db + 64);
  wg_cv_1_1(d, a[4], a[5], a[6], a[7], db + 32);
  wg_cv_0_0(d, a[4], a[5], a[6], a[7], db + 0);
  a[20] = lds32(ab + (1280));
  a[21] = lds32(ab + (1408));
  a[22] = lds32(ab + (1264));
  a[23] = lds32(ab + (1392));
  wg_cv_7_1(d, a[0], a[1], a[2], a[3], db + 240);
  wg_cv_6_1(d, a[0], a[1], a[2], a[3], db + 208);
  wg_cv_5_1(d, a[0], a[1], a[2], a[3], db + 176);
  wg_cv_4_1(d, a[0], a[1], a[2], a[3], db + 144);
  a[16] = lds32(ab + (1024));
  a[17] = lds32(ab + (1152));
  a[18] = lds32(ab + (1008));
  a[19] = lds32(ab + (1136));
  wg_cv_3_1(d, a[0], a[1], a[2], a[3], db + 112);
  wg_cv_2_1(d, a[0], a[1], a[2], a[3], db + 80);
  wg_cv_1_1(d, a[0], a[1], a[2], a[3], db + 48);
  wg_cv_0_1(d, a[0], a[1], a[2], a[3], db + 16);
  wg_commit();
  a[12] = lds32(ab + (768));
  a[13] = lds32(ab + (896));
  a[14] = lds32(ab + (752));
  a[15] = lds32(ab + (880));
  a[8] = lds32(ab + (512));
  a[9] = lds32(ab + (640));
  a[10] = lds32(ab + (496));
  a[11] = lds32(ab + (624));
}
template <class F, class T> __device__ __forceinline__ void conv_chain_0(float (&d)[128], uint32_t (&a)[64], uint32_t db, uint32_t ao, uint32_t ab, F hand, T dead) {
  wg_cv_7_0(d, a[60], a[61], a[62], a[63], db + 0);
  wg_cv_6_0(d, a[52], a[53], a[54], a[55], db + 0);
  dead();
  wg_cv_7_1(d, a[56], a[57], a[58], a[59], db + 16);
  wg_cv_5_0(d, a[44], a[45], a[46], a[47], db + 0);
  wg_cv_6_1(d, a[48], a[49], a[50], a[51], db + 16);
  wg_cv_7_1(d, a[52], a[53], a[54], a[55], db + 32);
  wg_cv_5_1(d, a[40], a[41], a[42], a[43], db + 16);
  wg_cv_6_1(d, a[44], a[45], a[46], a[47], db + 32);
  wg_cv_7_1(d, a[48], a[49], a[50], a[51], db + 48);
  wg_cv_6_1(d, a[40], a[41], a[42], a[43], db + 48);
  wg_cv_7_1(d, a[44], a[45], a[46], a[47], db + 64);
  wg_cv_7_1(d, a[40], a[41], a[42], a[43], db + 80);
  wg_commit();
  wg_cv_7_1(d, a[36], a[37], a[38], a[39], db + 96);
  wg_cv_6_1(d, a[36], a[37], a[38], a[39], db + 64);
  wg_cv_5_1(d, a[36], a[37], a[38], a[39], db + 32);
  wg_cv_4_0(d, a[36], a[37], a[38], a[39], db + 0);
  wg_cv_7_1(d, a[32], a[33], a[34], a[35], db + 112);
  wg_cv_6_1(d, a[32], a[33], a[34], a[35], db + 80);
  wg_cv_5_1(d, a[32], a[33], a[34], a[35], db + 48);
  wg_cv_4_1(d, a[32], a[33], a[34], a[35], db + 16);
  wg_cv_7_1(d, a[28], a[29], a[30], a[31], db + 128);
  wg_cv_6_1(d, a[28], a[29], a[30], a[31], db + 96);
  wg_cv_5_1(d, a[28], a[29], a[30], a[31], db + 64);
  wg_cv_4_1(d, a[28], a[29], a[30], a[31], db + 32);
  wg_cv_3_0(d, a[28], a[29], a[30], a[31], db + 0);
  wg_cv_7_1(d, a[24], a[25], a[26], a[27], db + 144);
  wg_cv_6_1(d, a[24], a[25], a[26], a[27], db + 112);
  wg_cv_5_1(d, a[24], a[25], a[26], a[27], db + 80);
  wg_cv_4_1(d, a[24], a[25], a[26], a[27], db + 48);
  wg_cv_3_1(d, a[24], a[25], a[26], a[27], db + 16);
  wg_commit();
  wg_cv_7_1(d, a[20], a[21], a[22], a[23], db + 160);
  wg_cv_6_1(d, a[20], a[21], a[22], a[23], db + 128);
  wg_cv_5_1(d, a[20], a[21], a[22], a[23], db + 96);
  wg_cv_4_1(d, a[20], a[21], a[22], a[23], db + 64);
  wg_cv_3_1(d, a[20], a[21], a[22], a[23], db + 32);
  wg_cv_2_0(d, a[20], a[21], a[22], a[23], db + 0);
  wg_cv_7_1(d, a[16], a[17], a[18], a[19], db + 176);
  wg_cv_6_1(d, a[16], a[17], a[18], a[19], db + 144);
  wg_cv_5_1(d, a[16], a[17], a[18], a[19], db + 112);
  wg_cv_4_1(d, a[16], a[17], a[18], a[19], db + 80);
  wg_cv_3_1(d, a[16], a[17], a[18], a[19], db + 48);
  wg_cv_2_1(d, a[16], a[17], a[18], a[19], db + 16);
  wg_cv_7_1(d, a[12], a[13], a[14], a[15], db + 192);
  wg_cv_6_1(d, a[12], a[13], a[14], a[15], db + 160);
  wg_cv_5_1(d, a[12], a[13], a[14], a[15], db + 128);
  wg_cv_4_1(d, a[12], a[13], a[14], a[15], db + 96);
  wg_cv_3_1(d, a[12], a[13], a[14], a[15], db + 64);
  wg_cv_2_1(d, a[12], a[13], a[14], a[15], db + 32);
  wg_cv_1_0(d, a[12], a[13], a[14], a[15], db + 0);
  wg_cv_7_1(d, a[8], a[9], a[10], a[11], db + 208);
  wg_cv_6_1(d, a[8], a[9], a[10], a[11], db + 176);
  wg_cv_5_1(d, a[8], a[9], a[10], a[11], db + 144);
  wg_cv_4_1(d, a[8], a[9], a[10], a[11], db + 112);
  wg_cv_3_1(d, a[8], a[9], a[10], a[11], db + 80);
  wg_cv_2_1(d, a[8], a[9], a[10], a[11], db + 48);
  wg_cv_1_1(d, a[8], a[9], a[10], a[11], db + 16);
  wg_commit();
  wg_cv_7_1(d, a[4], a[5], a[6], a[7], db + 224);
  wg_cv_6_1(d, a[4], a[5], a[6], a[7], db + 192);
  wg_cv_5_1(d, a[4], a[5], a[6], a[7], db + 160);
  wg_cv_4_1(d, a[4], a[5], a[6], a[7], db + 128);
  hand();
  wg_cv_3_1(d, a[4], a[5], a[6], a[7], db + 96);
  wg_cv_2_1(d, a[4], a[5], a[6], a[7], db + 64);
  wg_cv_1_1(d, a[4], a[5], a[6], a[7], db + 32);
  wg_cv_0_0(d, a[4], a[5], a[6], a[7], db + 0);
  wg_cv_7_1(d, a[0], a[1], a[2], a[3], db + 240);
  wg_cv_6_1(d, a[0], a[1], a[2], a[3], db + 208);
  wg_cv_5_1(d, a[0], a[1], a[2], a[3], db + 176);
  wg_cv_4_1(d, a[0], a[1], a[2], a[3], db + 144);
  wg_cv_3_1(d, a[0], a[1], a[2], a[3], db + 112);
  wg_cv_2_1(d, a[0], a[1], a[2], a[3], db + 80);
  wg_cv_1_1(d, a[0], a[1], a[2], a[3], db + 48);
  wg_cv_0_1(d, a[0], a[1], a[2], a[3], db + 16);
  wg_commit();
}
constexpr bool CV_OWN = false;
constexpr int CV_RELOADED = 2;

struct Params {
  const __nv_bfloat16 *q, *w1, *shift_k, *ssm_k, *ssm_D, *b1, *w2, *b2;
  __nv_bfloat16 *kvT, *yT;
  uint2* stat;
  uint32_t *cs, *cnt, *launch;
};
struct Maps { CUtensorMap q0, w1, w1x, k, v, hs, hx, ha, w2, w2x, kvs, qf, y, out; };

__global__ void __cluster_dims__(2, 1, 1) __launch_bounds__(384, 1) h3_kernel(const Params P, const __grid_constant__ Maps M) {
  extern __shared__ __align__(1024) uint8_t smem_raw[];
  constexpr uint32_t sc = 1024;
  const int tid = threadIdx.x, lane = tid & 31;
  auto pf0 = [&]() {
    const int l = min((int)blockIdx.x * 30 + lane, 3775);
    const char* p = l < 2048 ? reinterpret_cast<const char*>(P.q) + l * (DM * 2) : reinterpret_cast<const char*>(P.w1) + (l - 2048) * 128;
    asm volatile("prefetch.global.L2 [%0];" ::"l"(p));
  };
  if (tid < 32) { pf0(); if (tid == 0) { prefetch_map(&M.q0); prefetch_map(&M.w1); prefetch_map(&M.w1x); } }
  const int warp = __shfl_sync(0xffffffffu, tid >> 5, 0);
  const uint32_t sb = __shfl_sync(0xffffffffu, s32(smem_raw), 0);
  const int b = blockIdx.x, pr = b >> 1;
  const int pq = pr < 4 ? 32 + 8 * pr : (pr < 36 ? pr - 4 : pr - 3 + (((pr - 36) * 37) >> 8)), G = pq & 7, gi = pq >> 3;
  const int kh = b & 1, nt = (G & 1) * 2 + (gi & 1), rb = (G >> 1) * 4 + (gi >> 1);
  const int dir = (G ^ (G >> 1)) & 1, ri = (gi & 1) * 2 + kh, ci = (G >> 2) * 4 + (gi >> 1);
  const uint32_t gmap = (nt & 1) ? 0x03412u : 0x43210u;
  const int j = kh * 4 + nt;
  const uint32_t bar = sb + M_BAR;
  auto BAR = [&](int i) { return bar + 8 * i; };
  auto g1_load = [&](int kc) {
    const uint32_t st = sb + (kc & 3) * G1_STAGE, fb = BAR(B_F1 + (kc & 3));
    const int k0 = dir && kc >= 2 ? 704 - kc * 64 : kc * 64;
    mbar_expect(fb, G1_TX);
    tma2d(st, &M.q0, k0, rb * 128, fb); tma2d(st + 8192, &M.q0, k0, rb * 128 + 64, fb);
    tma3d(st + 16384, &M.w1, 0, k0, 3 * j, fb);
    tma2d(st + 40960, &M.w1x, 1536 + 24 * j, k0, fb);
  };
  auto kv_load = [&](int r, int hf) {
    const uint32_t st = sb + KVS + (r < 3 ? r : r - 3) * KV_BUF, fb = BAR((hf ? B_KIN1 : B_KIN) + r);
    mbar_expect(fb, KV_BUF / 2);
    tma2d(st + 4096 + hf * 2432, &M.k, 128 * r + 64 * (b & 1), 32 * (b >> 1) + 16 * hf - 3, fb);
    tma2d(st + hf * 2048, &M.v, 128 * r + 64 * (b & 1), 32 * (b >> 1) + 16 * hf, fb);
  };
  auto conv_sum = [&](int c, int ck, bool third, uint32_t ep) {
    const uint32_t ra = sb + cv_p(c) + ck * 16;
    __nv_bfloat16* yp = P.yT + (size_t)(128 * c + b) * SL + ck * 8;
    uint4 p[2][4];
    auto ld = [&](int u) {
#pragma unroll
      for (int w = 0; w < 4; w++) p[u & 1][w] = lds128((u == 0 && ck < 2 * w) ? sb + M_ZERO : ra + u * 512 + w * (4096 - 32));
    };
    auto st = [&](int u) {
      auto sum = [&](uint32_t a0, uint32_t a1, uint32_t a2, uint32_t a3) { return badd2(badd2(badd2(a3, a2), a1), a0); };
      const uint4* r = p[u & 1];
      const uint32_t m = ~ck & 1u;
      stg128(yp + u * 256, (sum(r[0].x, r[1].x, r[2].x, r[3].x) & ~m) | (ep & m), sum(r[0].y, r[1].y, r[2].y, r[3].y), sum(r[0].z, r[1].z, r[2].z, r[3].z), sum(r[0].w, r[1].w, r[2].w, r[3].w));
    };
    ld(0); ld(1); st(0);
    if (third) ld(2);
    st(1);
    if (third) st(2);
  };
  if (warp == 8) {
    if (lane == 0) {
      TS(0);
      mbar_init(BAR(B_F0), 1); mbar_init(BAR(B_F1), 1);
    }
    __syncwarp();
    ONE(mbar_expect(BAR(B_F0), G1_TX - 8192);
        tma2d(sb, &M.q0, 0, rb * 128, BAR(B_F0));
        tma3d(sb + 16384, &M.w1, 0, 0, 3 * j, BAR(B_F0));
        tma2d(sb + 40960, &M.w1x, 1536 + 24 * j, 0, BAR(B_F0));
        mbar_expect(BAR(B_F1), 8192);
        tma2d(sb + 8192, &M.q0, 0, rb * 128 + 64, BAR(B_F1));
        for (int s = 1; s < 4; s++) mbar_init(BAR(B_F1 + s), 1));
    bar_arrive(NB_INIT, 384);
    ONE(for (int s = 1; s <= PRO; s++) g1_load(s));
  } else {
    const int blk = warp - (warp > 8);
    ONE(for (int i = 0; i < 8; i++) mbar_init(BAR(8 * blk + i), blk < 2 ? 8 : (blk < 5 ? 4 : 1));
        asm volatile("fence.mbarrier_init.release.cluster;" ::: "memory"));
    bar_sync(NB_INIT, 384);
  }
  if ((sb & 0xFFFFFFu) != sc) { if (warp == 8) { mbar_wait(BAR(B_F0), 0); for (int s = 0; s <= PRO; s++) mbar_wait(BAR(B_F1 + s), 0); } return; }

  if (warp >= 8) {
    asm volatile("setmaxnreg.dec.sync.aligned.u32 " REG_AUX ";");
    auto table = [&](int c, int aw) {
      const uint32_t kb = sb + cv_t(c);
      const uint32_t dd = lds32(sb + M_AUX + aw * 32 + c * 4);
      if (lane < 2) sts128(kb + lane * (KT_E - 16), 0u, 0u, 0u, 0u);
      uint4 r[8];
#pragma unroll
      for (int it = 0; it < 8; it++) r[it] = lds128(kb + KT_E + (it * 32 + lane) * 16);
      if (lane == 0) { r[0].x = __byte_perm(badd2(r[0].x, dd), r[0].x, 0x7610); sts32(kb + KT_E, r[0].x); }
#pragma unroll
      for (int it = 0; it < 8; it++) {
        const uint32_t pv = __shfl_sync(0xffffffffu, lane == 31 ? (it ? r[it ? it - 1 : 0].w : 0u) : r[it].w, lane - 1);
        sts128(kb + KT_O + (it * 32 + lane) * 16, __byte_perm(pv, r[it].x, 0x5432), __byte_perm(r[it].x, r[it].y, 0x5432),
               __byte_perm(r[it].y, r[it].z, 0x5432), __byte_perm(r[it].z, r[it].w, 0x5432));
      }
      __syncwarp();
      if (lane == 0) mbar_arrive(BAR(B_KT + c));
    };
    const int aw = warp - 9, at = tid - 288;
    auto x_load = [&](int c) { mbar_expect(BAR(B_XL + c), 4096); bulk_g2s(sb + cv_x(c) + XD, P.kvT + (size_t)(128 * c + b) * SL, 4096, BAR(B_XL + c)); };
    auto x_pad = [&](int c0, int c1) {
      if (lane < 17) for (int c = c0; c < c1; c++) sts128(sb + cv_x(c) + lane * 16, 0u, 0u, 0u, 0u);
      fence_async_smem();
      __syncwarp();
    };
    if (warp == 8) {
      if (PRO < 3) ONE(for (int s = PRO + 1; s < 4; s++) g1_load(s));
      bar_sync(NB_INIT2, 64);
      unsigned ep;
#pragma unroll P1_UNROLL
      for (int kc = 4; kc < 10; kc++) {
        if (kc == 9) {
          bar_sync(NB_INIT3, 64);
          ep = lds32(sb + M_AUX + 20);
          mbar_wait(BAR(B_RED), 0);
          float2 u[8];
#pragma unroll
          for (int i = 0; i < 8; i++) u[i] = lds64f(sb + M_RED0 + (lane & 15) * 128 + ((i + lane) & 7) * 16 + (lane >> 4) * 8);
          const float c = bf_round(u[0].x * (1.f / 40)), cc = 40.f * c * c;
          float s1 = 0.f, s2 = 0.f;
#pragma unroll
          for (int i = 0; i < 8; i++) { s1 += fmaf(-40.f, c, u[i].x); s2 += fmaf(-2.f * c, u[i].x, u[i].y) + cc; }
          const float dm = s1 * (1.f / 320);
          st_relaxed64(&P.stat[dir * SL + rb * 128 + ri * 32 + lane], tagged(c + dm, ep), tagged(fmaf(-dm, s1, s2), ep));
          ONE(mbar_arrive(BAR(B_RD)));
        }
        mbar_wait(BAR(B_E1 + (kc & 3)), (kc >> 3) & 1);
        ONE(g1_load(kc));
        const int r = kc == (KV_MAP & 15) ? 0 : (kc == ((KV_MAP >> 4) & 15) ? 1 : (kc == (KV_MAP >> 8) ? 2 : -1));
        if (r >= 0) ONE(kv_load(r, 0); kv_load(r, 1));
        if (kc == PF_RAW) ONE(prefetch_l2(P.ssm_k + (size_t)b * SL, 4096));
      }
      ONE(prefetch_map(&M.hs); prefetch_map(&M.hx); prefetch_map(&M.ha); prefetch_map(&M.w2); prefetch_map(&M.w2x));
      {
        mbar_wait(BAR(CS_WAIT ? B_FR : B_F1), 0);
        uint32_t x[16], n = 0;
#pragma unroll 1
        while (true) {
          uint32_t bad = 0;
#pragma unroll
          for (int i = 0; i < 4; i++) {
            const uint4 v = ld_relaxed128(P.stat + (i >> 1) * SL + rb * 128 + lane * 4 + (i & 1) * 2);
            x[4 * i] = v.x; x[4 * i + 1] = v.y; x[4 * i + 2] = v.z; x[4 * i + 3] = v.w;
          }
#pragma unroll
          for (int i = 0; i < 16; i++) { x[i] ^= ep & 15u; bad |= x[i]; }
          if (__all_sync(0xffffffffu, (bad & 15u) == 0) || spin_guard(n, 0x132)) break;
          RETRY(9);
        }
        uint32_t st[4];
#pragma unroll
        for (int i = 0; i < 4; i++) {
          const float ma = __uint_as_float(x[2 * i]), mb = __uint_as_float(x[8 + 2 * i]), dl = ma - mb;
          const float m2 = fmaf(dl * dl, 160.f, __uint_as_float(x[1 + 2 * i]) + __uint_as_float(x[9 + 2 * i]));
          const float vb = bf_round(fmaxf(m2, 0.f) * (1.f / DM));
          st[i] = pack_bf16(0.5f * (ma + mb), sqrt_fast(bf_round(vb + 1e-5f)));
        }
        sts128(sb + M_STAT + lane * 16, st[0], st[1], st[2], st[3]);
        __syncwarp();
        if (lane < 2) mbar_arrive(BAR(B_BX));
      }
    } else {
      if (aw == 0) bar_arrive(NB_INIT2, 64);
      if (aw == 2) ONE(mbar_expect(BAR(B_XD), XD_N * 2048); mbar_expect(BAR(B_XD + 1), (XD_M - XD_N) * 2048); mbar_expect(BAR(B_XD + 2), (10 - XD_M) * 2048));
      if (aw == 1) mbar_wait(BAR(B_F0), 0);
      if (aw == 1) ONE(prefetch_map(&M.kvs); prefetch_map(&M.k); prefetch_map(&M.v); mbar_expect(BAR(B_SK), 2560);
                       for (int r = 0; r < 5; r++) bulk_g2s(sb + M_SK + r * 512, P.shift_k + (128 * r + 64 * (b & 1)) * 4, 512, BAR(B_SK)));
      const uint32_t dv0 = ld_relaxed32(lane < 5 ? static_cast<const void*>(P.ssm_D + 128 * lane + (b & ~1)) : &P.launch[b * 8]);
      const uint32_t b2v = ldg32(reinterpret_cast<const uint32_t*>(P.b2 + nt * 160) + ((gmap >> (4 * (min(at, 79) >> 4))) & 7) * 16 + (at & 15));
      const int l27 = min(lane, 26), col = l27 < 24 ? 192 * j + 8 * l27 : 1536 + 24 * j + 8 * (l27 - 24);
      uint4 bb;
      if (aw == 2) bb = ldg128(P.b1 + col);
      if (lane < 4) sts32(sb + M_ZERO + lane * 4, 0u);
      if (lane < 8) sts32(sb + M_AUX + aw * 32 + lane * 4, lane >= 5 ? dv0 + 1 : ((b & 1) ? dv0 >> 16 : dv0 & 0xFFFFu));
      if (at < 80) sts64f(sb + M_B2 + at * 8, 0.5f * bf_lo(b2v), 0.5f * bf_hi(b2v));
      __syncwarp();
      if (aw == 0) bar_arrive(NB_INIT3, 64);
      if (aw == 2) {
        const unsigned ep = lds32(sb + M_AUX + 64 + 20);
        const uint32_t ba = sb + M_BX + (l27 >> 2) * 512 + ((l27 & 3) << 4);
        mbar_wait(BAR(B_RED1), 0);
        const uint32_t tg = ep & 15u;
        float c0 = 0.f, c1 = 0.f;
#pragma unroll
        for (int i = 0; i < 16; i += 2) { c0 += __uint_as_float(lds32(sb + M_RED1 + i * 128 + lane * 4)); c1 += __uint_as_float(lds32(sb + M_RED1 + i * 128 + 128 + lane * 4)); }
        st_relaxed32(&P.cs[(dir * 8 + j) * 256 + ci * 32 + lane], tagged(c0 + c1, ep));
        if (lane == 0) TS(30);
        mbar_wait(BAR(B_RD), 0);
        sts128((ba + 128) ^ 16, 0u, 0u, 0u, 0u); sts128((ba + 192) ^ 16, bb.x, bb.y, bb.z, bb.w);
#pragma unroll
        for (int i = 4; i < 8; i++) sts128((ba + i * 64) ^ ((i >> 1) << 4), 0u, 0u, 0u, 0u);
        mbar_wait(BAR(CS_WAIT ? B_FR : B_F1), 0);
        auto raw_load = [&]() {
          if (!CS_WAIT) mbar_wait(BAR(B_FR), 0);
          ONE(mbar_expect(BAR(B_KRAW), KRAW_N * 4096); mbar_expect(BAR(B_KRAW + 1), (5 - KRAW_N) * 4096);
              for (int c = 0; c < 5; c++) bulk_g2s(sb + cv_t(c) + KT_E, P.ssm_k + (size_t)(128 * c + b) * SL, 4096, BAR(B_KRAW + (c >= KRAW_N))));
        };
        uint32_t x[16], n = 0;
#pragma unroll 1
        while (true) {
#pragma unroll
          for (int i = 0; i < 4; i++) {
            const uint4 v = ld_relaxed128(P.cs + ((i >> 1) * 8 + j) * 256 + l27 * 8 + (i & 1) * 4);
            x[4 * i] = v.x; x[4 * i + 1] = v.y; x[4 * i + 2] = v.z; x[4 * i + 3] = v.w;
          }
          if (!RAW_LATE && n == 0) raw_load();
          uint32_t bad = 0;
#pragma unroll
          for (int i = 0; i < 16; i++) { x[i] ^= tg; bad |= x[i]; }
          if (__all_sync(0xffffffffu, (bad & 15u) == 0) || spin_guard(n, 0x131)) break;
          RETRY(8);
        }
        if (RAW_LATE) raw_load();
        uint32_t hi[4], lo[4];
#pragma unroll
        for (int i = 0; i < 4; i++) {
          const float x0 = __uint_as_float(x[2 * i]) + __uint_as_float(x[8 + 2 * i]), x1 = __uint_as_float(x[2 * i + 1]) + __uint_as_float(x[9 + 2 * i]);
          hi[i] = pack_bf16(x0, x1); lo[i] = pack_bf16(x0 - bf_lo(hi[i]), x1 - bf_hi(hi[i]));
        }
        sts128(ba, hi[0], hi[1], hi[2], hi[3]); sts128(ba + 64, lo[0], lo[1], lo[2], lo[3]);
        fence_async_smem();
        __syncwarp();
        if (lane < 2) mbar_arrive(BAR(B_BX));
        if (lane == 0) TS(54);
      }
      if (aw < 2) {
        auto done = [&](int r) {
          bulk_wait_read();
          ONE(kv_load(r + 3, aw); TSKV);
        };
        const uint32_t par = lds32(sb + M_AUX + aw * 32 + 20) & 1u;
        bool pend = false;
        mbar_wait(BAR(B_SK), 0);
#pragma unroll 1
        for (int r = 0; r < 5; r++) {
          const int c0 = 128 * r + 64 * (b & 1);
          const uint32_t buf = sb + KVS + (r < 3 ? r : r - 3) * KV_BUF, stg = buf + aw * 2048, vb = stg + lane * 4, kb = buf + 4096 + aw * 2432 + lane * 4;
          const uint4 sk = lds128(sb + M_SK + r * 512 + lane * 16);
          const uint32_t w0 = __byte_perm(sk.x, sk.z, 0x5410), w1 = __byte_perm(sk.x, sk.z, 0x7632);
          const uint32_t w2 = __byte_perm(sk.y, sk.w, 0x5410), w3 = __byte_perm(sk.y, sk.w, 0x7632);
          mbar_wait(BAR((aw ? B_KIN1 : B_KIN) + r), 0);
          if (at == 0 && r == 0) TS(56);
          uint32_t kk[19], o[16];
#pragma unroll
          for (int i = 0; i < 19; i++) { kk[i] = lds32(kb + i * 128); if (i >= 3) o[i - 3] = lds32(vb + (i - 3) * 128); }
#pragma unroll
          for (int i = 0; i < 16; i++) o[i] = bmul2(bfma2(kk[i + 3], w0, bfma2(kk[i + 2], w1, bfma2(kk[i + 1], w2, bmul2(kk[i], w3)))), o[i]);
          __syncwarp();
          const uint32_t a0 = stg + lane * 64 + ((lane & 6) << 3);
          const uint32_t s0 = (lane & 4) ? 0x7632 : 0x5410, s1 = s0 ^ 0x2222;
#pragma unroll
          for (int hh = 0; hh < 2; hh++) {
            const uint32_t* u = o + 8 * hh;
            const uint32_t a = a0 ^ (hh << 4);
            auto nz = [&](uint32_t x) { return hh ? x : (x & ~1u) | par; };
            sts128(a, nz(__byte_perm(u[1], u[0], s0)), __byte_perm(u[3], u[2], s0), __byte_perm(u[5], u[4], s0), __byte_perm(u[7], u[6], s0));
            sts128(a ^ 32, nz(__byte_perm(u[1], u[0], s1)), __byte_perm(u[3], u[2], s1), __byte_perm(u[5], u[4], s1), __byte_perm(u[7], u[6], s1));
          }
          if (pend) done(r - 1);
          fence_async_smem();
          __syncwarp();
          ONE(tma2d_st(&M.kvs, 32 * (b >> 1) + 16 * aw, c0, stg); bulk_commit());
          pend = r < 2 && mbar_test(BAR((aw ? B_KIN1 : B_KIN) + r + 1), 0);
          if (!pend && r < 2) done(r);
        }
      }
      if (aw == 2) {
        mbar_wait(BAR(B_FR + 1), 0);
        ONE(x_load(0));
        x_pad(0, 4);
      }
    }
#pragma unroll 1
    for (uint32_t t = (TB_MAP >> (8 * (warp - 8))) & 255; t & 15; t >>= 4) {
      const int c = (t & 15) - 1;
      mbar_wait(BAR(B_KRAW + (c >= KRAW_N)), 0);
      if (lane == 0 && c == 1) TS(35);
      table(c, max(aw, 0));
      if (lane == 0 && c == 2) TS(55);
    }
    const unsigned ep = lds32(sb + M_AUX + max(aw, 0) * 32 + 20);
    if (warp == 8) {
      const int cf = (nt * 160 + (nt & 1) * 32) >> 6, ch = (nt >> 1) * 320 + 128;
      auto g2_k = [&](int kc) { return (kc < NSH ? kh * NSH + kc : NSH + kc) * 64; };
      auto g2_load_b = [&](int kc) {
        const int s = kc & 3;
        const uint32_t fb = BAR(B_F2 + s);
        mbar_expect(fb, kc >= NSH ? 8192 + 24576 : 16384 + 24576);
        tma3d(sb + g2_b(s), &M.w2, 0, g2_k(kc), cf, fb);
        tma2d(sb + g2_b(s) + 16384, &M.w2x, ch, g2_k(kc), fb);
      };
      auto g2_load_a = [&](int kc) {
        const int s = kc & 3, o = kc >= NSH ? kh : 0;
        tma2d(sb + g2_a(s) + o * 8192, kc >= NSH ? &M.hs : &M.ha, g2_k(kc), rb * 128 + o * 64, BAR(B_F2 + s));
      };
      const int hc = j * 192, hx = 1536 + j * 24;
#pragma unroll 1
      for (int n = 0; n < 32; n += 4) {
        const int i = (H_ORD >> n) & 7, hw = i >> 2, blk = i & 3;
        if (n == 4 * W2_PF) ONE(prefetch_l2(P.w2 + (size_t)b * (FF * DM / NCTA), FF * DM / NCTA * 2));
        mbar_wait(BAR(B_HB + i), 0);
        fence_async_smem();
        asm volatile("cp.async.bulk.wait_group %0;" ::"n"(H_FLY - 1) : "memory");
        ONE(if (n == 4 * (H_FLY + 1)) mbar_arrive(BAR(B_HD));
            tma2d_st(blk < 3 ? &M.hs : &M.hx, blk < 3 ? hc + blk * 64 : hx, rb * 128 + hw * 64, sb + hst(hw) + blk * 8192); bulk_commit());
      }
      bulk_wait_all();
      ONE(mbar_arrive(BAR(B_HD + 1)); TS(52));
      fence_release();
      ONE(signal_cnt(P.cnt + rb * 32); TS(37); g2_load_b(0); g2_load_b(1));
      wait_cnt(P.cnt + rb * 32, 8 * ep);
      ONE(TS(39); g2_load_a(0); g2_load_a(1); prefetch_map(&M.qf); prefetch_map(&M.y); prefetch_map(&M.out));
      mbar_wait(BAR(B_KD), 0);
      ONE(g2_load_b(3));
      mbar_wait(BAR(B_TD + 1), 0);
      fence_async_smem();
      ONE(g2_load_b(2); g2_load_a(2));
      mbar_wait(BAR(B_SD + 3), 0);
      ONE(mbar_expect(BAR(B_FINQ), 20480);
          for (int i = 0; i < 5; i++) tma2d(sb + FIN_Q + i * 4096, &M.qf, nt * 160 + ((gmap >> (4 * i)) & 7) * 32, rb * 128 + kh * 64, BAR(B_FINQ)));
      mbar_wait(BAR(B_RF + 2), 0);
      ONE(g2_load_a(3); TS(38));
#pragma unroll 1
      for (int kc = 4; kc < NST; kc++) {
        mbar_wait(BAR(B_E2 + (kc & 3)), ((kc >> 2) - 1) & 1);
                ONE(g2_load_a(kc); g2_load_b(kc); if (kc >= Y_KC && kc < Y_KC + 3) mbar_arrive(BAR(B_YSLOT + kc - Y_KC)));
      }
      if (lane == 0) P.launch[b * 8] = ep;
#pragma unroll 1
      for (int i = 0; i < 5; i++) {
        const int gi = (gmap >> (4 * i)) & 7;
        mbar_wait(BAR(B_OUT + i), 0);
        fence_async_smem();
        ONE(tma2d_st(&M.out, nt * 160 + gi * 32, rb * 128 + kh * 64, sb + FIN_Q + i * 4096));
      }
      ONE(bulk_commit());
      bulk_wait_read();
    } else {
      if (aw < 2) { bulk_wait_read(); __syncwarp(); if (lane < 2) mbar_arrive(BAR(B_KD)); if (at == 0) TS(34); }
      if (aw == 2) {
#pragma unroll 1
        for (int c = 0, n = 0; c < 5;) {
          if (n == 0 && c < 4) {
            mbar_wait(BAR((X_TRIG >> (8 * c)) & 255), 0);
            if (c == 3) { mbar_wait(BAR(B_KD), 0); x_pad(4, 5); }
          }
          if (n || c < 4) ONE(x_load(n ? c : c + 1));
          mbar_wait(BAR(B_XL + c), n & 1);
          const uint32_t a = sb + cv_x(c) + XD + lane * 32;
          const uint32_t v = ((lds32(a) ^ ep) | (lds32(a + 1024) ^ ep) | (lds32(a + 2048) ^ ep) | (lds32(a + 3072) ^ ep)) & 1u;
          if (__all_sync(0xffffffffu, v == 0) || n > 100000) {
            ONE(mbar_arrive(BAR(B_XF + c)); if (c == 0) TS(36); if (c >= 3) TS(28 + c));
            c++; n = 0;
          } else {
            n++;
            RETRY(c);
          }
        }
      }
      if (RED_GATE) mbar_wait(BAR(RED_GATE == 1 ? B_TD + 1 : B_SD + RED_GATE - 1), 0);
#pragma unroll 1
      for (int c = 0; c < 5; c++) {
        mbar_wait(BAR(B_SD + c), 0);
        conv_sum(c, aw * 96 + lane, aw < 2, ep);
        __syncwarp();
        if (c < 3 && lane < 3 - (aw >> 1)) mbar_arrive(BAR(B_RF + c));
        if (at == 0) TS(59 + c);
      }
      bar_sync(NB_AUX, 96);
      if (aw == 0) ONE(mbar_arrive_remote(mapa(BAR(B_XR), kh ^ 1)); TS(3));
      auto ytab = [](int a) { return (uint32_t)(fin_y(3 * a) >> 10 | fin_y(3 * a + 1) >> 10 << 8 | fin_y(3 * a + 2) >> 10 << 16 | fin_y(a == 2 ? 9 : 3 * a) >> 10 << 24); };
      const uint32_t yt = aw == 0 ? ytab(0) : (aw == 1 ? ytab(1) : ytab(2));
      mbar_wait(BAR(B_YSLOT + ((Y_MAP >> (4 * aw)) & 3)), 0);
#pragma unroll 1
      for (int n = 0;; n++) {
        ONE(mbar_expect(BAR(B_YL + aw), aw == 2 ? 8192 : 6144));
#pragma unroll 1
        for (int i = 0; i < (aw == 2 ? 4 : 3); i++) {
          const int np = 3 * aw + i;
          ONE(tma2d(sb + (((yt >> (8 * i)) & 255) << 10), &M.y, rb * 128 + kh * 64, nt * 160 + ((gmap >> (4 * (np >> 1))) & 7) * 32 + (np & 1) * 16, BAR(B_YL + aw)));
        }
        mbar_wait(BAR(B_YL + aw), n & 1);
        uint32_t bad = 0;
#pragma unroll
        for (int i = 0; i < 4; i++) {
          const uint32_t a = sb + (((yt >> (8 * i)) & 255) << 10) + (lane >> 2) * 128 + ((((lane & 3) * 2) ^ (lane >> 2)) << 4);
          bad |= (lds32(a) ^ ep) | (lds32(a + 1024) ^ ep);
        }
        if (__all_sync(0xffffffffu, (bad & 1u) == 0) || n > 100000) break;
        RETRY(5 + aw);
        if (lane == 0) TS(33);
      }
      if (lane <= (aw >> 1)) mbar_arrive(BAR(B_FINY));
      if (at == 64) TS(40);
    }
  } else {
    const int wg = warp >> 2, w = warp & 3, g = lane >> 2, q = lane & 3;
    constexpr bool elect = false;
    uint32_t ca[64];
    const uint32_t ab0 = sb + ((g & 1) ? KT_E : KT_O) + (8 * w + 4 + (g >> 1) - q) * 4;
    auto conv_lda = [&](uint32_t ab, int k0, int k1) {
#pragma unroll
      for (int ks = 15; ks >= 0; ks--) {
        if (ks >= k0 && ks < k1) {
          ca[4 * ks + 0] = lds32(ab + ks * 256);
          ca[4 * ks + 1] = lds32(ab + ks * 256 + 128);
          ca[4 * ks + 2] = lds32(ab + ks * 256 - 16);
          ca[4 * ks + 3] = lds32(ab + ks * 256 + 112);
        }
      }
    };
    {
      float d[108];
      auto g1_release = [&](int kc) { if (lane == 0) mbar_arrive(BAR(kc < 6 ? B_E1 + (kc & 3) : B_FR + kc - 6)); };
      auto g1_wait = [&](int kc) { mbar_wait(BAR(B_F1 + (kc & 3)), (kc >> 2) & 1); };
      auto g1_issue = [&](int kc) {
        const int s = kc & 3;
        if (tid == 0) TS(8 + kc);
        const uint32_t st = sc + s * G1_STAGE;
        const uint64_t da = mkdesc(st + wg * 8192, 16, 1024, 1), db = mkdesc(st + 16384, 8192, 1024, 1);
        wg_fence();
#pragma unroll
        for (int k = 0; k < 4; k++) {
          wg_ss_216(d, da + k * 2, db + k * 128, (kc | k) != 0);
          if (k == REL_K || k == 3) wg_commit();
          if (k == REL_K) { wg_wait<1>(); if (kc > 0) g1_release(kc - 1); }
        }
      };
      const int t7 = tid & 127, wr = ((t7 >> 3) & 1) * 4 + (t7 >> 4) * 8, wc = 4 * min(ci, 6) + ((t7 >> 1) & 3);
      const uint32_t sa0 = sb + (wg ? 16384 + (wc >> 3) * 8192 + wr * 128 + (((wc ^ wr) & 7) << 4) + (t7 & 1) * 8 : ri * 4096 + t7 * 16);
      float t1 = 0.f, t2 = 0.f, t3 = 0.f, t4 = 0.f;
      auto piece = [&](int i) {
        const uint32_t so = (i & 3) * G1_STAGE;
        if (wg == 0) {
          const uint4 x = lds128(sa0 + so), y = lds128(sa0 + so + 2048);
          const uint32_t xx[4] = {x.x, x.y, x.z, x.w}, yy[4] = {y.x, y.y, y.z, y.w};
#pragma unroll
          for (int e = 0; e < 4; e++) {
            const float u = bf_lo(xx[e]), v = bf_hi(xx[e]), r = bf_lo(yy[e]), z = bf_hi(yy[e]);
            t1 += u; t2 = fmaf(u, u, t2); t3 += r; t4 = fmaf(r, r, t4);
            t1 += v; t2 = fmaf(v, v, t2); t3 += z; t4 = fmaf(z, z, t4);
          }
        } else {
          float2 xx[4];
#pragma unroll
          for (int e = 0; e < 4; e++) xx[e] = lds64f((sa0 ^ (e * 144)) + so);
#pragma unroll
          for (int e = 0; e < 4; e++) {
            const uint32_t u = __float_as_uint(xx[e].x), v = __float_as_uint(xx[e].y);
            t1 += bf_lo(u); t2 += bf_hi(u); t3 += bf_lo(v); t4 += bf_hi(v);
          }
        }
      };
      const int mi = lane >> 3, row = w * 16 + (mi & 1) * 8 + (lane & 7);
      uint32_t ha[4], hx = sb + hst(wg) + 24576 + row * 48 + (mi >> 1) * 16, hb = BAR(B_HB + wg * 4), aw0 = ab0 + cv_t(wg);
#pragma unroll
      for (int i = 0; i < 4; i++) ha[i] = sb + hst(wg) + row * 128 + (((2 * i + (mi >> 1)) ^ (row & 7)) << 4);
      keep(ha[0]); keep(ha[1]); keep(ha[2]); keep(ha[3]); keep(hx); keep(hb); keep(aw0);
      if (wg == 1) { g1_wait(0); bar_sync(NB_LEAD, 256); }
      mbar_wait(BAR(B_F0), 0);
#pragma unroll G1_UNROLL
      for (int kc = 0; kc < 6; kc++) {
        g1_issue(kc);
        if (kc == 0 && wg == 0) bar_arrive(NB_LEAD, 256);
        if (kc >= 2 || kc == dir) { g1_wait(kc); piece(kc); }
        if (kc < 5) g1_wait(kc + 1);
      }
      sts128(sb + (wg ? M_RED1 : M_RED0) + t7 * 16, __float_as_uint(t1), __float_as_uint(t2), __float_as_uint(t3), __float_as_uint(t4));
      __syncwarp();
      if (lane == 0) mbar_arrive(BAR(wg ? B_RED1 : B_RED));
      asm volatile("setmaxnreg.inc.sync.aligned.u32 " REG_CON ";");
#pragma unroll G1_UNROLL
      for (int kc = 6; kc < 10; kc++) {
        g1_wait(kc);
        if (kc == STAG_KC && wg == 1) mbar_wait(BAR(B_LNI), 0);
        g1_issue(kc);
      }
      uint2 s0, s1;
      {
        mbar_wait(BAR(B_BX), 0);
        s0.x = lds32(sb + M_STAT + (wg * 64 + w * 16 + g) * 4); s1.x = lds32(sb + M_STAT + (wg * 64 + w * 16 + g + 8) * 4);
        if (tid == 0) TS(46);
        const uint32_t f0 = q == 0 ? ((s0.x & 0xFFFFu) * 0x10001u) ^ 0x80008000u : (q == 1 ? s0.x ^ 0x8000u : 0u);
        const uint32_t f1 = q == 0 ? ((s1.x & 0xFFFFu) * 0x10001u) ^ 0x80008000u : (q == 1 ? s1.x ^ 0x8000u : 0u);
        wg_fence();
        wg_rs_216(d, f0, f1, 0u, 0u, mkdesc(sc + M_BX, 512, 0, 2));
        wg_commit();
        if (wg == 0 && lane == 0) mbar_arrive(BAR(B_LNI));
      }
      wg_wait<1>();
      if (lane == 0) mbar_arrive(BAR(B_FR + 3));
      const float r0 = rcp_fast(bf_hi(s0.x)), r1 = rcp_fast(bf_hi(s1.x));
      constexpr float C1 = 0.7978845608028654f, C2 = 0.7978845608028654f * 0.044715f;
      const float ga0 = C1 * r0, gb0 = C2 * r0 * r0 * r0, ga1 = C1 * r1, gb1 = C2 * r1 * r1 * r1;
      if (wg == 0) mbar_wait(BAR(B_FR + STAG_KC - 7), 0);
      wg_wait<0>();
      if (elect) TS(1 + 47 * wg);
      if (wg == 1) bar_sync(NB_GELU, 256);
      sched_fence(sb);
      float u[2][8];
#pragma unroll
      for (int st = -1; st < 15; st++) {
        const int nb = 2 * (st - 1);
        if (st >= 1) {
          uint32_t p[4];
#pragma unroll
          for (int e = 0; e < (nb < 26 ? 4 : 2); e++) {
            const float x = d[4 * nb + 2 * e], y = d[4 * nb + 2 * e + 1];
            p[e] = pack_bf16(fmaf(x, u[(st - 1) & 1][2 * e], x), fmaf(y, u[(st - 1) & 1][2 * e + 1], y));
          }
          if (nb < 24) stsm4(ha[(nb >> 1) & 3] + (nb >> 3) * 8192, p[0], p[1], p[2], p[3]);
          else if (nb == 24) stsm4(hx, p[0], p[1], p[2], p[3]);
          else stsm2(hx + 32, p[0], p[1]);
          if ((nb & 7) == 6 || nb == 26) {
            __syncwarp();
            if (lane == 0) mbar_arrive(hb + 8 * (nb >> 3));
          }
        }
        if (st >= 0 && st < 14) {
#pragma unroll
          for (int i = 0; i < (st < 13 ? 8 : 4); i++) u[st & 1][i] = tanh_fast(u[st & 1][i]);
        }
        if (st + 1 < 14) {
#pragma unroll
          for (int i = 0; i < (st + 1 < 13 ? 8 : 4); i++) {
            const float x = d[8 * (st + 1) + i];
            u[(st + 1) & 1][i] = x * fmaf(x * ((i & 2) ? gb1 : gb0), x, (i & 2) ? ga1 : ga0);
          }
        }
        constexpr int S0 = A_NB0 / 2, NK = CV_OWN ? 16 - CV_RELOADED : 16;
        if (st >= S0 && st < 14) conv_lda(aw0, 16 - (st + 1 - S0) * NK / (14 - S0), 16 - (st - S0) * NK / (14 - S0));
        if (2 * st == GELU_NB && wg == 0) bar_arrive(NB_GELU, 256);
        if (st + 1 == S0) mbar_wait(BAR(B_KT + wg), 0); else if (st < 14 && (st + 1) % SCH == 0) sched_fence(sb);
      }
      if (elect) TS(2 + 47 * wg);
    }
#pragma unroll 1
    for (int c = wg; c < 5; c += 2) {
      float d[128];
      mbar_wait(BAR(B_XF + c), 0);
      if (c < 3) mbar_wait(BAR(B_KT + c + 2), 0);
      const uint64_t db = mkdesc(sc + cv_x(c), 16, 128, 0);
      if (c > 0) { if (wg) bar_sync(NB_TURN + 1, 256); else bar_sync(NB_TURN, 256); }
      wg_fence();
      auto hand = [&]() { if (wg) bar_arrive(NB_TURN, 256); else if (c < 4 || !HAND4) bar_arrive(NB_TURN + 1, 256); };
      const uint32_t ao = ab0 + cv_t(c);
      if (c < 3) conv_chain_1(d, ca, db, ao, ao + 2 * KT_CH, hand, []() {});
      else conv_chain_0(d, ca, db, ao, 0, hand, [&]() { if (lane == 0) mbar_arrive(BAR(B_TD + 1)); });
      if (c == 4 && HAND4) bar_arrive(NB_TURN + 1, 256);
      mbar_wait(BAR(c >= 3 ? B_RF + c - 3 : (c ? B_HD + c - 1 : B_FR + 3)), 0);
      wg_wait<0>();
      if (elect) TS(41 + c);
      if (c < 3 && !CV_OWN) conv_lda(ao + 2 * KT_CH, 0, CV_RELOADED);
      const uint32_t wa = sb + cv_p(c) + w * 4096 + lane * 16;
#pragma unroll
      for (int n4 = 0; n4 < 32; n4 += 4) {
        uint32_t p[4];
#pragma unroll
        for (int e = 0; e < 4; e++) {
          const int nb = n4 + e;
          float x = d[4 * nb], y = d[4 * nb + 1];
          if (nb > 0) { x += d[4 * nb - 2]; y += d[4 * nb - 1]; }
          p[e] = pack_bf16(x, y);
        }
        stsm4t(wa + n4 * 128, p[0], p[1], p[2], p[3]);
      }
      __syncwarp();
      if (lane == 0) mbar_arrive(BAR(B_SD + c));
    }
    if (tid == 0) TS(51);
    {
      float d[80];
      const uint32_t aoff = (wg ^ kh) * 8192;
      const uint64_t boff = (uint64_t)(nt & 1) << 51;
      const uint32_t s0 = lds32(sb + M_STAT + ((wg ^ kh) * 64 + w * 16 + g) * 4), s1 = lds32(sb + M_STAT + ((wg ^ kh) * 64 + w * 16 + g + 8) * 4);
      auto g2_release = [&](int kc) { if (lane == 0) mbar_arrive(BAR(B_E2 + (kc & 3))); };
      auto g2_mma_w = [&](int kc, int first, bool rel, auto side) {
        const int s = kc & 3;
        mbar_wait(BAR(B_F2 + s), (kc >> 2) & 1);
        const uint64_t da = mkdesc(sc + g2_a(s) + aoff, 16, 1024, 1), db = mkdesc(sc + g2_b(s), 8192, 1024, 1) | boff;
        wg_fence();
#pragma unroll
        for (int k = 0; k < 4; k++) {
          wg_ss_160(d, da + k * 2, db + k * 128, k ? 1 : first);
          if ((k == REL_K && rel) || k == 3) wg_commit();
          if (k == REL_K && rel) { wg_wait<1>(); g2_release(kc - 1); }
          side(k);
        }
      };
      auto g2_mma = [&](int kc, int first, bool rel) { g2_mma_w(kc, first, rel, [](int) {}); };
      sched_fence(sb);
      if (wg == 1) bar_sync(NB_TURN + 1, 256);
      g2_mma(0, 0, false);
      if (wg == 0) bar_arrive(NB_LEAD, 256);
#pragma unroll
      for (int kc = 1; kc < XP_KC; kc++) {
        if (tid == 0) TS(17 + kc);
        if (kc == LEAD_KC && wg == 1) bar_sync(NB_LEAD, 256);
        g2_mma(kc, 1, true);
      }
      if (wg == 1) {
        float bi[40];
#pragma unroll
        for (int nb = 0; nb < 20; nb++) { const float2 v = lds64f(sb + M_B2 + nb * 32 + q * 8); bi[2 * nb] = v.x; bi[2 * nb + 1] = v.y; }
        const float c0 = 0.25f * rcp_fast(bf_hi(s0)), c1 = 0.25f * rcp_fast(bf_hi(s1));
#pragma unroll
        for (int kc = XP_KC; kc < NSH; kc++) {
          g2_mma(kc, 1, kc < NST - 3);
          if (kc == END_KC) bar_arrive(NB_END, 256);
        }
        mbar_wait(BAR(B_XR), 0);
        wg_wait<0>();
#pragma unroll
        for (int kc = NSH - 1; kc < NST - 4; kc++) g2_release(kc);
        if (elect) TS(53);
        const uint32_t ra = mapa(sb, kh ^ 1), rbar = ra + M_BAR + 8 * B_XD, dst = ra + (tid & 127) * 16;
#pragma unroll
        for (int i = 0; i < 10; i++) {
          const float *dd = d + 8 * i, *bb = bi + 4 * i;
          st_async128(dst + (i < 5 ? P0 + i * 2048 : P1 + (i - 5) * 2048), pack_bf16(fmaf(dd[0], c0, bb[0]), fmaf(dd[1], c0, bb[1])), pack_bf16(fmaf(dd[2], c1, bb[0]), fmaf(dd[3], c1, bb[1])),
                      pack_bf16(fmaf(dd[4], c0, bb[2]), fmaf(dd[5], c0, bb[3])), pack_bf16(fmaf(dd[6], c1, bb[2]), fmaf(dd[7], c1, bb[3])), rbar + 8 * ((i >= XD_N) + (i >= XD_M)));
          sched_fence(sb);
        }
        if (elect) TS(7);
      } else {
        const int mi = lane >> 3, row = (mi & 1) * 8 + (lane & 7);
        const uint32_t qa = sb + FIN_Q + (w * 16 + row) * 64 + (((mi >> 1) ^ ((row >> 1) & 3)) << 4), qb = qa ^ 32;
        auto q_addr = [&](int np) { return ((np & 1) ? qb : qa) + (np >> 1) * 4096; };
        uint32_t sv[40], xq[40];
        const uint32_t m0 = (s0 & 0xFFFFu) * 0x10001u, m1 = (s1 & 0xFFFFu) * 0x10001u;
        float rs0 = rcp_fast(bf_hi(s0)), rs1 = rcp_fast(bf_hi(s1));
        const uint32_t rh0 = pack_bf16(rs0, rs0), rh1 = pack_bf16(rs1, rs1);
        const uint32_t rl0 = pack_bf16(rs0 - bf_lo(rh0), rs0 - bf_lo(rh0)), rl1 = pack_bf16(rs1 - bf_lo(rh1), rs1 - bf_lo(rh1));
#pragma unroll
        for (int kc = XP_KC; kc < 10; kc++) {
          if (tid == 0) TS(17 + kc);
          g2_mma(kc, 1, true);
          if (kc >= XP_KC && XP_KC < 10) {
            mbar_wait(BAR(B_FINQ), 0);
#pragma unroll
            for (int np = 10 * (kc - XP_KC) / (XP_KC < 10 ? 10 - XP_KC : 1); np < 10 * (kc + 1 - XP_KC) / (XP_KC < 10 ? 10 - XP_KC : 1); np++) {
              ldsm4(q_addr(np), xq[4 * np], xq[4 * np + 1], xq[4 * np + 2], xq[4 * np + 3]);
#pragma unroll
              for (int e = 0; e < 4; e++) {
                const uint32_t dm = bsub2(xq[4 * np + e], (e & 1) ? m1 : m0);
                sv[4 * np + e] = bfma2(dm, (e & 1) ? rh1 : rh0, bmul2(dm, (e & 1) ? rl1 : rl0));
              }
            }
          }
        }
        const uint32_t ya = sb + (mi >> 1) * 1024 + (lane & 7) * 128 + (((2 * w + (mi & 1)) ^ (lane & 7)) << 4);
        uint32_t y[3][4];
        auto y_step = [&](int i) {
          if (i < 0 || i >= 12) return;
          if (i >= 2) {
#pragma unroll
            for (int e = 0; e < 4; e++) asm volatile("mul.rn.bf16x2 %0, %0, %1;" : "+r"(sv[4 * (i - 2) + e]) : "r"(y[(i - 2) % 3][e]));
          }
          if (i < 10) ldsm4t(ya + fin_y(i), y[i % 3][0], y[i % 3][1], y[i % 3][2], y[i % 3][3]);
          if (YFENCE) sched_fence(sb);
        };
        rs0 *= 0.25f; rs1 *= 0.25f;
        if (tid == 0) TS(27);
#pragma unroll
        for (int kc = 9; kc < NST; kc++) {
          if (kc == YP_KC) mbar_wait(BAR(B_FINY), 0);
          if (kc > 9) g2_mma_w(kc, 1, kc < NST - 3 && kc != HOLD_KC + 1, [&](int k) { y_step(4 * (kc - YP_KC) + k); });
          if (kc == HOLD_KC) {
            if (kc < NST - 4) { wg_wait<0>(); g2_release(kc); }
            if (tid == 0) TS(28);
            bar_sync(NB_END, 256);
          }
        }
        if (tid == 0) TS(29);
#pragma unroll
        for (int i = 4 * (NST - YP_KC); i < 12; i++) y_step(i);
        if (tid == 0) TS(47);
        mbar_wait(BAR(B_XD), 0);
        if (tid == 0) TS(5);
        uint4 v[10];
        auto ld_v = [&](int n0, int n1) {
#pragma unroll
          for (int i = n0; i < n1; i++) v[i] = lds128(sb + tid * 16 + (i < 5 ? P0 + i * 2048 : P1 + (i - 5) * 2048));
        };
        ld_v(0, XD_N);
        wg_wait<0>();
        if (tid == 0) TS(4);
        float t[2][8];
#pragma unroll
        for (int st = -1; st < 11; st++) {
          if (st == XD_N - 3) { mbar_wait(BAR(B_XD + 1), 0); ld_v(XD_N, XD_M); }
          if (st == XD_M - 3) { mbar_wait(BAR(B_XD + 2), 0); ld_v(XD_M, 10); }
          if (st >= 1) {
            const int np = st - 1;
            uint32_t o[4];
#pragma unroll
            for (int e = 0; e < 4; e++) {
              const float h0 = d[8 * np + 2 * e], h1 = d[8 * np + 2 * e + 1];
              o[e] = bfma2(sv[4 * np + e], pack_bf16(fmaf(h0, t[np & 1][2 * e], h0), fmaf(h1, t[np & 1][2 * e + 1], h1)), xq[4 * np + e]);
            }
            stsm4(q_addr(np), o[0], o[1], o[2], o[3]);
            if (np & 1) {
              if (np == 9 && tid == 0) TS(50);
              __syncwarp();
              if (lane == 0) mbar_arrive(BAR(B_OUT + (np >> 1)));
            }
          }
          if (st >= 0 && st < 10) {
#pragma unroll
            for (int i = 0; i < 8; i++) t[st & 1][i] = tanh_fast(d[8 * st + i]);
          }
          if (st + 1 < 10) {
            const int np = st + 1;
            const uint32_t pw[4] = {v[np].x, v[np].y, v[np].z, v[np].w};
#pragma unroll
            for (int e = 0; e < 4; e++) {
              d[8 * np + 2 * e] = fmaf(d[8 * np + 2 * e], (e & 1) ? rs1 : rs0, bf_lo(pw[e]));
              d[8 * np + 2 * e + 1] = fmaf(d[8 * np + 2 * e + 1], (e & 1) ? rs1 : rs0, bf_hi(pw[e]));
            }
          }
          if (SCH2 && (st + 1) % (SCH2 ? SCH2 : 1) == 0) sched_fence(sb);
        }
      }
    }
  }
}

typedef CUresult (*EncFn)(CUtensorMap*, CUtensorMapDataType, cuuint32_t, void*, const cuuint64_t*, const cuuint64_t*, const cuuint32_t*, const cuuint32_t*,
                          CUtensorMapInterleave, CUtensorMapSwizzle, CUtensorMapL2promotion, CUtensorMapFloatOOBfill);

static void make_map(EncFn enc, CUtensorMap* tm, const void* ptr, int cols, int rows, int bc, int br, int grp, CUtensorMapSwizzle sw,
                     CUtensorMapL2promotion promo = CU_TENSOR_MAP_L2_PROMOTION_NONE) {
  cuuint64_t gd[3] = {(cuuint64_t)(grp ? bc : cols), (cuuint64_t)rows, (cuuint64_t)(cols / bc)};
  cuuint64_t gs[2] = {(cuuint64_t)cols * 2, (cuuint64_t)bc * 2};
  cuuint32_t bd[3] = {(cuuint32_t)bc, (cuuint32_t)br, (cuuint32_t)grp};
  cuuint32_t es[3] = {1, 1, 1};
  CUresult r = enc(tm, CU_TENSOR_MAP_DATA_TYPE_BFLOAT16, grp ? 3 : 2, const_cast<void*>(ptr), gd, gs, bd, es, CU_TENSOR_MAP_INTERLEAVE_NONE, sw,
                   promo, CU_TENSOR_MAP_FLOAT_OOB_FILL_NONE);
  (void)r;
}

}

extern "C" void kernel_launch(void* const* d_in, const int* in_sizes, int n_in, void* d_out, int out_size) {
  using namespace h3;
  (void)in_sizes; (void)n_in; (void)out_size;
  static EncFn enc = nullptr;
  static void *p_h, *p_yT, *p_kvT, *p_stat, *p_cs, *p_cnt, *p_launch;
  if (!enc) {
    void* fn = nullptr; cudaDriverEntryPointQueryResult qr;
    cudaGetDriverEntryPoint("cuTensorMapEncodeTiled", &fn, cudaEnableDefault, &qr);
    enc = (EncFn)fn;
    cudaGetSymbolAddress(&p_h, g_h); cudaGetSymbolAddress(&p_yT, g_yT); cudaGetSymbolAddress(&p_kvT, g_kvT); cudaGetSymbolAddress(&p_stat, g_stat);
    cudaGetSymbolAddress(&p_cs, g_cs); cudaGetSymbolAddress(&p_cnt, g_cnt); cudaGetSymbolAddress(&p_launch, g_launch);
    cudaFuncSetAttribute(h3_kernel, cudaFuncAttributeMaxDynamicSharedMemorySize, SMEM_BYTES);
  }
  const void *q = d_in[0], *k = d_in[1], *v = d_in[2], *w1 = d_in[7];
  Params P;
  P.q = (const __nv_bfloat16*)q; P.w1 = (const __nv_bfloat16*)w1;
  P.shift_k = (const __nv_bfloat16*)d_in[3]; P.ssm_k = (const __nv_bfloat16*)d_in[4]; P.ssm_D = (const __nv_bfloat16*)d_in[5];
  P.b1 = (const __nv_bfloat16*)d_in[8]; P.w2 = (const __nv_bfloat16*)d_in[9]; P.b2 = (const __nv_bfloat16*)d_in[10];
  P.kvT = (__nv_bfloat16*)p_kvT; P.yT = (__nv_bfloat16*)p_yT; P.stat = (uint2*)p_stat;
  P.cs = (uint32_t*)p_cs; P.cnt = (uint32_t*)p_cnt; P.launch = (uint32_t*)p_launch;
  const CUtensorMapSwizzle S128 = CU_TENSOR_MAP_SWIZZLE_128B, S64 = CU_TENSOR_MAP_SWIZZLE_64B, S0 = CU_TENSOR_MAP_SWIZZLE_NONE;
  Maps M;
  make_map(enc, &M.q0, q, DM, SL, 64, 64, 0, S128);
  make_map(enc, &M.w1, w1, FF, DM, 64, 64, 3, S128);
  make_map(enc, &M.w1x, w1, FF, DM, 24, 64, 0, S128, WS_PROMO);
  make_map(enc, &M.k, k, DM, SL, 64, 19, 0, S0);
  make_map(enc, &M.v, v, DM, SL, 64, 16, 0, S0);
  make_map(enc, &M.hs, p_h, FF, SL, 64, 64, 0, S128);
  make_map(enc, &M.hx, p_h, FF, SL, 24, 64, 0, S0);
  make_map(enc, &M.ha, p_h, FF, SL, 64, 128, 0, S128);
  make_map(enc, &M.w2, P.w2, DM, FF, 64, 64, 2, S128);
  make_map(enc, &M.w2x, P.w2, DM, FF, 64, 64, 0, S128);
  make_map(enc, &M.kvs, p_kvT, SL, DM, 16, 64, 0, CU_TENSOR_MAP_SWIZZLE_32B);
  make_map(enc, &M.qf, q, DM, SL, 32, 64, 0, S64);
  make_map(enc, &M.y, p_yT, SL, DM, 64, 16, 0, S128);
  make_map(enc, &M.out, d_out, DM, SL, 32, 64, 0, S64);
  h3_kernel<<<NCTA, 384, SMEM_BYTES>>>(P, M);
}
```
